```python
import torch

def _softmax(x, axis=-1):
    return torch.softmax(x, dim=axis)
def _gelu(x):
    return torch.nn.functional.gelu(x, approximate="tanh")
def _silu(x):
    return torch.nn.functional.silu(x)
def _sigmoid(x):
    return torch.sigmoid(x)
def _layernorm(x, axis=-1, eps=1e-5):
    m = x.mean(dim=axis, keepdim=True)
    v = x.var(dim=axis, keepdim=True, unbiased=False)
    return (x - m) / torch.sqrt(v + eps)
def _scatter_add(tgt, idx, src, axis=0):
    return tgt.clone().index_add_(axis, idx, src)
def _segment_sum(src, seg, n):
    out = torch.zeros((n,) + src.shape[1:], dtype=src.dtype)
    return out.index_add_(0, seg, src)
def _pad(x, pw):
    flat = tuple(v for pair in reversed(pw) for v in pair)
    return torch.nn.functional.pad(x, flat)

kernel_name = 'standalone__edge_featured_mpnn_gatedgcn__graph'

def setup_inputs():

    _w = (lambda a: (lambda t: t.to(torch.bfloat16) if t.is_floating_point() else t)(torch.as_tensor(a)))
    N, deg, D, De = 50000, 16, 64, max(16, 1)
    E = N * deg
    return {
        "x": _w((lambda *s: torch.randn(*s, dtype=torch.bfloat16) * 0.4)(N, D)),
        "e_attr": _w((lambda *s: torch.randn(*s, dtype=torch.bfloat16) * 0.8)(E, De)),
        "src": _w((lambda lo, hi, *s: torch.randint(lo, hi, s))(0, N, E).to(torch.int64)),
        "dst": _w((lambda lo, hi, *s: torch.randint(lo, hi, s))(0, N, E).to(torch.int64)),
        "w_a": _w((lambda *s: torch.randn(*s, dtype=torch.bfloat16) * 0.8)(D, D)),
        "w_b": _w((lambda *s: torch.randn(*s, dtype=torch.bfloat16) * 0.4)(D, D)),
        "w_c": _w((lambda *s: torch.randn(*s, dtype=torch.bfloat16) * 0.8)(De, D)),
        "w_u": _w((lambda *s: torch.randn(*s, dtype=torch.bfloat16) * 0.05)(D, D)),
        "w_v": _w((lambda *s: torch.randn(*s, dtype=torch.bfloat16) * 0.05)(D, D)),
    }

def reference(x, e_attr, src, dst, w_a, w_b, w_c, w_u, w_v):
    N, D = x.shape
    hv = x @ w_v
    g = x[dst] @ w_a + x[src] @ w_b + e_attr @ w_c
    eta = _sigmoid(g)
    denom = _segment_sum(eta, dst, N) + 1e-6
    eta_n = eta / denom[dst]
    agg = _segment_sum(eta_n * hv[src], dst, N)
    z = x @ w_u + agg
    relu_z = torch.where(z > 0, z, 0 * z)
    return x + relu_z
```

```cpp
#include <cuda_runtime.h>
#include <cuda.h>
#include <cuda_bf16.h>
#include <stdint.h>

#define PACE 16
#define PACE_E 16
#define MIX 0
#define ORDX 2
#define T1W 0
#define SKIP 1
#define XPF 0
#define WV -2
#define PRE 1
#define TOFF 128
#define G2 0
#define DEC1 0
#define P1T 448
#define P2L 0
#define MINV 0
#define XDEP0 0
#define XA 2
#define XDEP 6
#define XALL 0
#define XT 448
#define DBL 1
namespace {

constexpr int N_MAX = 65536;
constexpr int NPMAX = 11;
constexpr int THREADS = 512;
constexpr int EPT = 12;
constexpr int CH_MAX = THREADS * EPT;
constexpr int NB_MAX = 134;
constexpr int GAL = 128;
constexpr int CE = 64;
constexpr int P1B = (256 + NB_MAX * CE * 2 + GAL - 1) / GAL * GAL;
constexpr int P2B = (256 + NB_MAX * CE * 4 + GAL - 1) / GAL * GAL;
constexpr int NPB_MAX = 384;
constexpr int SLOT_CAP = 6784;
constexpr int TILE_CAP = 124;
constexpr int TILE_X = 8;
constexpr int NCLS = 64;
constexpr int XCAP = 128;
constexpr int NSTAGE = 2;
constexpr int TR = 2;
constexpr float LOG2E = 1.4426950408889634f;

__device__ __align__(128) uint4 g_str[NB_MAX * (P1B + P2B) / 16];
__device__ __align__(128) unsigned g_bar[64];
__device__ float g_slow[N_MAX * 128];

#define WS(k)
#define WGD()
#define WSL(k)
#define WSG(k)
#define WG0()
#define WG1()
#define SMEM_LAUNCH SMEM_BYTES
#define FORCE64 0
#define EDHI ((16ull << 32) | (3ull << 62))
template<int NP> struct TileMMA;
template<> struct TileMMA<1> {
  static __device__ __forceinline__ void issue(float* g, float* h, const uint32_t* w, uint64_t dx, uint64_t de, uint64_t dh, uint64_t dc) {
    asm volatile(
      "{\n.reg .b64 dx1, dx2, dx3;\n"
      "add.s64 dx1, %48, 2;\nadd.s64 dx2, %48, 4;\nadd.s64 dx3, %48, 6;\n"
      "wgmma.fence.sync.aligned;\n"
      "wgmma.mma_async.sync.aligned.m64n8k16.f32.bf16.bf16 {%0, %1, %2, %3}, {%44, %45, %46, %47}, %50, 0, 1, 1, 0;\n"
      "wgmma.mma_async.sync.aligned.m64n8k16.f32.bf16.bf16 {%0, %1, %2, %3}, {%24, %25, %26, %27}, %49, 1, 1, 1, 0;\n"
      "wgmma.mma_async.sync.aligned.m64n8k16.f32.bf16.bf16 {%0, %1, %2, %3}, {%8, %9, %10, %11}, %48, 1, 1, 1, 0;\n"
      "wgmma.mma_async.sync.aligned.m64n8k16.f32.bf16.bf16 {%0, %1, %2, %3}, {%12, %13, %14, %15}, dx1, 1, 1, 1, 0;\n"
      "wgmma.mma_async.sync.aligned.m64n8k16.f32.bf16.bf16 {%0, %1, %2, %3}, {%16, %17, %18, %19}, dx2, 1, 1, 1, 0;\n"
      "wgmma.mma_async.sync.aligned.m64n8k16.f32.bf16.bf16 {%0, %1, %2, %3}, {%20, %21, %22, %23}, dx3, 1, 1, 1, 0;\n"
      "wgmma.commit_group.sync.aligned;\n"
      "wgmma.mma_async.sync.aligned.m64n8k16.f32.bf16.bf16 {%4, %5, %6, %7}, {%28, %29, %30, %31}, %48, 0, 1, 1, 0;\n"
      "wgmma.mma_async.sync.aligned.m64n8k16.f32.bf16.bf16 {%4, %5, %6, %7}, {%32, %33, %34, %35}, dx1, 1, 1, 1, 0;\n"
      "wgmma.mma_async.sync.aligned.m64n8k16.f32.bf16.bf16 {%4, %5, %6, %7}, {%36, %37, %38, %39}, dx2, 1, 1, 1, 0;\n"
      "wgmma.mma_async.sync.aligned.m64n8k16.f32.bf16.bf16 {%4, %5, %6, %7}, {%40, %41, %42, %43}, dx3, 1, 1, 1, 0;\n"
      "wgmma.commit_group.sync.aligned;\n}\n"
      : "=f"(g[0]), "=f"(g[1]), "=f"(g[2]), "=f"(g[3]),
        "=f"(h[0]), "=f"(h[1]), "=f"(h[2]), "=f"(h[3])
      : "r"(w[0]), "r"(w[1]), "r"(w[2]), "r"(w[3]), "r"(w[4]), "r"(w[5]), "r"(w[6]), "r"(w[7]), "r"(w[8]), "r"(w[9]), "r"(w[10]), "r"(w[11]), "r"(w[12]), "r"(w[13]), "r"(w[14]), "r"(w[15]), "r"(w[16]), "r"(w[17]), "r"(w[18]), "r"(w[19]), "r"(w[20]), "r"(w[21]), "r"(w[22]), "r"(w[23]), "r"(w[24]), "r"(w[25]), "r"(w[26]), "r"(w[27]), "r"(w[28]), "r"(w[29]), "r"(w[30]), "r"(w[31]), "r"(w[32]), "r"(w[33]), "r"(w[34]), "r"(w[35]), "r"(w[36]), "r"(w[37]), "r"(w[38]), "r"(w[39]), "l"(dx), "l"(de), "l"(dh)
      : "memory");
  }
  static __device__ __forceinline__ void wait_g(float* g) {
    asm volatile("wgmma.wait_group.sync.aligned 1;\n"
      : "+f"(g[0]), "+f"(g[1]), "+f"(g[2]), "+f"(g[3])
      :: "memory");
  }
  static __device__ __forceinline__ void wait_h(float* h) {
    asm volatile("wgmma.wait_group.sync.aligned 0;\n"
      : "+f"(h[0]), "+f"(h[1]), "+f"(h[2]), "+f"(h[3])
      :: "memory");
  }
};
template<> struct TileMMA<2> {
  static __device__ __forceinline__ void issue(float* g, float* h, const uint32_t* w, uint64_t dx, uint64_t de, uint64_t dh, uint64_t dc) {
    asm volatile(
      "{\n.reg .b64 dx1, dx2, dx3;\n"
      "add.s64 dx1, %56, 2;\nadd.s64 dx2, %56, 4;\nadd.s64 dx3, %56, 6;\n"
      "wgmma.fence.sync.aligned;\n"
      "wgmma.mma_async.sync.aligned.m64n16k16.f32.bf16.bf16 {%0, %1, %2, %3, %4, %5, %6, %7}, {%52, %53, %54, %55}, %58, 0, 1, 1, 0;\n"
      "wgmma.mma_async.sync.aligned.m64n16k16.f32.bf16.bf16 {%0, %1, %2, %3, %4, %5, %6, %7}, {%32, %33, %34, %35}, %57, 1, 1, 1, 0;\n"
      "wgmma.mma_async.sync.aligned.m64n16k16.f32.bf16.bf16 {%0, %1, %2, %3, %4, %5, %6, %7}, {%16, %17, %18, %19}, %56, 1, 1, 1, 0;\n"
      "wgmma.mma_async.sync.aligned.m64n16k16.f32.bf16.bf16 {%0, %1, %2, %3, %4, %5, %6, %7}, {%20, %21, %22, %23}, dx1, 1, 1, 1, 0;\n"
      "wgmma.mma_async.sync.aligned.m64n16k16.f32.bf16.bf16 {%0, %1, %2, %3, %4, %5, %6, %7}, {%24, %25, %26, %27}, dx2, 1, 1, 1, 0;\n"
      "wgmma.mma_async.sync.aligned.m64n16k16.f32.bf16.bf16 {%0, %1, %2, %3, %4, %5, %6, %7}, {%28, %29, %30, %31}, dx3, 1, 1, 1, 0;\n"
      "wgmma.commit_group.sync.aligned;\n"
      "wgmma.mma_async.sync.aligned.m64n16k16.f32.bf16.bf16 {%8, %9, %10, %11, %12, %13, %14, %15}, {%36, %37, %38, %39}, %56, 0, 1, 1, 0;\n"
      "wgmma.mma_async.sync.aligned.m64n16k16.f32.bf16.bf16 {%8, %9, %10, %11, %12, %13, %14, %15}, {%40, %41, %42, %43}, dx1, 1, 1, 1, 0;\n"
      "wgmma.mma_async.sync.aligned.m64n16k16.f32.bf16.bf16 {%8, %9, %10, %11, %12, %13, %14, %15}, {%44, %45, %46, %47}, dx2, 1, 1, 1, 0;\n"
      "wgmma.mma_async.sync.aligned.m64n16k16.f32.bf16.bf16 {%8, %9, %10, %11, %12, %13, %14, %15}, {%48, %49, %50, %51}, dx3, 1, 1, 1, 0;\n"
      "wgmma.commit_group.sync.aligned;\n}\n"
      : "=f"(g[0]), "=f"(g[1]), "=f"(g[2]), "=f"(g[3]), "=f"(g[4]), "=f"(g[5]), "=f"(g[6]), "=f"(g[7]),
        "=f"(h[0]), "=f"(h[1]), "=f"(h[2]), "=f"(h[3]), "=f"(h[4]), "=f"(h[5]), "=f"(h[6]), "=f"(h[7])
      : "r"(w[0]), "r"(w[1]), "r"(w[2]), "r"(w[3]), "r"(w[4]), "r"(w[5]), "r"(w[6]), "r"(w[7]), "r"(w[8]), "r"(w[9]), "r"(w[10]), "r"(w[11]), "r"(w[12]), "r"(w[13]), "r"(w[14]), "r"(w[15]), "r"(w[16]), "r"(w[17]), "r"(w[18]), "r"(w[19]), "r"(w[20]), "r"(w[21]), "r"(w[22]), "r"(w[23]), "r"(w[24]), "r"(w[25]), "r"(w[26]), "r"(w[27]), "r"(w[28]), "r"(w[29]), "r"(w[30]), "r"(w[31]), "r"(w[32]), "r"(w[33]), "r"(w[34]), "r"(w[35]), "r"(w[36]), "r"(w[37]), "r"(w[38]), "r"(w[39]), "l"(dx), "l"(de), "l"(dh)
      : "memory");
  }
  static __device__ __forceinline__ void wait_g(float* g) {
    asm volatile("wgmma.wait_group.sync.aligned 1;\n"
      : "+f"(g[0]), "+f"(g[1]), "+f"(g[2]), "+f"(g[3]), "+f"(g[4]), "+f"(g[5]), "+f"(g[6]), "+f"(g[7])
      :: "memory");
  }
  static __device__ __forceinline__ void wait_h(float* h) {
    asm volatile("wgmma.wait_group.sync.aligned 0;\n"
      : "+f"(h[0]), "+f"(h[1]), "+f"(h[2]), "+f"(h[3]), "+f"(h[4]), "+f"(h[5]), "+f"(h[6]), "+f"(h[7])
      :: "memory");
  }
};
template<> struct TileMMA<3> {
  static __device__ __forceinline__ void issue(float* g, float* h, const uint32_t* w, uint64_t dx, uint64_t de, uint64_t dh, uint64_t dc) {
    asm volatile(
      "{\n.reg .b64 dx1, dx2, dx3;\n"
      "add.s64 dx1, %64, 2;\nadd.s64 dx2, %64, 4;\nadd.s64 dx3, %64, 6;\n"
      "wgmma.fence.sync.aligned;\n"
      "wgmma.mma_async.sync.aligned.m64n24k16.f32.bf16.bf16 {%0, %1, %2, %3, %4, %5, %6, %7, %8, %9, %10, %11}, {%60, %61, %62, %63}, %66, 0, 1, 1, 0;\n"
      "wgmma.mma_async.sync.aligned.m64n24k16.f32.bf16.bf16 {%0, %1, %2, %3, %4, %5, %6, %7, %8, %9, %10, %11}, {%40, %41, %42, %43}, %65, 1, 1, 1, 0;\n"
      "wgmma.mma_async.sync.aligned.m64n24k16.f32.bf16.bf16 {%0, %1, %2, %3, %4, %5, %6, %7, %8, %9, %10, %11}, {%24, %25, %26, %27}, %64, 1, 1, 1, 0;\n"
      "wgmma.mma_async.sync.aligned.m64n24k16.f32.bf16.bf16 {%0, %1, %2, %3, %4, %5, %6, %7, %8, %9, %10, %11}, {%28, %29, %30, %31}, dx1, 1, 1, 1, 0;\n"
      "wgmma.mma_async.sync.aligned.m64n24k16.f32.bf16.bf16 {%0, %1, %2, %3, %4, %5, %6, %7, %8, %9, %10, %11}, {%32, %33, %34, %35}, dx2, 1, 1, 1, 0;\n"
      "wgmma.mma_async.sync.aligned.m64n24k16.f32.bf16.bf16 {%0, %1, %2, %3, %4, %5, %6, %7, %8, %9, %10, %11}, {%36, %37, %38, %39}, dx3, 1, 1, 1, 0;\n"
      "wgmma.commit_group.sync.aligned;\n"
      "wgmma.mma_async.sync.aligned.m64n24k16.f32.bf16.bf16 {%12, %13, %14, %15, %16, %17, %18, %19, %20, %21, %22, %23}, {%44, %45, %46, %47}, %64, 0, 1, 1, 0;\n"
      "wgmma.mma_async.sync.aligned.m64n24k16.f32.bf16.bf16 {%12, %13, %14, %15, %16, %17, %18, %19, %20, %21, %22, %23}, {%48, %49, %50, %51}, dx1, 1, 1, 1, 0;\n"
      "wgmma.mma_async.sync.aligned.m64n24k16.f32.bf16.bf16 {%12, %13, %14, %15, %16, %17, %18, %19, %20, %21, %22, %23}, {%52, %53, %54, %55}, dx2, 1, 1, 1, 0;\n"
      "wgmma.mma_async.sync.aligned.m64n24k16.f32.bf16.bf16 {%12, %13, %14, %15, %16, %17, %18, %19, %20, %21, %22, %23}, {%56, %57, %58, %59}, dx3, 1, 1, 1, 0;\n"
      "wgmma.commit_group.sync.aligned;\n}\n"
      : "=f"(g[0]), "=f"(g[1]), "=f"(g[2]), "=f"(g[3]), "=f"(g[4]), "=f"(g[5]), "=f"(g[6]), "=f"(g[7]), "=f"(g[8]), "=f"(g[9]), "=f"(g[10]), "=f"(g[11]),
        "=f"(h[0]), "=f"(h[1]), "=f"(h[2]), "=f"(h[3]), "=f"(h[4]), "=f"(h[5]), "=f"(h[6]), "=f"(h[7]), "=f"(h[8]), "=f"(h[9]), "=f"(h[10]), "=f"(h[11])
      : "r"(w[0]), "r"(w[1]), "r"(w[2]), "r"(w[3]), "r"(w[4]), "r"(w[5]), "r"(w[6]), "r"(w[7]), "r"(w[8]), "r"(w[9]), "r"(w[10]), "r"(w[11]), "r"(w[12]), "r"(w[13]), "r"(w[14]), "r"(w[15]), "r"(w[16]), "r"(w[17]), "r"(w[18]), "r"(w[19]), "r"(w[20]), "r"(w[21]), "r"(w[22]), "r"(w[23]), "r"(w[24]), "r"(w[25]), "r"(w[26]), "r"(w[27]), "r"(w[28]), "r"(w[29]), "r"(w[30]), "r"(w[31]), "r"(w[32]), "r"(w[33]), "r"(w[34]), "r"(w[35]), "r"(w[36]), "r"(w[37]), "r"(w[38]), "r"(w[39]), "l"(dx), "l"(de), "l"(dh)
      : "memory");
  }
  static __device__ __forceinline__ void wait_g(float* g) {
    asm volatile("wgmma.wait_group.sync.aligned 1;\n"
      : "+f"(g[0]), "+f"(g[1]), "+f"(g[2]), "+f"(g[3]), "+f"(g[4]), "+f"(g[5]), "+f"(g[6]), "+f"(g[7]), "+f"(g[8]), "+f"(g[9]), "+f"(g[10]), "+f"(g[11])
      :: "memory");
  }
  static __device__ __forceinline__ void wait_h(float* h) {
    asm volatile("wgmma.wait_group.sync.aligned 0;\n"
      : "+f"(h[0]), "+f"(h[1]), "+f"(h[2]), "+f"(h[3]), "+f"(h[4]), "+f"(h[5]), "+f"(h[6]), "+f"(h[7]), "+f"(h[8]), "+f"(h[9]), "+f"(h[10]), "+f"(h[11])
      :: "memory");
  }
};
template<> struct TileMMA<4> {
  static __device__ __forceinline__ void issue(float* g, float* h, const uint32_t* w, uint64_t dx, uint64_t de, uint64_t dh, uint64_t dc) {
    asm volatile(
      "{\n.reg .b64 dx1, dx2, dx3;\n"
      "add.s64 dx1, %72, 2;\nadd.s64 dx2, %72, 4;\nadd.s64 dx3, %72, 6;\n"
      "wgmma.fence.sync.aligned;\n"
      "wgmma.mma_async.sync.aligned.m64n32k16.f32.bf16.bf16 {%0, %1, %2, %3, %4, %5, %6, %7, %8, %9, %10, %11, %12, %13, %14, %15}, {%68, %69, %70, %71}, %74, 0, 1, 1, 0;\n"
      "wgmma.mma_async.sync.aligned.m64n32k16.f32.bf16.bf16 {%0, %1, %2, %3, %4, %5, %6, %7, %8, %9, %10, %11, %12, %13, %14, %15}, {%48, %49, %50, %51}, %73, 1, 1, 1, 0;\n"
      "wgmma.mma_async.sync.aligned.m64n32k16.f32.bf16.bf16 {%0, %1, %2, %3, %4, %5, %6, %7, %8, %9, %10, %11, %12, %13, %14, %15}, {%32, %33, %34, %35}, %72, 1, 1, 1, 0;\n"
      "wgmma.mma_async.sync.aligned.m64n32k16.f32.bf16.bf16 {%0, %1, %2, %3, %4, %5, %6, %7, %8, %9, %10, %11, %12, %13, %14, %15}, {%36, %37, %38, %39}, dx1, 1, 1, 1, 0;\n"
      "wgmma.mma_async.sync.aligned.m64n32k16.f32.bf16.bf16 {%0, %1, %2, %3, %4, %5, %6, %7, %8, %9, %10, %11, %12, %13, %14, %15}, {%40, %41, %42, %43}, dx2, 1, 1, 1, 0;\n"
      "wgmma.mma_async.sync.aligned.m64n32k16.f32.bf16.bf16 {%0, %1, %2, %3, %4, %5, %6, %7, %8, %9, %10, %11, %12, %13, %14, %15}, {%44, %45, %46, %47}, dx3, 1, 1, 1, 0;\n"
      "wgmma.commit_group.sync.aligned;\n"
      "wgmma.mma_async.sync.aligned.m64n32k16.f32.bf16.bf16 {%16, %17, %18, %19, %20, %21, %22, %23, %24, %25, %26, %27, %28, %29, %30, %31}, {%52, %53, %54, %55}, %72, 0, 1, 1, 0;\n"
      "wgmma.mma_async.sync.aligned.m64n32k16.f32.bf16.bf16 {%16, %17, %18, %19, %20, %21, %22, %23, %24, %25, %26, %27, %28, %29, %30, %31}, {%56, %57, %58, %59}, dx1, 1, 1, 1, 0;\n"
      "wgmma.mma_async.sync.aligned.m64n32k16.f32.bf16.bf16 {%16, %17, %18, %19, %20, %21, %22, %23, %24, %25, %26, %27, %28, %29, %30, %31}, {%60, %61, %62, %63}, dx2, 1, 1, 1, 0;\n"
      "wgmma.mma_async.sync.aligned.m64n32k16.f32.bf16.bf16 {%16, %17, %18, %19, %20, %21, %22, %23, %24, %25, %26, %27, %28, %29, %30, %31}, {%64, %65, %66, %67}, dx3, 1, 1, 1, 0;\n"
      "wgmma.commit_group.sync.aligned;\n}\n"
      : "=f"(g[0]), "=f"(g[1]), "=f"(g[2]), "=f"(g[3]), "=f"(g[4]), "=f"(g[5]), "=f"(g[6]), "=f"(g[7]), "=f"(g[8]), "=f"(g[9]), "=f"(g[10]), "=f"(g[11]), "=f"(g[12]), "=f"(g[13]), "=f"(g[14]), "=f"(g[15]),
        "=f"(h[0]), "=f"(h[1]), "=f"(h[2]), "=f"(h[3]), "=f"(h[4]), "=f"(h[5]), "=f"(h[6]), "=f"(h[7]), "=f"(h[8]), "=f"(h[9]), "=f"(h[10]), "=f"(h[11]), "=f"(h[12]), "=f"(h[13]), "=f"(h[14]), "=f"(h[15])
      : "r"(w[0]), "r"(w[1]), "r"(w[2]), "r"(w[3]), "r"(w[4]), "r"(w[5]), "r"(w[6]), "r"(w[7]), "r"(w[8]), "r"(w[9]), "r"(w[10]), "r"(w[11]), "r"(w[12]), "r"(w[13]), "r"(w[14]), "r"(w[15]), "r"(w[16]), "r"(w[17]), "r"(w[18]), "r"(w[19]), "r"(w[20]), "r"(w[21]), "r"(w[22]), "r"(w[23]), "r"(w[24]), "r"(w[25]), "r"(w[26]), "r"(w[27]), "r"(w[28]), "r"(w[29]), "r"(w[30]), "r"(w[31]), "r"(w[32]), "r"(w[33]), "r"(w[34]), "r"(w[35]), "r"(w[36]), "r"(w[37]), "r"(w[38]), "r"(w[39]), "l"(dx), "l"(de), "l"(dh)
      : "memory");
  }
  static __device__ __forceinline__ void wait_g(float* g) {
    asm volatile("wgmma.wait_group.sync.aligned 1;\n"
      : "+f"(g[0]), "+f"(g[1]), "+f"(g[2]), "+f"(g[3]), "+f"(g[4]), "+f"(g[5]), "+f"(g[6]), "+f"(g[7]), "+f"(g[8]), "+f"(g[9]), "+f"(g[10]), "+f"(g[11]), "+f"(g[12]), "+f"(g[13]), "+f"(g[14]), "+f"(g[15])
      :: "memory");
  }
  static __device__ __forceinline__ void wait_h(float* h) {
    asm volatile("wgmma.wait_group.sync.aligned 0;\n"
      : "+f"(h[0]), "+f"(h[1]), "+f"(h[2]), "+f"(h[3]), "+f"(h[4]), "+f"(h[5]), "+f"(h[6]), "+f"(h[7]), "+f"(h[8]), "+f"(h[9]), "+f"(h[10]), "+f"(h[11]), "+f"(h[12]), "+f"(h[13]), "+f"(h[14]), "+f"(h[15])
      :: "memory");
  }
};
template<> struct TileMMA<5> {
  static __device__ __forceinline__ void issue(float* g, float* h, const uint32_t* w, uint64_t dx, uint64_t de, uint64_t dh, uint64_t dc) {
    asm volatile(
      "{\n.reg .b64 dx1, dx2, dx3;\n"
      "add.s64 dx1, %80, 2;\nadd.s64 dx2, %80, 4;\nadd.s64 dx3, %80, 6;\n"
      "wgmma.fence.sync.aligned;\n"
      "wgmma.mma_async.sync.aligned.m64n40k16.f32.bf16.bf16 {%0, %1, %2, %3, %4, %5, %6, %7, %8, %9, %10, %11, %12, %13, %14, %15, %16, %17, %18, %19}, {%76, %77, %78, %79}, %82, 0, 1, 1, 0;\n"
      "wgmma.mma_async.sync.aligned.m64n40k16.f32.bf16.bf16 {%0, %1, %2, %3, %4, %5, %6, %7, %8, %9, %10, %11, %12, %13, %14, %15, %16, %17, %18, %19}, {%56, %57, %58, %59}, %81, 1, 1, 1, 0;\n"
      "wgmma.mma_async.sync.aligned.m64n40k16.f32.bf16.bf16 {%0, %1, %2, %3, %4, %5, %6, %7, %8, %9, %10, %11, %12, %13, %14, %15, %16, %17, %18, %19}, {%40, %41, %42, %43}, %80, 1, 1, 1, 0;\n"
      "wgmma.mma_async.sync.aligned.m64n40k16.f32.bf16.bf16 {%0, %1, %2, %3, %4, %5, %6, %7, %8, %9, %10, %11, %12, %13, %14, %15, %16, %17, %18, %19}, {%44, %45, %46, %47}, dx1, 1, 1, 1, 0;\n"
      "wgmma.mma_async.sync.aligned.m64n40k16.f32.bf16.bf16 {%0, %1, %2, %3, %4, %5, %6, %7, %8, %9, %10, %11, %12, %13, %14, %15, %16, %17, %18, %19}, {%48, %49, %50, %51}, dx2, 1, 1, 1, 0;\n"
      "wgmma.mma_async.sync.aligned.m64n40k16.f32.bf16.bf16 {%0, %1, %2, %3, %4, %5, %6, %7, %8, %9, %10, %11, %12, %13, %14, %15, %16, %17, %18, %19}, {%52, %53, %54, %55}, dx3, 1, 1, 1, 0;\n"
      "wgmma.commit_group.sync.aligned;\n"
      "wgmma.mma_async.sync.aligned.m64n40k16.f32.bf16.bf16 {%20, %21, %22, %23, %24, %25, %26, %27, %28, %29, %30, %31, %32, %33, %34, %35, %36, %37, %38, %39}, {%60, %61, %62, %63}, %80, 0, 1, 1, 0;\n"
      "wgmma.mma_async.sync.aligned.m64n40k16.f32.bf16.bf16 {%20, %21, %22, %23, %24, %25, %26, %27, %28, %29, %30, %31, %32, %33, %34, %35, %36, %37, %38, %39}, {%64, %65, %66, %67}, dx1, 1, 1, 1, 0;\n"
      "wgmma.mma_async.sync.aligned.m64n40k16.f32.bf16.bf16 {%20, %21, %22, %23, %24, %25, %26, %27, %28, %29, %30, %31, %32, %33, %34, %35, %36, %37, %38, %39}, {%68, %69, %70, %71}, dx2, 1, 1, 1, 0;\n"
      "wgmma.mma_async.sync.aligned.m64n40k16.f32.bf16.bf16 {%20, %21, %22, %23, %24, %25, %26, %27, %28, %29, %30, %31, %32, %33, %34, %35, %36, %37, %38, %39}, {%72, %73, %74, %75}, dx3, 1, 1, 1, 0;\n"
      "wgmma.commit_group.sync.aligned;\n}\n"
      : "=f"(g[0]), "=f"(g[1]), "=f"(g[2]), "=f"(g[3]), "=f"(g[4]), "=f"(g[5]), "=f"(g[6]), "=f"(g[7]), "=f"(g[8]), "=f"(g[9]), "=f"(g[10]), "=f"(g[11]), "=f"(g[12]), "=f"(g[13]), "=f"(g[14]), "=f"(g[15]), "=f"(g[16]), "=f"(g[17]), "=f"(g[18]), "=f"(g[19]),
        "=f"(h[0]), "=f"(h[1]), "=f"(h[2]), "=f"(h[3]), "=f"(h[4]), "=f"(h[5]), "=f"(h[6]), "=f"(h[7]), "=f"(h[8]), "=f"(h[9]), "=f"(h[10]), "=f"(h[11]), "=f"(h[12]), "=f"(h[13]), "=f"(h[14]), "=f"(h[15]), "=f"(h[16]), "=f"(h[17]), "=f"(h[18]), "=f"(h[19])
      : "r"(w[0]), "r"(w[1]), "r"(w[2]), "r"(w[3]), "r"(w[4]), "r"(w[5]), "r"(w[6]), "r"(w[7]), "r"(w[8]), "r"(w[9]), "r"(w[10]), "r"(w[11]), "r"(w[12]), "r"(w[13]), "r"(w[14]), "r"(w[15]), "r"(w[16]), "r"(w[17]), "r"(w[18]), "r"(w[19]), "r"(w[20]), "r"(w[21]), "r"(w[22]), "r"(w[23]), "r"(w[24]), "r"(w[25]), "r"(w[26]), "r"(w[27]), "r"(w[28]), "r"(w[29]), "r"(w[30]), "r"(w[31]), "r"(w[32]), "r"(w[33]), "r"(w[34]), "r"(w[35]), "r"(w[36]), "r"(w[37]), "r"(w[38]), "r"(w[39]), "l"(dx), "l"(de), "l"(dh)
      : "memory");
  }
  static __device__ __forceinline__ void wait_g(float* g) {
    asm volatile("wgmma.wait_group.sync.aligned 1;\n"
      : "+f"(g[0]), "+f"(g[1]), "+f"(g[2]), "+f"(g[3]), "+f"(g[4]), "+f"(g[5]), "+f"(g[6]), "+f"(g[7]), "+f"(g[8]), "+f"(g[9]), "+f"(g[10]), "+f"(g[11]), "+f"(g[12]), "+f"(g[13]), "+f"(g[14]), "+f"(g[15]), "+f"(g[16]), "+f"(g[17]), "+f"(g[18]), "+f"(g[19])
      :: "memory");
  }
  static __device__ __forceinline__ void wait_h(float* h) {
    asm volatile("wgmma.wait_group.sync.aligned 0;\n"
      : "+f"(h[0]), "+f"(h[1]), "+f"(h[2]), "+f"(h[3]), "+f"(h[4]), "+f"(h[5]), "+f"(h[6]), "+f"(h[7]), "+f"(h[8]), "+f"(h[9]), "+f"(h[10]), "+f"(h[11]), "+f"(h[12]), "+f"(h[13]), "+f"(h[14]), "+f"(h[15]), "+f"(h[16]), "+f"(h[17]), "+f"(h[18]), "+f"(h[19])
      :: "memory");
  }
};
template<> struct TileMMA<6> {
  static __device__ __forceinline__ void issue(float* g, float* h, const uint32_t* w, uint64_t dx, uint64_t de, uint64_t dh, uint64_t dc) {
    asm volatile(
      "{\n.reg .b64 dx1, dx2, dx3;\n"
      "add.s64 dx1, %88, 2;\nadd.s64 dx2, %88, 4;\nadd.s64 dx3, %88, 6;\n"
      "wgmma.fence.sync.aligned;\n"
      "wgmma.mma_async.sync.aligned.m64n48k16.f32.bf16.bf16 {%0, %1, %2, %3, %4, %5, %6, %7, %8, %9, %10, %11, %12, %13, %14, %15, %16, %17, %18, %19, %20, %21, %22, %23}, {%84, %85, %86, %87}, %90, 0, 1, 1, 0;\n"
      "wgmma.mma_async.sync.aligned.m64n48k16.f32.bf16.bf16 {%0, %1, %2, %3, %4, %5, %6, %7, %8, %9, %10, %11, %12, %13, %14, %15, %16, %17, %18, %19, %20, %21, %22, %23}, {%64, %65, %66, %67}, %89, 1, 1, 1, 0;\n"
      "wgmma.mma_async.sync.aligned.m64n48k16.f32.bf16.bf16 {%0, %1, %2, %3, %4, %5, %6, %7, %8, %9, %10, %11, %12, %13, %14, %15, %16, %17, %18, %19, %20, %21, %22, %23}, {%48, %49, %50, %51}, %88, 1, 1, 1, 0;\n"
      "wgmma.mma_async.sync.aligned.m64n48k16.f32.bf16.bf16 {%0, %1, %2, %3, %4, %5, %6, %7, %8, %9, %10, %11, %12, %13, %14, %15, %16, %17, %18, %19, %20, %21, %22, %23}, {%52, %53, %54, %55}, dx1, 1, 1, 1, 0;\n"
      "wgmma.mma_async.sync.aligned.m64n48k16.f32.bf16.bf16 {%0, %1, %2, %3, %4, %5, %6, %7, %8, %9, %10, %11, %12, %13, %14, %15, %16, %17, %18, %19, %20, %21, %22, %23}, {%56, %57, %58, %59}, dx2, 1, 1, 1, 0;\n"
      "wgmma.mma_async.sync.aligned.m64n48k16.f32.bf16.bf16 {%0, %1, %2, %3, %4, %5, %6, %7, %8, %9, %10, %11, %12, %13, %14, %15, %16, %17, %18, %19, %20, %21, %22, %23}, {%60, %61, %62, %63}, dx3, 1, 1, 1, 0;\n"
      "wgmma.commit_group.sync.aligned;\n"
      "wgmma.mma_async.sync.aligned.m64n48k16.f32.bf16.bf16 {%24, %25, %26, %27, %28, %29, %30, %31, %32, %33, %34, %35, %36, %37, %38, %39, %40, %41, %42, %43, %44, %45, %46, %47}, {%68, %69, %70, %71}, %88, 0, 1, 1, 0;\n"
      "wgmma.mma_async.sync.aligned.m64n48k16.f32.bf16.bf16 {%24, %25, %26, %27, %28, %29, %30, %31, %32, %33, %34, %35, %36, %37, %38, %39, %40, %41, %42, %43, %44, %45, %46, %47}, {%72, %73, %74, %75}, dx1, 1, 1, 1, 0;\n"
      "wgmma.mma_async.sync.aligned.m64n48k16.f32.bf16.bf16 {%24, %25, %26, %27, %28, %29, %30, %31, %32, %33, %34, %35, %36, %37, %38, %39, %40, %41, %42, %43, %44, %45, %46, %47}, {%76, %77, %78, %79}, dx2, 1, 1, 1, 0;\n"
      "wgmma.mma_async.sync.aligned.m64n48k16.f32.bf16.bf16 {%24, %25, %26, %27, %28, %29, %30, %31, %32, %33, %34, %35, %36, %37, %38, %39, %40, %41, %42, %43, %44, %45, %46, %47}, {%80, %81, %82, %83}, dx3, 1, 1, 1, 0;\n"
      "wgmma.commit_group.sync.aligned;\n}\n"
      : "=f"(g[0]), "=f"(g[1]), "=f"(g[2]), "=f"(g[3]), "=f"(g[4]), "=f"(g[5]), "=f"(g[6]), "=f"(g[7]), "=f"(g[8]), "=f"(g[9]), "=f"(g[10]), "=f"(g[11]), "=f"(g[12]), "=f"(g[13]), "=f"(g[14]), "=f"(g[15]), "=f"(g[16]), "=f"(g[17]), "=f"(g[18]), "=f"(g[19]), "=f"(g[20]), "=f"(g[21]), "=f"(g[22]), "=f"(g[23]),
        "=f"(h[0]), "=f"(h[1]), "=f"(h[2]), "=f"(h[3]), "=f"(h[4]), "=f"(h[5]), "=f"(h[6]), "=f"(h[7]), "=f"(h[8]), "=f"(h[9]), "=f"(h[10]), "=f"(h[11]), "=f"(h[12]), "=f"(h[13]), "=f"(h[14]), "=f"(h[15]), "=f"(h[16]), "=f"(h[17]), "=f"(h[18]), "=f"(h[19]), "=f"(h[20]), "=f"(h[21]), "=f"(h[22]), "=f"(h[23])
      : "r"(w[0]), "r"(w[1]), "r"(w[2]), "r"(w[3]), "r"(w[4]), "r"(w[5]), "r"(w[6]), "r"(w[7]), "r"(w[8]), "r"(w[9]), "r"(w[10]), "r"(w[11]), "r"(w[12]), "r"(w[13]), "r"(w[14]), "r"(w[15]), "r"(w[16]), "r"(w[17]), "r"(w[18]), "r"(w[19]), "r"(w[20]), "r"(w[21]), "r"(w[22]), "r"(w[23]), "r"(w[24]), "r"(w[25]), "r"(w[26]), "r"(w[27]), "r"(w[28]), "r"(w[29]), "r"(w[30]), "r"(w[31]), "r"(w[32]), "r"(w[33]), "r"(w[34]), "r"(w[35]), "r"(w[36]), "r"(w[37]), "r"(w[38]), "r"(w[39]), "l"(dx), "l"(de), "l"(dh)
      : "memory");
  }
  static __device__ __forceinline__ void wait_g(float* g) {
    asm volatile("wgmma.wait_group.sync.aligned 1;\n"
      : "+f"(g[0]), "+f"(g[1]), "+f"(g[2]), "+f"(g[3]), "+f"(g[4]), "+f"(g[5]), "+f"(g[6]), "+f"(g[7]), "+f"(g[8]), "+f"(g[9]), "+f"(g[10]), "+f"(g[11]), "+f"(g[12]), "+f"(g[13]), "+f"(g[14]), "+f"(g[15]), "+f"(g[16]), "+f"(g[17]), "+f"(g[18]), "+f"(g[19]), "+f"(g[20]), "+f"(g[21]), "+f"(g[22]), "+f"(g[23])
      :: "memory");
  }
  static __device__ __forceinline__ void wait_h(float* h) {
    asm volatile("wgmma.wait_group.sync.aligned 0;\n"
      : "+f"(h[0]), "+f"(h[1]), "+f"(h[2]), "+f"(h[3]), "+f"(h[4]), "+f"(h[5]), "+f"(h[6]), "+f"(h[7]), "+f"(h[8]), "+f"(h[9]), "+f"(h[10]), "+f"(h[11]), "+f"(h[12]), "+f"(h[13]), "+f"(h[14]), "+f"(h[15]), "+f"(h[16]), "+f"(h[17]), "+f"(h[18]), "+f"(h[19]), "+f"(h[20]), "+f"(h[21]), "+f"(h[22]), "+f"(h[23])
      :: "memory");
  }
};
template<> struct TileMMA<7> {
  static __device__ __forceinline__ void issue(float* g, float* h, const uint32_t* w, uint64_t dx, uint64_t de, uint64_t dh, uint64_t dc) {
    asm volatile(
      "{\n.reg .b64 dx1, dx2, dx3;\n"
      "add.s64 dx1, %96, 2;\nadd.s64 dx2, %96, 4;\nadd.s64 dx3, %96, 6;\n"
      "wgmma.fence.sync.aligned;\n"
      "wgmma.mma_async.sync.aligned.m64n56k16.f32.bf16.bf16 {%0, %1, %2, %3, %4, %5, %6, %7, %8, %9, %10, %11, %12, %13, %14, %15, %16, %17, %18, %19, %20, %21, %22, %23, %24, %25, %26, %27}, {%92, %93, %94, %95}, %98, 0, 1, 1, 0;\n"
      "wgmma.mma_async.sync.aligned.m64n56k16.f32.bf16.bf16 {%0, %1, %2, %3, %4, %5, %6, %7, %8, %9, %10, %11, %12, %13, %14, %15, %16, %17, %18, %19, %20, %21, %22, %23, %24, %25, %26, %27}, {%72, %73, %74, %75}, %97, 1, 1, 1, 0;\n"
      "wgmma.mma_async.sync.aligned.m64n56k16.f32.bf16.bf16 {%0, %1, %2, %3, %4, %5, %6, %7, %8, %9, %10, %11, %12, %13, %14, %15, %16, %17, %18, %19, %20, %21, %22, %23, %24, %25, %26, %27}, {%56, %57, %58, %59}, %96, 1, 1, 1, 0;\n"
      "wgmma.mma_async.sync.aligned.m64n56k16.f32.bf16.bf16 {%0, %1, %2, %3, %4, %5, %6, %7, %8, %9, %10, %11, %12, %13, %14, %15, %16, %17, %18, %19, %20, %21, %22, %23, %24, %25, %26, %27}, {%60, %61, %62, %63}, dx1, 1, 1, 1, 0;\n"
      "wgmma.mma_async.sync.aligned.m64n56k16.f32.bf16.bf16 {%0, %1, %2, %3, %4, %5, %6, %7, %8, %9, %10, %11, %12, %13, %14, %15, %16, %17, %18, %19, %20, %21, %22, %23, %24, %25, %26, %27}, {%64, %65, %66, %67}, dx2, 1, 1, 1, 0;\n"
      "wgmma.mma_async.sync.aligned.m64n56k16.f32.bf16.bf16 {%0, %1, %2, %3, %4, %5, %6, %7, %8, %9, %10, %11, %12, %13, %14, %15, %16, %17, %18, %19, %20, %21, %22, %23, %24, %25, %26, %27}, {%68, %69, %70, %71}, dx3, 1, 1, 1, 0;\n"
      "wgmma.commit_group.sync.aligned;\n"
      "wgmma.mma_async.sync.aligned.m64n56k16.f32.bf16.bf16 {%28, %29, %30, %31, %32, %33, %34, %35, %36, %37, %38, %39, %40, %41, %42, %43, %44, %45, %46, %47, %48, %49, %50, %51, %52, %53, %54, %55}, {%76, %77, %78, %79}, %96, 0, 1, 1, 0;\n"
      "wgmma.mma_async.sync.aligned.m64n56k16.f32.bf16.bf16 {%28, %29, %30, %31, %32, %33, %34, %35, %36, %37, %38, %39, %40, %41, %42, %43, %44, %45, %46, %47, %48, %49, %50, %51, %52, %53, %54, %55}, {%80, %81, %82, %83}, dx1, 1, 1, 1, 0;\n"
      "wgmma.mma_async.sync.aligned.m64n56k16.f32.bf16.bf16 {%28, %29, %30, %31, %32, %33, %34, %35, %36, %37, %38, %39, %40, %41, %42, %43, %44, %45, %46, %47, %48, %49, %50, %51, %52, %53, %54, %55}, {%84, %85, %86, %87}, dx2, 1, 1, 1, 0;\n"
      "wgmma.mma_async.sync.aligned.m64n56k16.f32.bf16.bf16 {%28, %29, %30, %31, %32, %33, %34, %35, %36, %37, %38, %39, %40, %41, %42, %43, %44, %45, %46, %47, %48, %49, %50, %51, %52, %53, %54, %55}, {%88, %89, %90, %91}, dx3, 1, 1, 1, 0;\n"
      "wgmma.commit_group.sync.aligned;\n}\n"
      : "=f"(g[0]), "=f"(g[1]), "=f"(g[2]), "=f"(g[3]), "=f"(g[4]), "=f"(g[5]), "=f"(g[6]), "=f"(g[7]), "=f"(g[8]), "=f"(g[9]), "=f"(g[10]), "=f"(g[11]), "=f"(g[12]), "=f"(g[13]), "=f"(g[14]), "=f"(g[15]), "=f"(g[16]), "=f"(g[17]), "=f"(g[18]), "=f"(g[19]), "=f"(g[20]), "=f"(g[21]), "=f"(g[22]), "=f"(g[23]), "=f"(g[24]), "=f"(g[25]), "=f"(g[26]), "=f"(g[27]),
        "=f"(h[0]), "=f"(h[1]), "=f"(h[2]), "=f"(h[3]), "=f"(h[4]), "=f"(h[5]), "=f"(h[6]), "=f"(h[7]), "=f"(h[8]), "=f"(h[9]), "=f"(h[10]), "=f"(h[11]), "=f"(h[12]), "=f"(h[13]), "=f"(h[14]), "=f"(h[15]), "=f"(h[16]), "=f"(h[17]), "=f"(h[18]), "=f"(h[19]), "=f"(h[20]), "=f"(h[21]), "=f"(h[22]), "=f"(h[23]), "=f"(h[24]), "=f"(h[25]), "=f"(h[26]), "=f"(h[27])
      : "r"(w[0]), "r"(w[1]), "r"(w[2]), "r"(w[3]), "r"(w[4]), "r"(w[5]), "r"(w[6]), "r"(w[7]), "r"(w[8]), "r"(w[9]), "r"(w[10]), "r"(w[11]), "r"(w[12]), "r"(w[13]), "r"(w[14]), "r"(w[15]), "r"(w[16]), "r"(w[17]), "r"(w[18]), "r"(w[19]), "r"(w[20]), "r"(w[21]), "r"(w[22]), "r"(w[23]), "r"(w[24]), "r"(w[25]), "r"(w[26]), "r"(w[27]), "r"(w[28]), "r"(w[29]), "r"(w[30]), "r"(w[31]), "r"(w[32]), "r"(w[33]), "r"(w[34]), "r"(w[35]), "r"(w[36]), "r"(w[37]), "r"(w[38]), "r"(w[39]), "l"(dx), "l"(de), "l"(dh)
      : "memory");
  }
  static __device__ __forceinline__ void wait_g(float* g) {
    asm volatile("wgmma.wait_group.sync.aligned 1;\n"
      : "+f"(g[0]), "+f"(g[1]), "+f"(g[2]), "+f"(g[3]), "+f"(g[4]), "+f"(g[5]), "+f"(g[6]), "+f"(g[7]), "+f"(g[8]), "+f"(g[9]), "+f"(g[10]), "+f"(g[11]), "+f"(g[12]), "+f"(g[13]), "+f"(g[14]), "+f"(g[15]), "+f"(g[16]), "+f"(g[17]), "+f"(g[18]), "+f"(g[19]), "+f"(g[20]), "+f"(g[21]), "+f"(g[22]), "+f"(g[23]), "+f"(g[24]), "+f"(g[25]), "+f"(g[26]), "+f"(g[27])
      :: "memory");
  }
  static __device__ __forceinline__ void wait_h(float* h) {
    asm volatile("wgmma.wait_group.sync.aligned 0;\n"
      : "+f"(h[0]), "+f"(h[1]), "+f"(h[2]), "+f"(h[3]), "+f"(h[4]), "+f"(h[5]), "+f"(h[6]), "+f"(h[7]), "+f"(h[8]), "+f"(h[9]), "+f"(h[10]), "+f"(h[11]), "+f"(h[12]), "+f"(h[13]), "+f"(h[14]), "+f"(h[15]), "+f"(h[16]), "+f"(h[17]), "+f"(h[18]), "+f"(h[19]), "+f"(h[20]), "+f"(h[21]), "+f"(h[22]), "+f"(h[23]), "+f"(h[24]), "+f"(h[25]), "+f"(h[26]), "+f"(h[27])
      :: "memory");
  }
};
template<> struct TileMMA<8> {
  static __device__ __forceinline__ void issue(float* g, float* h, const uint32_t* w, uint64_t dx, uint64_t de, uint64_t dh, uint64_t dc) {
    asm volatile(
      "{\n.reg .b64 dx1, dx2, dx3;\n"
      "add.s64 dx1, %104, 2;\nadd.s64 dx2, %104, 4;\nadd.s64 dx3, %104, 6;\n"
      "wgmma.fence.sync.aligned;\n"
      "wgmma.mma_async.sync.aligned.m64n64k16.f32.bf16.bf16 {%0, %1, %2, %3, %4, %5, %6, %7, %8, %9, %10, %11, %12, %13, %14, %15, %16, %17, %18, %19, %20, %21, %22, %23, %24, %25, %26, %27, %28, %29, %30, %31}, {%100, %101, %102, %103}, %106, 0, 1, 1, 0;\n"
      "wgmma.mma_async.sync.aligned.m64n64k16.f32.bf16.bf16 {%0, %1, %2, %3, %4, %5, %6, %7, %8, %9, %10, %11, %12, %13, %14, %15, %16, %17, %18, %19, %20, %21, %22, %23, %24, %25, %26, %27, %28, %29, %30, %31}, {%80, %81, %82, %83}, %105, 1, 1, 1, 0;\n"
      "wgmma.mma_async.sync.aligned.m64n64k16.f32.bf16.bf16 {%0, %1, %2, %3, %4, %5, %6, %7, %8, %9, %10, %11, %12, %13, %14, %15, %16, %17, %18, %19, %20, %21, %22, %23, %24, %25, %26, %27, %28, %29, %30, %31}, {%64, %65, %66, %67}, %104, 1, 1, 1, 0;\n"
      "wgmma.mma_async.sync.aligned.m64n64k16.f32.bf16.bf16 {%0, %1, %2, %3, %4, %5, %6, %7, %8, %9, %10, %11, %12, %13, %14, %15, %16, %17, %18, %19, %20, %21, %22, %23, %24, %25, %26, %27, %28, %29, %30, %31}, {%68, %69, %70, %71}, dx1, 1, 1, 1, 0;\n"
      "wgmma.mma_async.sync.aligned.m64n64k16.f32.bf16.bf16 {%0, %1, %2, %3, %4, %5, %6, %7, %8, %9, %10, %11, %12, %13, %14, %15, %16, %17, %18, %19, %20, %21, %22, %23, %24, %25, %26, %27, %28, %29, %30, %31}, {%72, %73, %74, %75}, dx2, 1, 1, 1, 0;\n"
      "wgmma.mma_async.sync.aligned.m64n64k16.f32.bf16.bf16 {%0, %1, %2, %3, %4, %5, %6, %7, %8, %9, %10, %11, %12, %13, %14, %15, %16, %17, %18, %19, %20, %21, %22, %23, %24, %25, %26, %27, %28, %29, %30, %31}, {%76, %77, %78, %79}, dx3, 1, 1, 1, 0;\n"
      "wgmma.commit_group.sync.aligned;\n"
      "wgmma.mma_async.sync.aligned.m64n64k16.f32.bf16.bf16 {%32, %33, %34, %35, %36, %37, %38, %39, %40, %41, %42, %43, %44, %45, %46, %47, %48, %49, %50, %51, %52, %53, %54, %55, %56, %57, %58, %59, %60, %61, %62, %63}, {%84, %85, %86, %87}, %104, 0, 1, 1, 0;\n"
      "wgmma.mma_async.sync.aligned.m64n64k16.f32.bf16.bf16 {%32, %33, %34, %35, %36, %37, %38, %39, %40, %41, %42, %43, %44, %45, %46, %47, %48, %49, %50, %51, %52, %53, %54, %55, %56, %57, %58, %59, %60, %61, %62, %63}, {%88, %89, %90, %91}, dx1, 1, 1, 1, 0;\n"
      "wgmma.mma_async.sync.aligned.m64n64k16.f32.bf16.bf16 {%32, %33, %34, %35, %36, %37, %38, %39, %40, %41, %42, %43, %44, %45, %46, %47, %48, %49, %50, %51, %52, %53, %54, %55, %56, %57, %58, %59, %60, %61, %62, %63}, {%92, %93, %94, %95}, dx2, 1, 1, 1, 0;\n"
      "wgmma.mma_async.sync.aligned.m64n64k16.f32.bf16.bf16 {%32, %33, %34, %35, %36, %37, %38, %39, %40, %41, %42, %43, %44, %45, %46, %47, %48, %49, %50, %51, %52, %53, %54, %55, %56, %57, %58, %59, %60, %61, %62, %63}, {%96, %97, %98, %99}, dx3, 1, 1, 1, 0;\n"
      "wgmma.commit_group.sync.aligned;\n}\n"
      : "=f"(g[0]), "=f"(g[1]), "=f"(g[2]), "=f"(g[3]), "=f"(g[4]), "=f"(g[5]), "=f"(g[6]), "=f"(g[7]), "=f"(g[8]), "=f"(g[9]), "=f"(g[10]), "=f"(g[11]), "=f"(g[12]), "=f"(g[13]), "=f"(g[14]), "=f"(g[15]), "=f"(g[16]), "=f"(g[17]), "=f"(g[18]), "=f"(g[19]), "=f"(g[20]), "=f"(g[21]), "=f"(g[22]), "=f"(g[23]), "=f"(g[24]), "=f"(g[25]), "=f"(g[26]), "=f"(g[27]), "=f"(g[28]), "=f"(g[29]), "=f"(g[30]), "=f"(g[31]),
        "=f"(h[0]), "=f"(h[1]), "=f"(h[2]), "=f"(h[3]), "=f"(h[4]), "=f"(h[5]), "=f"(h[6]), "=f"(h[7]), "=f"(h[8]), "=f"(h[9]), "=f"(h[10]), "=f"(h[11]), "=f"(h[12]), "=f"(h[13]), "=f"(h[14]), "=f"(h[15]), "=f"(h[16]), "=f"(h[17]), "=f"(h[18]), "=f"(h[19]), "=f"(h[20]), "=f"(h[21]), "=f"(h[22]), "=f"(h[23]), "=f"(h[24]), "=f"(h[25]), "=f"(h[26]), "=f"(h[27]), "=f"(h[28]), "=f"(h[29]), "=f"(h[30]), "=f"(h[31])
      : "r"(w[0]), "r"(w[1]), "r"(w[2]), "r"(w[3]), "r"(w[4]), "r"(w[5]), "r"(w[6]), "r"(w[7]), "r"(w[8]), "r"(w[9]), "r"(w[10]), "r"(w[11]), "r"(w[12]), "r"(w[13]), "r"(w[14]), "r"(w[15]), "r"(w[16]), "r"(w[17]), "r"(w[18]), "r"(w[19]), "r"(w[20]), "r"(w[21]), "r"(w[22]), "r"(w[23]), "r"(w[24]), "r"(w[25]), "r"(w[26]), "r"(w[27]), "r"(w[28]), "r"(w[29]), "r"(w[30]), "r"(w[31]), "r"(w[32]), "r"(w[33]), "r"(w[34]), "r"(w[35]), "r"(w[36]), "r"(w[37]), "r"(w[38]), "r"(w[39]), "l"(dx), "l"(de), "l"(dh)
      : "memory");
  }
  static __device__ __forceinline__ void wait_g(float* g) {
    asm volatile("wgmma.wait_group.sync.aligned 1;\n"
      : "+f"(g[0]), "+f"(g[1]), "+f"(g[2]), "+f"(g[3]), "+f"(g[4]), "+f"(g[5]), "+f"(g[6]), "+f"(g[7]), "+f"(g[8]), "+f"(g[9]), "+f"(g[10]), "+f"(g[11]), "+f"(g[12]), "+f"(g[13]), "+f"(g[14]), "+f"(g[15]), "+f"(g[16]), "+f"(g[17]), "+f"(g[18]), "+f"(g[19]), "+f"(g[20]), "+f"(g[21]), "+f"(g[22]), "+f"(g[23]), "+f"(g[24]), "+f"(g[25]), "+f"(g[26]), "+f"(g[27]), "+f"(g[28]), "+f"(g[29]), "+f"(g[30]), "+f"(g[31])
      :: "memory");
  }
  static __device__ __forceinline__ void wait_h(float* h) {
    asm volatile("wgmma.wait_group.sync.aligned 0;\n"
      : "+f"(h[0]), "+f"(h[1]), "+f"(h[2]), "+f"(h[3]), "+f"(h[4]), "+f"(h[5]), "+f"(h[6]), "+f"(h[7]), "+f"(h[8]), "+f"(h[9]), "+f"(h[10]), "+f"(h[11]), "+f"(h[12]), "+f"(h[13]), "+f"(h[14]), "+f"(h[15]), "+f"(h[16]), "+f"(h[17]), "+f"(h[18]), "+f"(h[19]), "+f"(h[20]), "+f"(h[21]), "+f"(h[22]), "+f"(h[23]), "+f"(h[24]), "+f"(h[25]), "+f"(h[26]), "+f"(h[27]), "+f"(h[28]), "+f"(h[29]), "+f"(h[30]), "+f"(h[31])
      :: "memory");
  }
};
template<> struct TileMMA<9> {
  static __device__ __forceinline__ void issue(float* g, float* h, const uint32_t* w, uint64_t dx, uint64_t de, uint64_t dh, uint64_t dc) {
    asm volatile(
      "{\n.reg .b64 dx1, dx2, dx3;\n"
      "add.s64 dx1, %112, 2;\nadd.s64 dx2, %112, 4;\nadd.s64 dx3, %112, 6;\n"
      "wgmma.fence.sync.aligned;\n"
      "wgmma.mma_async.sync.aligned.m64n72k16.f32.bf16.bf16 {%0, %1, %2, %3, %4, %5, %6, %7, %8, %9, %10, %11, %12, %13, %14, %15, %16, %17, %18, %19, %20, %21, %22, %23, %24, %25, %26, %27, %28, %29, %30, %31, %32, %33, %34, %35}, {%108, %109, %110, %111}, %114, 0, 1, 1, 0;\n"
      "wgmma.mma_async.sync.aligned.m64n72k16.f32.bf16.bf16 {%0, %1, %2, %3, %4, %5, %6, %7, %8, %9, %10, %11, %12, %13, %14, %15, %16, %17, %18, %19, %20, %21, %22, %23, %24, %25, %26, %27, %28, %29, %30, %31, %32, %33, %34, %35}, {%88, %89, %90, %91}, %113, 1, 1, 1, 0;\n"
      "wgmma.mma_async.sync.aligned.m64n72k16.f32.bf16.bf16 {%0, %1, %2, %3, %4, %5, %6, %7, %8, %9, %10, %11, %12, %13, %14, %15, %16, %17, %18, %19, %20, %21, %22, %23, %24, %25, %26, %27, %28, %29, %30, %31, %32, %33, %34, %35}, {%72, %73, %74, %75}, %112, 1, 1, 1, 0;\n"
      "wgmma.mma_async.sync.aligned.m64n72k16.f32.bf16.bf16 {%0, %1, %2, %3, %4, %5, %6, %7, %8, %9, %10, %11, %12, %13, %14, %15, %16, %17, %18, %19, %20, %21, %22, %23, %24, %25, %26, %27, %28, %29, %30, %31, %32, %33, %34, %35}, {%76, %77, %78, %79}, dx1, 1, 1, 1, 0;\n"
      "wgmma.mma_async.sync.aligned.m64n72k16.f32.bf16.bf16 {%0, %1, %2, %3, %4, %5, %6, %7, %8, %9, %10, %11, %12, %13, %14, %15, %16, %17, %18, %19, %20, %21, %22, %23, %24, %25, %26, %27, %28, %29, %30, %31, %32, %33, %34, %35}, {%80, %81, %82, %83}, dx2, 1, 1, 1, 0;\n"
      "wgmma.mma_async.sync.aligned.m64n72k16.f32.bf16.bf16 {%0, %1, %2, %3, %4, %5, %6, %7, %8, %9, %10, %11, %12, %13, %14, %15, %16, %17, %18, %19, %20, %21, %22, %23, %24, %25, %26, %27, %28, %29, %30, %31, %32, %33, %34, %35}, {%84, %85, %86, %87}, dx3, 1, 1, 1, 0;\n"
      "wgmma.commit_group.sync.aligned;\n"
      "wgmma.mma_async.sync.aligned.m64n72k16.f32.bf16.bf16 {%36, %37, %38, %39, %40, %41, %42, %43, %44, %45, %46, %47, %48, %49, %50, %51, %52, %53, %54, %55, %56, %57, %58, %59, %60, %61, %62, %63, %64, %65, %66, %67, %68, %69, %70, %71}, {%92, %93, %94, %95}, %112, 0, 1, 1, 0;\n"
      "wgmma.mma_async.sync.aligned.m64n72k16.f32.bf16.bf16 {%36, %37, %38, %39, %40, %41, %42, %43, %44, %45, %46, %47, %48, %49, %50, %51, %52, %53, %54, %55, %56, %57, %58, %59, %60, %61, %62, %63, %64, %65, %66, %67, %68, %69, %70, %71}, {%96, %97, %98, %99}, dx1, 1, 1, 1, 0;\n"
      "wgmma.mma_async.sync.aligned.m64n72k16.f32.bf16.bf16 {%36, %37, %38, %39, %40, %41, %42, %43, %44, %45, %46, %47, %48, %49, %50, %51, %52, %53, %54, %55, %56, %57, %58, %59, %60, %61, %62, %63, %64, %65, %66, %67, %68, %69, %70, %71}, {%100, %101, %102, %103}, dx2, 1, 1, 1, 0;\n"
      "wgmma.mma_async.sync.aligned.m64n72k16.f32.bf16.bf16 {%36, %37, %38, %39, %40, %41, %42, %43, %44, %45, %46, %47, %48, %49, %50, %51, %52, %53, %54, %55, %56, %57, %58, %59, %60, %61, %62, %63, %64, %65, %66, %67, %68, %69, %70, %71}, {%104, %105, %106, %107}, dx3, 1, 1, 1, 0;\n"
      "wgmma.commit_group.sync.aligned;\n}\n"
      : "=f"(g[0]), "=f"(g[1]), "=f"(g[2]), "=f"(g[3]), "=f"(g[4]), "=f"(g[5]), "=f"(g[6]), "=f"(g[7]), "=f"(g[8]), "=f"(g[9]), "=f"(g[10]), "=f"(g[11]), "=f"(g[12]), "=f"(g[13]), "=f"(g[14]), "=f"(g[15]), "=f"(g[16]), "=f"(g[17]), "=f"(g[18]), "=f"(g[19]), "=f"(g[20]), "=f"(g[21]), "=f"(g[22]), "=f"(g[23]), "=f"(g[24]), "=f"(g[25]), "=f"(g[26]), "=f"(g[27]), "=f"(g[28]), "=f"(g[29]), "=f"(g[30]), "=f"(g[31]), "=f"(g[32]), "=f"(g[33]), "=f"(g[34]), "=f"(g[35]),
        "=f"(h[0]), "=f"(h[1]), "=f"(h[2]), "=f"(h[3]), "=f"(h[4]), "=f"(h[5]), "=f"(h[6]), "=f"(h[7]), "=f"(h[8]), "=f"(h[9]), "=f"(h[10]), "=f"(h[11]), "=f"(h[12]), "=f"(h[13]), "=f"(h[14]), "=f"(h[15]), "=f"(h[16]), "=f"(h[17]), "=f"(h[18]), "=f"(h[19]), "=f"(h[20]), "=f"(h[21]), "=f"(h[22]), "=f"(h[23]), "=f"(h[24]), "=f"(h[25]), "=f"(h[26]), "=f"(h[27]), "=f"(h[28]), "=f"(h[29]), "=f"(h[30]), "=f"(h[31]), "=f"(h[32]), "=f"(h[33]), "=f"(h[34]), "=f"(h[35])
      : "r"(w[0]), "r"(w[1]), "r"(w[2]), "r"(w[3]), "r"(w[4]), "r"(w[5]), "r"(w[6]), "r"(w[7]), "r"(w[8]), "r"(w[9]), "r"(w[10]), "r"(w[11]), "r"(w[12]), "r"(w[13]), "r"(w[14]), "r"(w[15]), "r"(w[16]), "r"(w[17]), "r"(w[18]), "r"(w[19]), "r"(w[20]), "r"(w[21]), "r"(w[22]), "r"(w[23]), "r"(w[24]), "r"(w[25]), "r"(w[26]), "r"(w[27]), "r"(w[28]), "r"(w[29]), "r"(w[30]), "r"(w[31]), "r"(w[32]), "r"(w[33]), "r"(w[34]), "r"(w[35]), "r"(w[36]), "r"(w[37]), "r"(w[38]), "r"(w[39]), "l"(dx), "l"(de), "l"(dh)
      : "memory");
  }
  static __device__ __forceinline__ void wait_g(float* g) {
    asm volatile("wgmma.wait_group.sync.aligned 1;\n"
      : "+f"(g[0]), "+f"(g[1]), "+f"(g[2]), "+f"(g[3]), "+f"(g[4]), "+f"(g[5]), "+f"(g[6]), "+f"(g[7]), "+f"(g[8]), "+f"(g[9]), "+f"(g[10]), "+f"(g[11]), "+f"(g[12]), "+f"(g[13]), "+f"(g[14]), "+f"(g[15]), "+f"(g[16]), "+f"(g[17]), "+f"(g[18]), "+f"(g[19]), "+f"(g[20]), "+f"(g[21]), "+f"(g[22]), "+f"(g[23]), "+f"(g[24]), "+f"(g[25]), "+f"(g[26]), "+f"(g[27]), "+f"(g[28]), "+f"(g[29]), "+f"(g[30]), "+f"(g[31]), "+f"(g[32]), "+f"(g[33]), "+f"(g[34]), "+f"(g[35])
      :: "memory");
  }
  static __device__ __forceinline__ void wait_h(float* h) {
    asm volatile("wgmma.wait_group.sync.aligned 0;\n"
      : "+f"(h[0]), "+f"(h[1]), "+f"(h[2]), "+f"(h[3]), "+f"(h[4]), "+f"(h[5]), "+f"(h[6]), "+f"(h[7]), "+f"(h[8]), "+f"(h[9]), "+f"(h[10]), "+f"(h[11]), "+f"(h[12]), "+f"(h[13]), "+f"(h[14]), "+f"(h[15]), "+f"(h[16]), "+f"(h[17]), "+f"(h[18]), "+f"(h[19]), "+f"(h[20]), "+f"(h[21]), "+f"(h[22]), "+f"(h[23]), "+f"(h[24]), "+f"(h[25]), "+f"(h[26]), "+f"(h[27]), "+f"(h[28]), "+f"(h[29]), "+f"(h[30]), "+f"(h[31]), "+f"(h[32]), "+f"(h[33]), "+f"(h[34]), "+f"(h[35])
      :: "memory");
  }
};
template<> struct TileMMA<10> {
  static __device__ __forceinline__ void issue(float* g, float* h, const uint32_t* w, uint64_t dx, uint64_t de, uint64_t dh, uint64_t dc) {
    asm volatile(
      "{\n.reg .b64 dx1, dx2, dx3;\n"
      "add.s64 dx1, %120, 2;\nadd.s64 dx2, %120, 4;\nadd.s64 dx3, %120, 6;\n"
      "wgmma.fence.sync.aligned;\n"
      "wgmma.mma_async.sync.aligned.m64n80k16.f32.bf16.bf16 {%0, %1, %2, %3, %4, %5, %6, %7, %8, %9, %10, %11, %12, %13, %14, %15, %16, %17, %18, %19, %20, %21, %22, %23, %24, %25, %26, %27, %28, %29, %30, %31, %32, %33, %34, %35, %36, %37, %38, %39}, {%116, %117, %118, %119}, %122, 0, 1, 1, 0;\n"
      "wgmma.mma_async.sync.aligned.m64n80k16.f32.bf16.bf16 {%0, %1, %2, %3, %4, %5, %6, %7, %8, %9, %10, %11, %12, %13, %14, %15, %16, %17, %18, %19, %20, %21, %22, %23, %24, %25, %26, %27, %28, %29, %30, %31, %32, %33, %34, %35, %36, %37, %38, %39}, {%96, %97, %98, %99}, %121, 1, 1, 1, 0;\n"
      "wgmma.mma_async.sync.aligned.m64n80k16.f32.bf16.bf16 {%0, %1, %2, %3, %4, %5, %6, %7, %8, %9, %10, %11, %12, %13, %14, %15, %16, %17, %18, %19, %20, %21, %22, %23, %24, %25, %26, %27, %28, %29, %30, %31, %32, %33, %34, %35, %36, %37, %38, %39}, {%80, %81, %82, %83}, %120, 1, 1, 1, 0;\n"
      "wgmma.mma_async.sync.aligned.m64n80k16.f32.bf16.bf16 {%0, %1, %2, %3, %4, %5, %6, %7, %8, %9, %10, %11, %12, %13, %14, %15, %16, %17, %18, %19, %20, %21, %22, %23, %24, %25, %26, %27, %28, %29, %30, %31, %32, %33, %34, %35, %36, %37, %38, %39}, {%84, %85, %86, %87}, dx1, 1, 1, 1, 0;\n"
      "wgmma.mma_async.sync.aligned.m64n80k16.f32.bf16.bf16 {%0, %1, %2, %3, %4, %5, %6, %7, %8, %9, %10, %11, %12, %13, %14, %15, %16, %17, %18, %19, %20, %21, %22, %23, %24, %25, %26, %27, %28, %29, %30, %31, %32, %33, %34, %35, %36, %37, %38, %39}, {%88, %89, %90, %91}, dx2, 1, 1, 1, 0;\n"
      "wgmma.mma_async.sync.aligned.m64n80k16.f32.bf16.bf16 {%0, %1, %2, %3, %4, %5, %6, %7, %8, %9, %10, %11, %12, %13, %14, %15, %16, %17, %18, %19, %20, %21, %22, %23, %24, %25, %26, %27, %28, %29, %30, %31, %32, %33, %34, %35, %36, %37, %38, %39}, {%92, %93, %94, %95}, dx3, 1, 1, 1, 0;\n"
      "wgmma.commit_group.sync.aligned;\n"
      "wgmma.mma_async.sync.aligned.m64n80k16.f32.bf16.bf16 {%40, %41, %42, %43, %44, %45, %46, %47, %48, %49, %50, %51, %52, %53, %54, %55, %56, %57, %58, %59, %60, %61, %62, %63, %64, %65, %66, %67, %68, %69, %70, %71, %72, %73, %74, %75, %76, %77, %78, %79}, {%100, %101, %102, %103}, %120, 0, 1, 1, 0;\n"
      "wgmma.mma_async.sync.aligned.m64n80k16.f32.bf16.bf16 {%40, %41, %42, %43, %44, %45, %46, %47, %48, %49, %50, %51, %52, %53, %54, %55, %56, %57, %58, %59, %60, %61, %62, %63, %64, %65, %66, %67, %68, %69, %70, %71, %72, %73, %74, %75, %76, %77, %78, %79}, {%104, %105, %106, %107}, dx1, 1, 1, 1, 0;\n"
      "wgmma.mma_async.sync.aligned.m64n80k16.f32.bf16.bf16 {%40, %41, %42, %43, %44, %45, %46, %47, %48, %49, %50, %51, %52, %53, %54, %55, %56, %57, %58, %59, %60, %61, %62, %63, %64, %65, %66, %67, %68, %69, %70, %71, %72, %73, %74, %75, %76, %77, %78, %79}, {%108, %109, %110, %111}, dx2, 1, 1, 1, 0;\n"
      "wgmma.mma_async.sync.aligned.m64n80k16.f32.bf16.bf16 {%40, %41, %42, %43, %44, %45, %46, %47, %48, %49, %50, %51, %52, %53, %54, %55, %56, %57, %58, %59, %60, %61, %62, %63, %64, %65, %66, %67, %68, %69, %70, %71, %72, %73, %74, %75, %76, %77, %78, %79}, {%112, %113, %114, %115}, dx3, 1, 1, 1, 0;\n"
      "wgmma.commit_group.sync.aligned;\n}\n"
      : "=f"(g[0]), "=f"(g[1]), "=f"(g[2]), "=f"(g[3]), "=f"(g[4]), "=f"(g[5]), "=f"(g[6]), "=f"(g[7]), "=f"(g[8]), "=f"(g[9]), "=f"(g[10]), "=f"(g[11]), "=f"(g[12]), "=f"(g[13]), "=f"(g[14]), "=f"(g[15]), "=f"(g[16]), "=f"(g[17]), "=f"(g[18]), "=f"(g[19]), "=f"(g[20]), "=f"(g[21]), "=f"(g[22]), "=f"(g[23]), "=f"(g[24]), "=f"(g[25]), "=f"(g[26]), "=f"(g[27]), "=f"(g[28]), "=f"(g[29]), "=f"(g[30]), "=f"(g[31]), "=f"(g[32]), "=f"(g[33]), "=f"(g[34]), "=f"(g[35]), "=f"(g[36]), "=f"(g[37]), "=f"(g[38]), "=f"(g[39]),
        "=f"(h[0]), "=f"(h[1]), "=f"(h[2]), "=f"(h[3]), "=f"(h[4]), "=f"(h[5]), "=f"(h[6]), "=f"(h[7]), "=f"(h[8]), "=f"(h[9]), "=f"(h[10]), "=f"(h[11]), "=f"(h[12]), "=f"(h[13]), "=f"(h[14]), "=f"(h[15]), "=f"(h[16]), "=f"(h[17]), "=f"(h[18]), "=f"(h[19]), "=f"(h[20]), "=f"(h[21]), "=f"(h[22]), "=f"(h[23]), "=f"(h[24]), "=f"(h[25]), "=f"(h[26]), "=f"(h[27]), "=f"(h[28]), "=f"(h[29]), "=f"(h[30]), "=f"(h[31]), "=f"(h[32]), "=f"(h[33]), "=f"(h[34]), "=f"(h[35]), "=f"(h[36]), "=f"(h[37]), "=f"(h[38]), "=f"(h[39])
      : "r"(w[0]), "r"(w[1]), "r"(w[2]), "r"(w[3]), "r"(w[4]), "r"(w[5]), "r"(w[6]), "r"(w[7]), "r"(w[8]), "r"(w[9]), "r"(w[10]), "r"(w[11]), "r"(w[12]), "r"(w[13]), "r"(w[14]), "r"(w[15]), "r"(w[16]), "r"(w[17]), "r"(w[18]), "r"(w[19]), "r"(w[20]), "r"(w[21]), "r"(w[22]), "r"(w[23]), "r"(w[24]), "r"(w[25]), "r"(w[26]), "r"(w[27]), "r"(w[28]), "r"(w[29]), "r"(w[30]), "r"(w[31]), "r"(w[32]), "r"(w[33]), "r"(w[34]), "r"(w[35]), "r"(w[36]), "r"(w[37]), "r"(w[38]), "r"(w[39]), "l"(dx), "l"(de), "l"(dh)
      : "memory");
  }
  static __device__ __forceinline__ void wait_g(float* g) {
    asm volatile("wgmma.wait_group.sync.aligned 1;\n"
      : "+f"(g[0]), "+f"(g[1]), "+f"(g[2]), "+f"(g[3]), "+f"(g[4]), "+f"(g[5]), "+f"(g[6]), "+f"(g[7]), "+f"(g[8]), "+f"(g[9]), "+f"(g[10]), "+f"(g[11]), "+f"(g[12]), "+f"(g[13]), "+f"(g[14]), "+f"(g[15]), "+f"(g[16]), "+f"(g[17]), "+f"(g[18]), "+f"(g[19]), "+f"(g[20]), "+f"(g[21]), "+f"(g[22]), "+f"(g[23]), "+f"(g[24]), "+f"(g[25]), "+f"(g[26]), "+f"(g[27]), "+f"(g[28]), "+f"(g[29]), "+f"(g[30]), "+f"(g[31]), "+f"(g[32]), "+f"(g[33]), "+f"(g[34]), "+f"(g[35]), "+f"(g[36]), "+f"(g[37]), "+f"(g[38]), "+f"(g[39])
      :: "memory");
  }
  static __device__ __forceinline__ void wait_h(float* h) {
    asm volatile("wgmma.wait_group.sync.aligned 0;\n"
      : "+f"(h[0]), "+f"(h[1]), "+f"(h[2]), "+f"(h[3]), "+f"(h[4]), "+f"(h[5]), "+f"(h[6]), "+f"(h[7]), "+f"(h[8]), "+f"(h[9]), "+f"(h[10]), "+f"(h[11]), "+f"(h[12]), "+f"(h[13]), "+f"(h[14]), "+f"(h[15]), "+f"(h[16]), "+f"(h[17]), "+f"(h[18]), "+f"(h[19]), "+f"(h[20]), "+f"(h[21]), "+f"(h[22]), "+f"(h[23]), "+f"(h[24]), "+f"(h[25]), "+f"(h[26]), "+f"(h[27]), "+f"(h[28]), "+f"(h[29]), "+f"(h[30]), "+f"(h[31]), "+f"(h[32]), "+f"(h[33]), "+f"(h[34]), "+f"(h[35]), "+f"(h[36]), "+f"(h[37]), "+f"(h[38]), "+f"(h[39])
      :: "memory");
  }
};
template<> struct TileMMA<11> {
  static __device__ __forceinline__ void issue(float* g, float* h, const uint32_t* w, uint64_t dx, uint64_t de, uint64_t dh, uint64_t dc) {
    asm volatile(
      "{\n.reg .b64 dx1, dx2, dx3;\n"
      "add.s64 dx1, %124, 2;\nadd.s64 dx2, %124, 4;\nadd.s64 dx3, %124, 6;\n"
      "wgmma.fence.sync.aligned;\n"
      "wgmma.mma_async.sync.aligned.m64n88k16.f32.bf16.bf16 {%0, %1, %2, %3, %4, %5, %6, %7, %8, %9, %10, %11, %12, %13, %14, %15, %16, %17, %18, %19, %20, %21, %22, %23, %24, %25, %26, %27, %28, %29, %30, %31, %32, %33, %34, %35, %36, %37, %38, %39, %40, %41, %42, %43}, {%120, %121, %122, %123}, %126, 0, 1, 1, 0;\n"
      "wgmma.mma_async.sync.aligned.m64n88k16.f32.bf16.bf16 {%0, %1, %2, %3, %4, %5, %6, %7, %8, %9, %10, %11, %12, %13, %14, %15, %16, %17, %18, %19, %20, %21, %22, %23, %24, %25, %26, %27, %28, %29, %30, %31, %32, %33, %34, %35, %36, %37, %38, %39, %40, %41, %42, %43}, %127, %125, 1, 1, 1, 0, 0;\n"
      "wgmma.mma_async.sync.aligned.m64n88k16.f32.bf16.bf16 {%0, %1, %2, %3, %4, %5, %6, %7, %8, %9, %10, %11, %12, %13, %14, %15, %16, %17, %18, %19, %20, %21, %22, %23, %24, %25, %26, %27, %28, %29, %30, %31, %32, %33, %34, %35, %36, %37, %38, %39, %40, %41, %42, %43}, {%88, %89, %90, %91}, %124, 1, 1, 1, 0;\n"
      "wgmma.mma_async.sync.aligned.m64n88k16.f32.bf16.bf16 {%0, %1, %2, %3, %4, %5, %6, %7, %8, %9, %10, %11, %12, %13, %14, %15, %16, %17, %18, %19, %20, %21, %22, %23, %24, %25, %26, %27, %28, %29, %30, %31, %32, %33, %34, %35, %36, %37, %38, %39, %40, %41, %42, %43}, {%92, %93, %94, %95}, dx1, 1, 1, 1, 0;\n"
      "wgmma.mma_async.sync.aligned.m64n88k16.f32.bf16.bf16 {%0, %1, %2, %3, %4, %5, %6, %7, %8, %9, %10, %11, %12, %13, %14, %15, %16, %17, %18, %19, %20, %21, %22, %23, %24, %25, %26, %27, %28, %29, %30, %31, %32, %33, %34, %35, %36, %37, %38, %39, %40, %41, %42, %43}, {%96, %97, %98, %99}, dx2, 1, 1, 1, 0;\n"
      "wgmma.mma_async.sync.aligned.m64n88k16.f32.bf16.bf16 {%0, %1, %2, %3, %4, %5, %6, %7, %8, %9, %10, %11, %12, %13, %14, %15, %16, %17, %18, %19, %20, %21, %22, %23, %24, %25, %26, %27, %28, %29, %30, %31, %32, %33, %34, %35, %36, %37, %38, %39, %40, %41, %42, %43}, {%100, %101, %102, %103}, dx3, 1, 1, 1, 0;\n"
      "wgmma.commit_group.sync.aligned;\n"
      "wgmma.mma_async.sync.aligned.m64n88k16.f32.bf16.bf16 {%44, %45, %46, %47, %48, %49, %50, %51, %52, %53, %54, %55, %56, %57, %58, %59, %60, %61, %62, %63, %64, %65, %66, %67, %68, %69, %70, %71, %72, %73, %74, %75, %76, %77, %78, %79, %80, %81, %82, %83, %84, %85, %86, %87}, {%104, %105, %106, %107}, %124, 0, 1, 1, 0;\n"
      "wgmma.mma_async.sync.aligned.m64n88k16.f32.bf16.bf16 {%44, %45, %46, %47, %48, %49, %50, %51, %52, %53, %54, %55, %56, %57, %58, %59, %60, %61, %62, %63, %64, %65, %66, %67, %68, %69, %70, %71, %72, %73, %74, %75, %76, %77, %78, %79, %80, %81, %82, %83, %84, %85, %86, %87}, {%108, %109, %110, %111}, dx1, 1, 1, 1, 0;\n"
      "wgmma.mma_async.sync.aligned.m64n88k16.f32.bf16.bf16 {%44, %45, %46, %47, %48, %49, %50, %51, %52, %53, %54, %55, %56, %57, %58, %59, %60, %61, %62, %63, %64, %65, %66, %67, %68, %69, %70, %71, %72, %73, %74, %75, %76, %77, %78, %79, %80, %81, %82, %83, %84, %85, %86, %87}, {%112, %113, %114, %115}, dx2, 1, 1, 1, 0;\n"
      "wgmma.mma_async.sync.aligned.m64n88k16.f32.bf16.bf16 {%44, %45, %46, %47, %48, %49, %50, %51, %52, %53, %54, %55, %56, %57, %58, %59, %60, %61, %62, %63, %64, %65, %66, %67, %68, %69, %70, %71, %72, %73, %74, %75, %76, %77, %78, %79, %80, %81, %82, %83, %84, %85, %86, %87}, {%116, %117, %118, %119}, dx3, 1, 1, 1, 0;\n"
      "wgmma.commit_group.sync.aligned;\n}\n"
      : "=f"(g[0]), "=f"(g[1]), "=f"(g[2]), "=f"(g[3]), "=f"(g[4]), "=f"(g[5]), "=f"(g[6]), "=f"(g[7]), "=f"(g[8]), "=f"(g[9]), "=f"(g[10]), "=f"(g[11]), "=f"(g[12]), "=f"(g[13]), "=f"(g[14]), "=f"(g[15]), "=f"(g[16]), "=f"(g[17]), "=f"(g[18]), "=f"(g[19]), "=f"(g[20]), "=f"(g[21]), "=f"(g[22]), "=f"(g[23]), "=f"(g[24]), "=f"(g[25]), "=f"(g[26]), "=f"(g[27]), "=f"(g[28]), "=f"(g[29]), "=f"(g[30]), "=f"(g[31]), "=f"(g[32]), "=f"(g[33]), "=f"(g[34]), "=f"(g[35]), "=f"(g[36]), "=f"(g[37]), "=f"(g[38]), "=f"(g[39]), "=f"(g[40]), "=f"(g[41]), "=f"(g[42]), "=f"(g[43]),
        "=f"(h[0]), "=f"(h[1]), "=f"(h[2]), "=f"(h[3]), "=f"(h[4]), "=f"(h[5]), "=f"(h[6]), "=f"(h[7]), "=f"(h[8]), "=f"(h[9]), "=f"(h[10]), "=f"(h[11]), "=f"(h[12]), "=f"(h[13]), "=f"(h[14]), "=f"(h[15]), "=f"(h[16]), "=f"(h[17]), "=f"(h[18]), "=f"(h[19]), "=f"(h[20]), "=f"(h[21]), "=f"(h[22]), "=f"(h[23]), "=f"(h[24]), "=f"(h[25]), "=f"(h[26]), "=f"(h[27]), "=f"(h[28]), "=f"(h[29]), "=f"(h[30]), "=f"(h[31]), "=f"(h[32]), "=f"(h[33]), "=f"(h[34]), "=f"(h[35]), "=f"(h[36]), "=f"(h[37]), "=f"(h[38]), "=f"(h[39]), "=f"(h[40]), "=f"(h[41]), "=f"(h[42]), "=f"(h[43])
      : "r"(w[0]), "r"(w[1]), "r"(w[2]), "r"(w[3]), "r"(w[4]), "r"(w[5]), "r"(w[6]), "r"(w[7]), "r"(w[8]), "r"(w[9]), "r"(w[10]), "r"(w[11]), "r"(w[12]), "r"(w[13]), "r"(w[14]), "r"(w[15]), "r"(w[20]), "r"(w[21]), "r"(w[22]), "r"(w[23]), "r"(w[24]), "r"(w[25]), "r"(w[26]), "r"(w[27]), "r"(w[28]), "r"(w[29]), "r"(w[30]), "r"(w[31]), "r"(w[32]), "r"(w[33]), "r"(w[34]), "r"(w[35]), "r"(w[36]), "r"(w[37]), "r"(w[38]), "r"(w[39]), "l"(dx), "l"(de), "l"(dh), "l"(dc)
      : "memory");
  }
  static __device__ __forceinline__ void wait_g(float* g) {
    asm volatile("wgmma.wait_group.sync.aligned 1;\n"
      : "+f"(g[0]), "+f"(g[1]), "+f"(g[2]), "+f"(g[3]), "+f"(g[4]), "+f"(g[5]), "+f"(g[6]), "+f"(g[7]), "+f"(g[8]), "+f"(g[9]), "+f"(g[10]), "+f"(g[11]), "+f"(g[12]), "+f"(g[13]), "+f"(g[14]), "+f"(g[15]), "+f"(g[16]), "+f"(g[17]), "+f"(g[18]), "+f"(g[19]), "+f"(g[20]), "+f"(g[21]), "+f"(g[22]), "+f"(g[23]), "+f"(g[24]), "+f"(g[25]), "+f"(g[26]), "+f"(g[27]), "+f"(g[28]), "+f"(g[29]), "+f"(g[30]), "+f"(g[31]), "+f"(g[32]), "+f"(g[33]), "+f"(g[34]), "+f"(g[35]), "+f"(g[36]), "+f"(g[37]), "+f"(g[38]), "+f"(g[39]), "+f"(g[40]), "+f"(g[41]), "+f"(g[42]), "+f"(g[43])
      :: "memory");
  }
  static __device__ __forceinline__ void wait_h(float* h) {
    asm volatile("wgmma.wait_group.sync.aligned 0;\n"
      : "+f"(h[0]), "+f"(h[1]), "+f"(h[2]), "+f"(h[3]), "+f"(h[4]), "+f"(h[5]), "+f"(h[6]), "+f"(h[7]), "+f"(h[8]), "+f"(h[9]), "+f"(h[10]), "+f"(h[11]), "+f"(h[12]), "+f"(h[13]), "+f"(h[14]), "+f"(h[15]), "+f"(h[16]), "+f"(h[17]), "+f"(h[18]), "+f"(h[19]), "+f"(h[20]), "+f"(h[21]), "+f"(h[22]), "+f"(h[23]), "+f"(h[24]), "+f"(h[25]), "+f"(h[26]), "+f"(h[27]), "+f"(h[28]), "+f"(h[29]), "+f"(h[30]), "+f"(h[31]), "+f"(h[32]), "+f"(h[33]), "+f"(h[34]), "+f"(h[35]), "+f"(h[36]), "+f"(h[37]), "+f"(h[38]), "+f"(h[39]), "+f"(h[40]), "+f"(h[41]), "+f"(h[42]), "+f"(h[43])
      :: "memory");
  }
};
__device__ __forceinline__ void node_mma(float* g, const uint32_t* w, uint64_t dx) {
    asm volatile(
      "{\n.reg .b64 dx1, dx2, dx3;\n"
      "add.s64 dx1, %48, 2;\nadd.s64 dx2, %48, 4;\nadd.s64 dx3, %48, 6;\n"
      "wgmma.fence.sync.aligned;\n"
      "wgmma.mma_async.sync.aligned.m64n64k16.f32.bf16.bf16 {%0, %1, %2, %3, %4, %5, %6, %7, %8, %9, %10, %11, %12, %13, %14, %15, %16, %17, %18, %19, %20, %21, %22, %23, %24, %25, %26, %27, %28, %29, %30, %31}, {%32, %33, %34, %35}, %48, 0, 1, 1, 0;\n"
      "wgmma.mma_async.sync.aligned.m64n64k16.f32.bf16.bf16 {%0, %1, %2, %3, %4, %5, %6, %7, %8, %9, %10, %11, %12, %13, %14, %15, %16, %17, %18, %19, %20, %21, %22, %23, %24, %25, %26, %27, %28, %29, %30, %31}, {%36, %37, %38, %39}, dx1, 1, 1, 1, 0;\n"
      "wgmma.mma_async.sync.aligned.m64n64k16.f32.bf16.bf16 {%0, %1, %2, %3, %4, %5, %6, %7, %8, %9, %10, %11, %12, %13, %14, %15, %16, %17, %18, %19, %20, %21, %22, %23, %24, %25, %26, %27, %28, %29, %30, %31}, {%40, %41, %42, %43}, dx2, 1, 1, 1, 0;\n"
      "wgmma.mma_async.sync.aligned.m64n64k16.f32.bf16.bf16 {%0, %1, %2, %3, %4, %5, %6, %7, %8, %9, %10, %11, %12, %13, %14, %15, %16, %17, %18, %19, %20, %21, %22, %23, %24, %25, %26, %27, %28, %29, %30, %31}, {%44, %45, %46, %47}, dx3, 1, 1, 1, 0;\n"
      "wgmma.commit_group.sync.aligned;\nwgmma.wait_group.sync.aligned 0;\n}\n"
      : "=f"(g[0]), "=f"(g[1]), "=f"(g[2]), "=f"(g[3]), "=f"(g[4]), "=f"(g[5]), "=f"(g[6]), "=f"(g[7]), "=f"(g[8]), "=f"(g[9]), "=f"(g[10]), "=f"(g[11]), "=f"(g[12]), "=f"(g[13]), "=f"(g[14]), "=f"(g[15]), "=f"(g[16]), "=f"(g[17]), "=f"(g[18]), "=f"(g[19]), "=f"(g[20]), "=f"(g[21]), "=f"(g[22]), "=f"(g[23]), "=f"(g[24]), "=f"(g[25]), "=f"(g[26]), "=f"(g[27]), "=f"(g[28]), "=f"(g[29]), "=f"(g[30]), "=f"(g[31])
      : "r"(w[0]), "r"(w[1]), "r"(w[2]), "r"(w[3]), "r"(w[4]), "r"(w[5]), "r"(w[6]), "r"(w[7]), "r"(w[8]), "r"(w[9]), "r"(w[10]), "r"(w[11]), "r"(w[12]), "r"(w[13]), "r"(w[14]), "r"(w[15]), "l"(dx)
      : "memory");
}
__device__ __forceinline__ void node_mma2(float* u, float* a, const uint32_t* w, uint64_t dx) {
    asm volatile(
      "{\n.reg .b64 dx1, dx2, dx3, dy0, dy1, dy2, dy3;\n"
      "add.s64 dx1, %80, 2;\nadd.s64 dx2, %80, 4;\nadd.s64 dx3, %80, 6;\n"
      "add.s64 dy0, %80, 512;\nadd.s64 dy1, %80, 514;\nadd.s64 dy2, %80, 516;\nadd.s64 dy3, %80, 518;\n"
      "wgmma.fence.sync.aligned;\n"
      "wgmma.mma_async.sync.aligned.m64n64k16.f32.bf16.bf16 {%0, %1, %2, %3, %4, %5, %6, %7, %8, %9, %10, %11, %12, %13, %14, %15, %16, %17, %18, %19, %20, %21, %22, %23, %24, %25, %26, %27, %28, %29, %30, %31}, {%64, %65, %66, %67}, %80, 0, 1, 1, 0;\n"
      "wgmma.mma_async.sync.aligned.m64n64k16.f32.bf16.bf16 {%0, %1, %2, %3, %4, %5, %6, %7, %8, %9, %10, %11, %12, %13, %14, %15, %16, %17, %18, %19, %20, %21, %22, %23, %24, %25, %26, %27, %28, %29, %30, %31}, {%68, %69, %70, %71}, dx1, 1, 1, 1, 0;\n"
      "wgmma.mma_async.sync.aligned.m64n64k16.f32.bf16.bf16 {%0, %1, %2, %3, %4, %5, %6, %7, %8, %9, %10, %11, %12, %13, %14, %15, %16, %17, %18, %19, %20, %21, %22, %23, %24, %25, %26, %27, %28, %29, %30, %31}, {%72, %73, %74, %75}, dx2, 1, 1, 1, 0;\n"
      "wgmma.mma_async.sync.aligned.m64n64k16.f32.bf16.bf16 {%0, %1, %2, %3, %4, %5, %6, %7, %8, %9, %10, %11, %12, %13, %14, %15, %16, %17, %18, %19, %20, %21, %22, %23, %24, %25, %26, %27, %28, %29, %30, %31}, {%76, %77, %78, %79}, dx3, 1, 1, 1, 0;\n"
      "wgmma.commit_group.sync.aligned;\n"
      "wgmma.mma_async.sync.aligned.m64n64k16.f32.bf16.bf16 {%32, %33, %34, %35, %36, %37, %38, %39, %40, %41, %42, %43, %44, %45, %46, %47, %48, %49, %50, %51, %52, %53, %54, %55, %56, %57, %58, %59, %60, %61, %62, %63}, {%64, %65, %66, %67}, dy0, 0, 1, 1, 0;\n"
      "wgmma.mma_async.sync.aligned.m64n64k16.f32.bf16.bf16 {%32, %33, %34, %35, %36, %37, %38, %39, %40, %41, %42, %43, %44, %45, %46, %47, %48, %49, %50, %51, %52, %53, %54, %55, %56, %57, %58, %59, %60, %61, %62, %63}, {%68, %69, %70, %71}, dy1, 1, 1, 1, 0;\n"
      "wgmma.mma_async.sync.aligned.m64n64k16.f32.bf16.bf16 {%32, %33, %34, %35, %36, %37, %38, %39, %40, %41, %42, %43, %44, %45, %46, %47, %48, %49, %50, %51, %52, %53, %54, %55, %56, %57, %58, %59, %60, %61, %62, %63}, {%72, %73, %74, %75}, dy2, 1, 1, 1, 0;\n"
      "wgmma.mma_async.sync.aligned.m64n64k16.f32.bf16.bf16 {%32, %33, %34, %35, %36, %37, %38, %39, %40, %41, %42, %43, %44, %45, %46, %47, %48, %49, %50, %51, %52, %53, %54, %55, %56, %57, %58, %59, %60, %61, %62, %63}, {%76, %77, %78, %79}, dy3, 1, 1, 1, 0;\n"
      "wgmma.commit_group.sync.aligned;\n}\n"
      : "=f"(u[0]), "=f"(u[1]), "=f"(u[2]), "=f"(u[3]), "=f"(u[4]), "=f"(u[5]), "=f"(u[6]), "=f"(u[7]), "=f"(u[8]), "=f"(u[9]), "=f"(u[10]), "=f"(u[11]), "=f"(u[12]), "=f"(u[13]), "=f"(u[14]), "=f"(u[15]), "=f"(u[16]), "=f"(u[17]), "=f"(u[18]), "=f"(u[19]), "=f"(u[20]), "=f"(u[21]), "=f"(u[22]), "=f"(u[23]), "=f"(u[24]), "=f"(u[25]), "=f"(u[26]), "=f"(u[27]), "=f"(u[28]), "=f"(u[29]), "=f"(u[30]), "=f"(u[31]),
        "=f"(a[0]), "=f"(a[1]), "=f"(a[2]), "=f"(a[3]), "=f"(a[4]), "=f"(a[5]), "=f"(a[6]), "=f"(a[7]), "=f"(a[8]), "=f"(a[9]), "=f"(a[10]), "=f"(a[11]), "=f"(a[12]), "=f"(a[13]), "=f"(a[14]), "=f"(a[15]), "=f"(a[16]), "=f"(a[17]), "=f"(a[18]), "=f"(a[19]), "=f"(a[20]), "=f"(a[21]), "=f"(a[22]), "=f"(a[23]), "=f"(a[24]), "=f"(a[25]), "=f"(a[26]), "=f"(a[27]), "=f"(a[28]), "=f"(a[29]), "=f"(a[30]), "=f"(a[31])
      : "r"(w[0]), "r"(w[1]), "r"(w[2]), "r"(w[3]), "r"(w[4]), "r"(w[5]), "r"(w[6]), "r"(w[7]), "r"(w[8]), "r"(w[9]), "r"(w[10]), "r"(w[11]), "r"(w[12]), "r"(w[13]), "r"(w[14]), "r"(w[15]), "l"(dx)
      : "memory");
}

__device__ __forceinline__ uint32_t smem_u32(const void* p) { return (uint32_t)__cvta_generic_to_shared(p); }
__device__ __forceinline__ float ex2f(float x) { float y; asm("ex2.approx.ftz.f32 %0, %1;" : "=f"(y) : "f"(x)); return y; }
__device__ __forceinline__ float rcpf(float x) { float y; asm("rcp.approx.ftz.f32 %0, %1;" : "=f"(y) : "f"(x)); return y; }
__device__ __forceinline__ uint32_t pack_bf16(float lo, float hi) {
    uint32_t r; asm("cvt.rn.bf16x2.f32 %0, %1, %2;" : "=r"(r) : "f"(hi), "f"(lo)); return r;
}
__device__ __forceinline__ float bf_lo(uint32_t v) { return __uint_as_float(v << 16); }
__device__ __forceinline__ float bf_hi(uint32_t v) { return __uint_as_float(v & 0xFFFF0000u); }
template<int STRIDE>
__device__ __forceinline__ void cp16i(uint32_t dst, const char* base, uint32_t idx) {
    asm volatile("{\n.reg .b64 a;\nmad.wide.u32 a, %2, %3, %1;\ncp.async.cg.shared.global [%0], [a], 16;\n}\n" :: "r"(dst), "l"(base), "r"(idx), "n"(STRIDE) : "memory");
}
__device__ __forceinline__ void cp16e(uint32_t dst, const char* base, uint32_t idx, uint64_t pol) {
    asm volatile("{\n.reg .b64 a;\nmad.wide.u32 a, %2, 32, %1;\ncp.async.cg.shared.global.L2::cache_hint [%0], [a], 16, %3;\n}\n" :: "r"(dst), "l"(base), "r"(idx), "l"(pol) : "memory");
}
template<int STRIDE>
__device__ __forceinline__ void cp16z(uint32_t dst, const char* base, uint32_t idx, int k, int n, uint64_t pol) {
    if (STRIDE == 32)
        asm volatile("{\n.reg .b64 a;\n.reg .pred p;\nsetp.ge.s32 p, %3, %4;\nmad.wide.u32 a, %2, 32, %1;\ncp.async.cg.shared.global.L2::cache_hint [%0], [a], 16, p, %5;\n}\n"
                     :: "r"(dst), "l"(base), "r"(idx), "r"(k), "r"(n), "l"(pol) : "memory");
    else
        asm volatile("{\n.reg .b64 a;\n.reg .pred p;\nsetp.ge.s32 p, %3, %4;\nmad.wide.u32 a, %2, 128, %1;\ncp.async.cg.shared.global [%0], [a], 16, p;\n}\n"
                     :: "r"(dst), "l"(base), "r"(idx), "r"(k), "r"(n) : "memory");
}
template<int HI, bool Z>
__device__ __forceinline__ void cpx(uint32_t hi, uint32_t dst, uint32_t p, uint32_t lo, int k, int n) {
    if (Z) asm volatile("{\n.reg .b32 l;\n.reg .b64 a;\n.reg .pred q;\nsetp.ge.s32 q, %5, %6;\ndp2a.lo.u32.u32 l, %1, %2, %3;\nmov.b64 a, {l, %0};\ncp.async.cg.shared.global [%4], [a], 16, q;\n}\n"
                        :: "r"(hi), "r"(p), "r"(HI ? 0x8000u : 0x80u), "r"(lo), "r"(dst), "r"(k), "r"(n) : "memory");
    else asm volatile("{\n.reg .b32 l;\n.reg .b64 a;\ndp2a.lo.u32.u32 l, %1, %2, %3;\nmov.b64 a, {l, %0};\ncp.async.cg.shared.global [%4], [a], 16;\n}\n"
                      :: "r"(hi), "r"(p), "r"(HI ? 0x8000u : 0x80u), "r"(lo), "r"(dst) : "memory");
}
template<bool Z>
__device__ __forceinline__ void cpe(uint32_t hi, uint32_t dst, uint32_t idx, uint32_t lo, int k, int n, uint64_t pol) {
    if (Z) asm volatile("{\n.reg .b32 l;\n.reg .b64 a;\n.reg .pred q;\nsetp.ge.s32 q, %5, %6;\nmad.lo.u32 l, %1, 32, %2;\nmov.b64 a, {l, %0};\ncp.async.cg.shared.global.L2::cache_hint [%3], [a], 16, q, %4;\n}\n"
                        :: "r"(hi), "r"(idx), "r"(lo), "r"(dst), "l"(pol), "r"(k), "r"(n) : "memory");
    else asm volatile("{\n.reg .b32 l;\n.reg .b64 a;\nmad.lo.u32 l, %1, 32, %2;\nmov.b64 a, {l, %0};\ncp.async.cg.shared.global.L2::cache_hint [%3], [a], 16, %4;\n}\n"
                      :: "r"(hi), "r"(idx), "r"(lo), "r"(dst), "l"(pol) : "memory");
}
__device__ __forceinline__ void cp_commit() { asm volatile("cp.async.commit_group;" ::: "memory"); }
template<int N> __device__ __forceinline__ void cp_wait() { asm volatile("cp.async.wait_group %0;" :: "n"(N) : "memory"); }
__device__ __forceinline__ void mbar_init(uint32_t bar, int cnt) { asm volatile("mbarrier.init.shared.b64 [%0], %1;" :: "r"(bar), "r"(cnt) : "memory"); }
__device__ __forceinline__ void mbar_arrive(uint32_t bar) { asm volatile("mbarrier.arrive.shared.b64 _, [%0];" :: "r"(bar) : "memory"); }
__device__ __forceinline__ void mbar_expect(uint32_t bar, uint32_t bytes) { asm volatile("mbarrier.arrive.expect_tx.shared.b64 _, [%0], %1;" :: "r"(bar), "r"(bytes) : "memory"); }
__device__ __forceinline__ void mbar_cp_arrive(uint32_t bar) { asm volatile("cp.async.mbarrier.arrive.noinc.shared.b64 [%0];" :: "r"(bar) : "memory"); }
__device__ __forceinline__ void mbar_wait(uint32_t bar, uint32_t parity) {
    asm volatile("{\n.reg .pred p;\n.reg .u32 n;\nmbarrier.try_wait.parity.shared.b64 p, [%0], %1;\n@p bra DONE_%=;\nmov.u32 n, 0;\n"
                 "WAIT_%=:\nmbarrier.try_wait.parity.shared.b64 p, [%0], %1, 0x100000;\n@p bra DONE_%=;\n"
                 "add.u32 n, n, 1;\nsetp.lt.u32 p, n, 0x400000;\n@p bra WAIT_%=;\ntrap;\nDONE_%=:\n}\n"
                 :: "r"(bar), "r"(parity) : "memory");
}
__device__ __forceinline__ void mbar_wait_c(uint32_t bar, uint32_t parity) {
    asm volatile("{\n.reg .pred p;\nWAIT_%=:\nmbarrier.try_wait.parity.shared.b64 p, [%0], %1;\n@p bra DONE_%=;\nbra WAIT_%=;\nDONE_%=:\n}\n"
                 :: "r"(bar), "r"(parity) : "memory");
}
__device__ __forceinline__ void mbar_wait_h(uint32_t bar, uint32_t parity) {
    asm volatile("{\n.reg .pred p;\nWAIT_%=:\nmbarrier.try_wait.parity.shared.b64 p, [%0], %1, 0x100000;\n@p bra DONE_%=;\nbra WAIT_%=;\nDONE_%=:\n}\n"
                 :: "r"(bar), "r"(parity) : "memory");
}
__device__ __forceinline__ uint32_t lds32(uint32_t a) { uint32_t v; asm volatile("ld.shared.u32 %0, [%1];" : "=r"(v) : "r"(a) : "memory"); return v; }
__device__ __forceinline__ void sts32(uint32_t a, uint32_t v) { asm volatile("st.shared.u32 [%0], %1;" :: "r"(a), "r"(v) : "memory"); }
__device__ __forceinline__ uint2 lds64(uint32_t a) { uint2 v; asm volatile("ld.shared.v2.u32 {%0,%1}, [%2];" : "=r"(v.x), "=r"(v.y) : "r"(a) : "memory"); return v; }
__device__ __forceinline__ uint4 lds128(uint32_t a) { uint4 v; asm volatile("ld.shared.v4.u32 {%0,%1,%2,%3}, [%4];" : "=r"(v.x), "=r"(v.y), "=r"(v.z), "=r"(v.w) : "r"(a) : "memory"); return v; }
__device__ __forceinline__ void sts128(uint32_t a, uint4 v) { asm volatile("st.shared.v4.u32 [%0], {%1,%2,%3,%4};" :: "r"(a), "r"(v.x), "r"(v.y), "r"(v.z), "r"(v.w) : "memory"); }
__device__ __forceinline__ void ldsm4t(uint32_t* v, uint32_t a) {
    asm volatile("ldmatrix.sync.aligned.m8n8.x4.trans.shared.b16 {%0,%1,%2,%3}, [%4];" : "=r"(v[0]), "=r"(v[1]), "=r"(v[2]), "=r"(v[3]) : "r"(a) : "memory");
}
__device__ __forceinline__ void stsm4t(uint32_t a, const uint32_t* v) {
    asm volatile("stmatrix.sync.aligned.m8n8.x4.trans.shared.b16 [%0], {%1,%2,%3,%4};" :: "r"(a), "r"(v[0]), "r"(v[1]), "r"(v[2]), "r"(v[3]) : "memory");
}
__device__ __forceinline__ int atoms_inc(uint32_t a) { int v; asm volatile("atom.shared.add.u32 %0, [%1], 1;" : "=r"(v) : "r"(a) : "memory"); return v; }
__device__ __forceinline__ bool elect_one() {
    uint32_t el;
    asm volatile("{\n.reg .pred p;\nelect.sync _|p, 0xffffffff;\nselp.u32 %0, 1, 0, p;\n}" : "=r"(el));
    return el != 0;
}
__device__ __forceinline__ float tanhf_a(float x) { float y; asm("tanh.approx.f32 %0, %1;" : "=f"(y) : "f"(x)); return y; }
__device__ __forceinline__ const char* as_pair(const void* p, uint32_t scratch) {
    const char* r;
    asm volatile("st.shared.u64 [%1], %2;\nld.volatile.shared.u64 %0, [%1];" : "=l"(r) : "r"(scratch), "l"(p) : "memory");
    return r;
}
__device__ __forceinline__ void ld_unit(uint4& v, const char* p, bool ok) {
    asm volatile("{\n.reg .pred q;\nsetp.ne.u32 q, %5, 0;\n@q ld.relaxed.gpu.global.v4.u32 {%0,%1,%2,%3}, [%4];\n}"
                 : "+r"(v.x), "+r"(v.y), "+r"(v.z), "+r"(v.w) : "l"(p), "r"((uint32_t)ok) : "memory");
}
__device__ __forceinline__ void ld_unit(uint2& v, const char* p, bool ok) {
    asm volatile("{\n.reg .pred q;\nsetp.ne.u32 q, %3, 0;\n@q ld.relaxed.gpu.global.v2.u32 {%0,%1}, [%2];\n}"
                 : "+r"(v.x), "+r"(v.y) : "l"(p), "r"((uint32_t)ok) : "memory");
}
__device__ __forceinline__ void bulk_ld(uint32_t dst, const void* src, int bytes, uint32_t bar) {
    mbar_expect(bar, bytes);
    if (bytes > 0) asm volatile("cp.async.bulk.shared::cluster.global.mbarrier::complete_tx::bytes [%0], [%1], %2, [%3];" :: "r"(dst), "l"(src), "r"(bytes), "r"(bar) : "memory");
}
__device__ __forceinline__ void sent(unsigned* gbar, uint32_t src) {
    asm volatile("cp.reduce.async.bulk.global.shared::cta.bulk_group.add.u32 [%0], [%1], 16;\ncp.async.bulk.commit_group;" :: "l"(gbar + 4), "r"(src) : "memory");
}
__device__ __forceinline__ uint32_t ld_hint(unsigned* p) { uint32_t v; asm volatile("ld.relaxed.gpu.global.u32 %0, [%1];" : "=r"(v) : "l"(p) : "memory"); return v; }
__device__ __forceinline__ void bulk_st(void* dst, uint32_t src, int bytes) {
    asm volatile("cp.async.bulk.global.shared::cta.bulk_group [%0], [%1], %2;" :: "l"(dst), "r"(src), "r"(bytes) : "memory");
}

__device__ __forceinline__ void finish(uint4& a, const uint4& xu, const uint4& xv) {
    asm("{\n.reg .b32 z;\nfma.rn.relu.bf16x2 z, %0, %3, %1;\nadd.rn.bf16x2 %0, z, %2;\n}" : "+r"(a.x) : "r"(xu.x), "r"(xv.x), "r"(0x3F803F80u));
    asm("{\n.reg .b32 z;\nfma.rn.relu.bf16x2 z, %0, %3, %1;\nadd.rn.bf16x2 %0, z, %2;\n}" : "+r"(a.y) : "r"(xu.y), "r"(xv.y), "r"(0x3F803F80u));
    asm("{\n.reg .b32 z;\nfma.rn.relu.bf16x2 z, %0, %3, %1;\nadd.rn.bf16x2 %0, z, %2;\n}" : "+r"(a.z) : "r"(xu.z), "r"(xv.z), "r"(0x3F803F80u));
    asm("{\n.reg .b32 z;\nfma.rn.relu.bf16x2 z, %0, %3, %1;\nadd.rn.bf16x2 %0, z, %2;\n}" : "+r"(a.w) : "r"(xu.w), "r"(xv.w), "r"(0x3F803F80u));
}

constexpr float EPS2 = 2e-6f;
constexpr float TAU = 2.5e-5f;

template<bool HALF>
__device__ __forceinline__ void make_wfrag(uint32_t* f, const uint32_t* v) {
    const uint32_t v0 = v[0], v1 = v[1], v2 = v[2], v3 = v[3];
    f[0] = __byte_perm(v0, v1, 0x5410); f[1] = __byte_perm(v0, v1, 0x7632);
    f[2] = __byte_perm(v2, v3, 0x5410); f[3] = __byte_perm(v2, v3, 0x7632);
    if (HALF) {
        #pragma unroll
        for (int i = 0; i < 4; i++) asm("mul.rn.bf16x2 %0, %0, %1;" : "+r"(f[i]) : "r"(0x3F003F00u));
    }
}

template<int NP>
__device__ __forceinline__ void epi_fast(const float* g, const float* h, float m1, float m2,
                                         float& n0, float& d0, float& n1, float& d1, float& dmin)
{
    constexpr int JC = NP >= 6 ? NP - 1 - 2 : NP >= 4 ? NP - 2 : NP - 1;
    constexpr int JT = NP < 3 ? -1 : JC < NP - 1 ? JC : NP - 2;
    #pragma unroll
    for (int j = 0; j < NP; j++) {
        float t0 = tanhf_a(g[4*j+0]), t1 = tanhf_a(g[4*j+1]), t2 = tanhf_a(g[4*j+2]), t3 = tanhf_a(g[4*j+3]);
        auto add_d = [&]() {
            if (j == 0) { d0 = t0 + (2.f * (JT + 1) + EPS2); d1 = t2 + (2.f * (JT + 1) + EPS2); } else { d0 += t0; d1 += t2; }
            d0 += t1; d1 += t3;
        };
        if (j <= JT) add_d();
        if (j == NP - 1) { t0 = fmaf(t0, m1, m1); t1 = fmaf(t1, m2, m2); t2 = fmaf(t2, m1, m1); t3 = fmaf(t3, m2, m2); }
        else { t0 += 1.f; t1 += 1.f; t2 += 1.f; t3 += 1.f; }
        if (j > JT) add_d();
        if (j == 0) { n0 = t0 * h[0]; n1 = t2 * h[2]; } else { n0 = fmaf(t0, h[4*j], n0); n1 = fmaf(t2, h[4*j+2], n1); }
        n0 = fmaf(t1, h[4*j+1], n0); n1 = fmaf(t3, h[4*j+3], n1);
        if (j == JC) dmin = fminf(d0, d1);
    }
}

__device__ __noinline__ float4 epi_exact(const float4* gh, int np, int dv)
{
    float n0 = 0.f, d0 = EPS2, n1 = 0.f, d1 = EPS2;
    #pragma unroll 2
    for (int j = 0; j < np; j++) {
        const float4 g = gh[j], h = gh[NPMAX + j];
        const float ma = (2 * j < dv) ? 2.f : 0.f, mb = (2 * j + 1 < dv) ? 2.f : 0.f;
        const float e0 = ma * rcpf(1.f + ex2f(-2.f * LOG2E * g.x)), e1 = mb * rcpf(1.f + ex2f(-2.f * LOG2E * g.y));
        const float e2 = ma * rcpf(1.f + ex2f(-2.f * LOG2E * g.z)), e3 = mb * rcpf(1.f + ex2f(-2.f * LOG2E * g.w));
        d0 += e0 + e1; n0 = fmaf(e0, h.x, fmaf(e1, h.y, n0));
        d1 += e2 + e3; n1 = fmaf(e2, h.z, fmaf(e3, h.w, n1));
    }
    return make_float4(n0, d0, n1, d1);
}
template<int NP>
__device__ __forceinline__ void epi_dump(const float* g, const float* h, float4* gh) {
    #pragma unroll
    for (int i = 0; i < NP; i++) {
        gh[i] = make_float4(g[4*i], g[4*i+1], g[4*i+2], g[4*i+3]);
        gh[NPMAX + i] = make_float4(h[4*i], h[4*i+1], h[4*i+2], h[4*i+3]);
    }
}

__device__ __noinline__ void slow_bin(const __nv_bfloat16* x, const __nv_bfloat16* ea, const int* src, const int* dst,
                                      const __nv_bfloat16* wa, const __nv_bfloat16* wb, const __nv_bfloat16* wc,
                                      const __nv_bfloat16* wu, const __nv_bfloat16* wv, __nv_bfloat16* out,
                                      int E, int node0, int nn, int nthr)
{
    const int tid = threadIdx.x, lane = tid & 31;
    for (int i = tid; i < nn * 128; i += nthr) g_slow[(size_t)node0 * 128 + i] = 0.f;
    asm volatile("bar.sync 1, %0;" :: "r"(nthr) : "memory");
    for (int e0 = (tid >> 5) * 32; e0 < E; e0 += nthr) {
        int d = (e0 + lane < E) ? dst[e0 + lane] - node0 : -1;
        unsigned m = __ballot_sync(~0u, d >= 0 && d < nn);
        while (m) {
            int l = __ffs(m) - 1; m &= m - 1;
            int e = e0 + l, n = node0 + __shfl_sync(~0u, d, l), s = src[e];
            float g0 = 0, g1 = 0, h0 = 0, h1 = 0;
            for (int k = 0; k < 64; k++) {
                float xs = __bfloat162float(x[(size_t)s * 64 + k]), xd = __bfloat162float(x[(size_t)n * 64 + k]);
                uint32_t b2 = *(const uint32_t*)(wb + k * 64 + 2 * lane), v2 = *(const uint32_t*)(wv + k * 64 + 2 * lane);
                uint32_t a2 = *(const uint32_t*)(wa + k * 64 + 2 * lane);
                g0 = fmaf(xs, bf_lo(b2), fmaf(xd, bf_lo(a2), g0)); g1 = fmaf(xs, bf_hi(b2), fmaf(xd, bf_hi(a2), g1));
                h0 = fmaf(xs, bf_lo(v2), h0); h1 = fmaf(xs, bf_hi(v2), h1);
            }
            for (int k = 0; k < 16; k++) {
                float ev = __bfloat162float(ea[(size_t)e * 16 + k]);
                uint32_t c2 = *(const uint32_t*)(wc + k * 64 + 2 * lane);
                g0 = fmaf(ev, bf_lo(c2), g0); g1 = fmaf(ev, bf_hi(c2), g1);
            }
            float s0 = rcpf(1.f + ex2f(-LOG2E * g0)), s1 = rcpf(1.f + ex2f(-LOG2E * g1));
            float* acc = g_slow + (size_t)n * 128 + 4 * lane;
            atomicAdd(acc + 0, s0 * h0); atomicAdd(acc + 1, s0);
            atomicAdd(acc + 2, s1 * h1); atomicAdd(acc + 3, s1);
        }
    }
    __threadfence();
    asm volatile("bar.sync 1, %0;" :: "r"(nthr) : "memory");
    for (int i = tid; i < nn * 32; i += nthr) {
        int n = node0 + (i >> 5), cp = i & 31;
        float4 a = __ldcg((const float4*)(g_slow + (size_t)n * 128 + 4 * cp));
        float u0 = 0, u1 = 0;
        for (int k = 0; k < 64; k++) {
            float xd = __bfloat162float(x[(size_t)n * 64 + k]);
            uint32_t w2 = *(const uint32_t*)(wu + k * 64 + 2 * cp);
            u0 = fmaf(xd, bf_lo(w2), u0); u1 = fmaf(xd, bf_hi(w2), u1);
        }
        uint32_t xv = *(const uint32_t*)(x + (size_t)n * 64 + 2 * cp);
        float z0 = u0 + a.x / (a.y + 1e-6f), z1 = u1 + a.z / (a.w + 1e-6f);
        *(uint32_t*)(out + (size_t)n * 64 + 2 * cp) = pack_bf16(bf_lo(xv) + fmaxf(z0, 0.f), bf_hi(xv) + fmaxf(z1, 0.f));
    }
}

__global__ void __launch_bounds__(256) slow_kernel(const __nv_bfloat16* x, const __nv_bfloat16* ea, const int* src, const int* dst,
        const __nv_bfloat16* wa, const __nv_bfloat16* wb, const __nv_bfloat16* wc, const __nv_bfloat16* wu, const __nv_bfloat16* wv,
        __nv_bfloat16* out, int N, int E, int npb)
{
    int node0 = blockIdx.x * npb;
    slow_bin(x, ea, src, dst, wa, wb, wc, wu, wv, out, E, node0, max(0, min(npb, N - node0)), 256);
}

constexpr int XS_BYTES = NPMAX * 1024;
constexpr int ES_BYTES = NPMAX * 256;
constexpr int SM_XS = 0;
constexpr int SM_XU = SM_XS + 3 * NSTAGE * XS_BYTES;
constexpr int SM_TAB = SM_XU + NPB_MAX * 128;
constexpr int SM_ES = SM_TAB + (NPB_MAX + 2) * 128;
constexpr int SM_WC = SM_ES + 3 * NSTAGE * ES_BYTES;
constexpr int SM_OH = SM_WC + 2048;
constexpr int SM_EID = SM_OH + 256;
constexpr int SM_SRC = SM_EID + (SLOT_CAP + 32) * 4;
constexpr int SM_TINFO = SM_SRC + (SLOT_CAP + 32) * 2;
constexpr int SM_MISC = SM_TINFO + TILE_CAP * 32;
constexpr int SM_CLAIM = SM_TAB + (NPB_MAX + 1) * 128;
constexpr int SM_BARS = SM_MISC + 32 * 4;
constexpr int SM_ABAR = SM_BARS + 6 * 48;
constexpr int SM_XBAR = SM_ABAR + 10 * 8;
constexpr int SM_GBAR = SM_XBAR + 6 * 8;
constexpr int SM_WL = SM_GBAR + 97 * 8;
constexpr int WST = 9;
constexpr int SMEM_BYTES = SM_WL + (96 + WST) * 8;
constexpr int SM_P2 = 0, SM_P1 = 6 * 384 * 16;
constexpr int SM_DEG = SM_P1 + P1B;
constexpr int SM_CLS = SM_DEG + 512 * 4;
constexpr int SM_HIST = SM_CLS + NCLS * 4;
constexpr int SM_XLIST = SM_HIST + NB_MAX * 4;
constexpr int SM_SORT = SM_XLIST + XCAP * 8;
constexpr int SM_SDEG = SM_SORT + NPB_MAX * 4;
constexpr int SM_PAIR = SM_SDEG + NPB_MAX * 2;
constexpr int SM_IDX = SM_EID;
constexpr int SM_WR = SM_TAB;
static_assert(TILE_CAP <= 128 && TR >= 2 && SM_ES % 256 == 0 && NSTAGE == 2 && SM_BARS % 16 == 0 && SM_TINFO % 16 == 0 && SM_EID % 128 == 0 && SM_TAB % 1024 == 0 && SM_XU % 1024 == 0 && SM_TINFO % 8 == 0 && SM_OH % 16 == 0 && SM_XLIST % 8 == 0 && SM_PAIR % 8 == 0, "align");
static_assert(P1B % 16 == 0 && P2B <= SM_P1 && NB_MAX <= 6 * 24 && SM_PAIR + 128 * 8 <= SM_XU && CH_MAX * 4 <= SM_SRC - SM_EID && SM_DEG >= 3 << 14, "alias");
static_assert(SMEM_BYTES <= 232448, "smem");
constexpr uint32_t C_BRK = 16  , C_CONT = 32, C_MORE = 64;
constexpr uint32_t ONE_F = 0x3F800000u;
constexpr int NONE = NPB_MAX;

__device__ __forceinline__ uint2 tile_info(uint32_t e) {
    const uint32_t y = (uint32_t)((int)e >> 16) & (ONE_F | 0x1FFFu);
    return make_uint2(e, (e & 0x1F000000u) ? y | 0x80000000u : y);
}
__device__ __forceinline__ bool unpad(uint32_t w1, int np, float ga, float gb, float& d0, float& d1, int& dv) {
    const int pad = (int)w1 < 0 ? (w1 >> 8) & 31 : 0;
    dv = 2 * np - 2 - pad + ((int)w1 > 127) + ((int)w1 >= (int)ONE_F);
    float t0 = TAU * 2 * np, t1 = t0;
    if (pad) {
        t0 = fmaxf(t0, d0 * (1.f / 1024)); t1 = fmaxf(t1, d1 * (1.f / 1024));
        asm volatile("tanh.approx.f32 %0, %0;\ntanh.approx.f32 %1, %1;" : "+f"(ga), "+f"(gb));
        d0 -= pad * (1.f + ga); d1 -= pad * (1.f + gb);
    }
    if (dv == 0) { d0 = d1 = EPS2; t0 = t1 = 0.f; }
    return __any_sync(~0u, d0 < t0 || d1 < t1);
}
__device__ __forceinline__ uint64_t desc_sw128(uint32_t a) {
    return (uint64_t)((a & 0x3FFFF) >> 4) | ((uint64_t)1 << 16) | ((uint64_t)64 << 32) | ((uint64_t)1 << 62);
}

template<int PART>
__device__ __forceinline__ void tables(uint8_t* smem, uint32_t sv, uint2 d4, int id, int ngroups) {
    int* misc = (int*)(smem + SM_MISC);
    const int t = id & 3, lane = id & 31;
    const uint32_t nd = sv & 0xFFFF;
    const int g = id >> 2;
    const int dg = ((t & 2 ? d4.y : d4.x) >> (16 * (t & 1))) & 0xFFFF;
    const uint32_t hi2 = __vmaxu2(d4.x, d4.y), lo2 = __vminu2(d4.x, d4.y);
    const int mx = max(hi2 >> 16, hi2 & 0xFFFF), mn = min(lo2 >> 16, lo2 & 0xFFFF);
    int left = (mx + 1) >> 1;
    int nx = ngroups + 4 + g;
    const bool two = left > NPMAX, odd = left > 2 * NPMAX || (two && nx >= TILE_CAP - TILE_X);
    const uint32_t w0 = nd * 128 + ((nd & 7) << 4);
    auto tile = [&](int tl, int np, int done, uint32_t flags, int next) {
        const int dv = min(max(dg - done, 0), 2 * np);
        const bool gen = mn - done < 2 * np - 2;
        const uint32_t code = (uint32_t)np | flags | (gen || flags ? C_BRK : 0u);
        const uint32_t w1 = code | (dv == 2 * np ? 0x8000u : dv == 2 * np - 1 ? 128u : (2 * np - 2 - dv) << 8);
        if (tl < TILE_CAP) *(uint2*)(smem + SM_TINFO + tl * 32 + t * 8) = make_uint2((dv ? (sv >> 16) + done : 0) | ((gen ? (np > 8 ? 15 : np > 5 ? 14 : 13) : np) << 16) | (next << 20) | ((uint32_t)dv << 27), w0 | (np == 0 ? 0u : w1 << 16));
    };
    if (PART == 1) {
        if (two && !odd) tile(nx, left >> 1, (left + 1) & ~1, C_CONT, 0);
        return;
    }
    const unsigned sm = __ballot_sync(~0u, odd);
    if (__builtin_expect(odd, 0)) {
        int nt = (left + NPMAX - 1) / NPMAX, tl = g, done = 0;
        if (t == 0) { nx = atomicAdd(&misc[5], nt - 1); if (nx + nt - 1 > TILE_CAP) misc[1] = 1; }
        nx = __shfl_sync(sm, nx, lane & ~3);
        if (nx + nt - 1 > TILE_CAP) left = 0;
        uint32_t cont = 0;
        #pragma unroll 1
        while (left > 0) {
            const int np = (left + nt - 1) / nt;
            left -= np; nt--;
            tile(tl, np, done, cont | (left > 0 ? C_MORE : 0u), left > 0 ? nx : 0);
            tl = nx++; cont = C_CONT; done += 2 * np;
        }
    } else if (!T1W && __any_sync(~sm, two)) {
        tile(g >= ngroups + 4 ? ngroups : g, two ? (left + 1) >> 1 : left, 0, two ? C_MORE : 0u, two ? nx : 0);
        tile(two ? nx : TILE_CAP, left >> 1, (left + 1) & ~1, C_CONT, 0);
    } else tile(g >= ngroups + 4 ? ngroups : g, two ? (left + 1) >> 1 : left, 0, two ? C_MORE : 0u, two ? nx : 0);
}

template<bool LO32>
__global__ void __launch_bounds__(THREADS, 1)
gcn_kernel(const int* __restrict__ dst, unsigned* gbar, char* gs, const int* __restrict__ src, int E, int ch, int N, int npb, uint32_t magic,
           const __nv_bfloat16* __restrict__ x, const __nv_bfloat16* __restrict__ ea,
           const __nv_bfloat16* __restrict__ wa, const __nv_bfloat16* __restrict__ wb, const __nv_bfloat16* __restrict__ wc,
           const __nv_bfloat16* __restrict__ wu, const __nv_bfloat16* __restrict__ wv,
           __nv_bfloat16* out, int4 wrow, const __grid_constant__ CUtensorMap tm2, const __grid_constant__ CUtensorMap tmw,
           const __grid_constant__ CUtensorMap tmc, const __grid_constant__ CUtensorMap tmx)
{
    extern __shared__ __align__(1024) uint8_t smem[];
    int* cls = (int*)(smem + SM_CLS);
    int* misc = (int*)(smem + SM_MISC);
    uint32_t* xlist = (uint32_t*)(smem + SM_XLIST);
    WG0(); WS(0);
    const uint32_t sbase = smem_u32(smem);
    const int tid = threadIdx.x, lane = tid & 31;
    const int b = blockIdx.x, nb = gridDim.x;
    const int cnt = max(0, min(ch, E - b * ch));
    const int node0 = b * npb;
    auto src_ld = [&]() { bulk_ld(sbase + SM_XU, src + b * ch, cnt * 4, sbase + SM_ABAR + 32); };
    auto box_ld = [&](uint32_t dst, const CUtensorMap* tm, int col, int row, uint32_t bar) {
        asm volatile("cp.async.bulk.tensor.2d.shared::cluster.global.mbarrier::complete_tx::bytes [%0], [%1, {%3, %4}], [%2];"
            :: "r"(dst), "l"((uint64_t)tm), "r"(bar), "r"(col), "r"(row) : "memory");
    };
    auto w_ld = [&]() {
        mbar_expect(sbase + SM_ABAR + 24, 272 * 128);
        box_ld(sbase + SM_WR, &tmw, 0, wrow.y, sbase + SM_ABAR + 24); box_ld(sbase + SM_WR + 64 * 128, &tmc, 0, 0, sbase + SM_ABAR + 24);
        box_ld(sbase + SM_WR + 80 * 128, &tmw, 0, wrow.w, sbase + SM_ABAR + 24); box_ld(sbase + SM_WR + 144 * 128, &tmw, 0, wrow.x, sbase + SM_ABAR + 24);
        box_ld(sbase + SM_WR + 208 * 128, &tmw, 0, wrow.z, sbase + SM_ABAR + 24);
    };
    auto x_ld = [&](int k0, int k1) {
        if (tid == XT) {
            for (int k = k0; k < min(k1, 6); k++) {
                mbar_expect(sbase + SM_XBAR + k * 8, 8192);
                box_ld(sbase + SM_XU + k * 8192, &tmx, 0, node0 + 64 * k, sbase + SM_XBAR + k * 8);
            }
        }
    };
    if (tid >= 384) {
        if (elect_one()) {
            const int v = (tid >> 5) & 3;
            mbar_init(sbase + SM_ABAR + v * 8, 1);
            asm volatile("fence.mbarrier_init.release.cluster;" ::: "memory");
            if (v < 3) bulk_ld(sbase + SM_IDX + v * 8192, dst + b * ch + v * 2048, min(max(cnt * 4 - v * 8192, 0), 8192), sbase + SM_ABAR + v * 8);
            else {
                mbar_init(sbase + SM_ABAR + 32, 1); mbar_init(sbase + SM_ABAR + 40, 1); mbar_init(sbase + SM_GBAR + 96 * 8, 32); mbar_init(sbase + SM_ABAR + 72, 12);
                if (WV == -1) w_ld();
                for (int k = 0; k < 6; k++) mbar_init(sbase + SM_XBAR + k * 8, 1);
            }
            #pragma unroll 8
            for (int i = 0; i < 24; i++) mbar_init(sbase + SM_GBAR + (v * 24 + i) * 8, 32);
            if (tid < 480) {
                #pragma unroll
                for (int i = 0; i < 2; i++) { mbar_init(sbase + SM_BARS + (v * 2 + i) * 48, 64); mbar_init(sbase + SM_BARS + (v * 2 + i) * 48 + 8, 128); }
                mbar_init(sbase + SM_ABAR + 48 + v * 8, 4);
            }
            asm volatile("fence.mbarrier_init.release.cluster;" ::: "memory");
        }
    }
    if (tid >= 128 && tid < 132) asm volatile("prefetch.tensormap [%0];" :: "l"((uint64_t)(tid == 128 ? &tmw : tid == 129 ? &tmc : tid == 130 ? &tm2 : &tmx)) : "memory");
    uint32_t tag = 0;
    if (tid < 32) asm volatile("ld.relaxed.gpu.global.u32 %0, [%1];" : "=r"(tag) : "l"(gbar));
    const int warp = (int)__reduce_max_sync(~0u, (unsigned)tid >> 5);
    const int wg = warp >> 2, w = warp & 3;
    const int q = lane >> 2, t = lane & 3;
    const int ch0 = 16 * w + 2 * q;
    const int nn = max(0, min(npb, N - node0));
    if (sbase & 1023) __trap();

    sts32(sbase + SM_DEG + tid * 4, tid < NPB_MAX ? 0 : 0x80000000u);
    if (tid < NCLS + NB_MAX) cls[tid] = tid < NCLS ? 0 : (tid - NCLS) * CE + 64;
    else if (wg == 2) {
        if (w < 2) {
            *(uint32_t*)(smem + SM_OH + (tid & 63) * 4) = t != (q >> 1) ? 0u : (w == 0 ? 0x00003F00u : 0x3F000000u);
        } else if (w == 2) *(uint32_t*)(smem + SM_TAB + NPB_MAX * 128 + lane * 4) = 0u;
        else misc[lane] = lane == 5 ? TILE_CAP - TILE_X : lane == 8;
    }
    if (warp == 13 && lane < WST * 2) sts32(sbase + SM_WL + 768 + lane * 4, NONE * 0x10001u);
    if (warp == 14) sts32(sbase + SM_TINFO + 96 * 32 + lane * 4, 0);
    if (warp == 15) sts32(sbase + SM_CLAIM + lane * 4, lane == 0 ? 3 : 0x40000000);
    if (tid == 0) sts32(sbase + SM_PAIR, tag);
    if (wg < 3) { asm volatile("bar.sync 1, 384;" ::: "memory"); tag = lds32(sbase + SM_PAIR); }
    tag = (tag & 1) | 2;
    if (wg < 3) {
        const uint32_t d0 = ((NPB_MAX + ((2 * lane) & 15) + 16 * (b & 1)) * 4 | (tag << 14)) * 0x10001u, d1 = d0 + 0x40004u, d2 = tag << 16;
        #pragma unroll 1
        for (int i = tid; i < P1B / 16; i += 384) {
            sts128(sbase + SM_P1 + i * 16, make_uint4(d0, d0, d1, d1));
            sts128(sbase + SM_P2 + i * 16, make_uint4(d2, d2, d2, d2)); sts128(sbase + SM_P2 + (P2B - P1B) + i * 16, make_uint4(d2, d2, d2, d2));
        }
    }
    if (WV == -2 && tid == 480) w_ld();
    WS(1);
    __syncthreads();
    if (wg == 3) tag = lds32(sbase + SM_P2) >> 16;
    const int p1n = (256 + nb * (CE * 2) + 15) & ~15;

    uint32_t ent[EPT];
    #pragma unroll
    for (int v = 0; v < EPT / 4; v++) {
        mbar_wait_c(sbase + SM_ABAR + v * 8, 0);
        if (v == 0 && tid == 480) { src_ld(); if (WV == 0) w_ld(); }
        const uint32_t off = v * (THREADS * 4) + tid * 4;
        if (off < (uint32_t)cnt) {
            const uint32_t ia = sbase + SM_IDX + off * 4;
            const uint4 u = lds128(ia);
            uint32_t dv[4] = {u.x, u.y, u.z, u.w}, ps[4], ck[4];
            uint32_t* en = ent + 4 * v;
            #pragma unroll
            for (int k = 0; k < 4; k++) {
                dv[k] = min(dv[k], (uint32_t)(nb * npb - 1));
                ps[k] = __umulhi(dv[k], magic); en[k] = atoms_inc(sbase + SM_HIST + ps[k] * 4);
            }
            #pragma unroll
            for (int k = 0; k < 4; k++) {
                dv[k] = (dv[k] - ps[k] * npb) * 4 + (tag << 14);
                ck[k] = en[k] - ps[k] * CE;
                en[k] ^= ps[k] * 4 & 60;
            }
            if (__builtin_expect(max(max(ck[0], ck[1]), max(ck[2], ck[3])) >= 64 + CE, 0)) {
                #pragma unroll
                for (int k = 0; k < 4; k++) {
                    if (ck[k] >= 64 + CE) {
                        uint32_t j; asm volatile("atom.shared.inc.u32 %0, [%1], 0x7fffffff;" : "=r"(j) : "r"(sbase + SM_MISC + 8) : "memory");
                        j = min(j, 63u);
                        sts32(sbase + SM_P1 + j * 4, dv[k] | ((j < 63 ? ps[k] : 255u) << 16));
                        en[k] = j;
                    }
                }
            }
            #pragma unroll
            for (int k = 0; k < 4; k++)
                asm volatile("{\n.reg .pred p;\nsetp.ge.u32 p, %2, 64;\n@p st.shared.u16 [%0], %1;\n}" :: "r"(sbase + SM_P1 + 128 + en[k] * 2), "r"(dv[k]), "r"(en[k]) : "memory");
        }
    }
    WS(5);
    __syncthreads();
    if (tid == P1T) {
        asm volatile("fence.proxy.async.shared::cta;" ::: "memory");
        bulk_st(gs + b * (P1B + P2B), sbase + SM_P1, p1n);
        asm volatile("cp.async.bulk.commit_group;" ::: "memory");
    }
    if (WV == 3 && tid == 480) w_ld();
    if (PRE) {
        #pragma unroll
        for (int i = 0; i < EPT; i++) { ent[i] = sbase + SM_P2 + ent[i] * 4; asm volatile("" : "+r"(ent[i])); }
    }
    mbar_wait_c(sbase + SM_ABAR + 32, 0);
    #pragma unroll
    for (int v = 0; v < EPT / 4; v++) {
        const uint32_t off = v * (THREADS * 4) + tid * 4;
        if (off < (uint32_t)cnt) {
            const uint4 sv = lds128(sbase + SM_XU + off * 4);
            const uint32_t* uu = ent + 4 * v;
            const uint32_t ss[4] = {sv.x, sv.y, sv.z, sv.w};
            #pragma unroll
            for (int k = 0; k < 4; k++) sts32(PRE ? uu[k] : sbase + SM_P2 + uu[k] * 4, (ss[k] & 0xFFFF) | (((off + k) << 19) + (tag << 16)));
        }
    }
    WS(7);
    __syncthreads();
    auto p2_st = [&]() {
        if (tid == 448) {
            asm volatile("fence.proxy.async.shared::cta;" ::: "memory");
            bulk_st(gs + b * (P1B + P2B) + P1B, sbase + SM_P2, 256 + nb * (CE * 4));
            asm volatile("cp.async.bulk.commit_group;" ::: "memory");
        }
    };
    if (!DEC1) p2_st();
    WSL(8);

    const int ngroups = (nn + 3) >> 2;
    if (wg == 3) {
        asm volatile("setmaxnreg.dec.sync.aligned.u32 56;");
        if (DEC1) p2_st();
        WS(2);
        const char* const ga = as_pair((const char*)x + (w < 3 ? 0 : (size_t)node0 * 128) + (lane & 7) * 16, sbase + SM_PAIR + (tid & 127) * 8);
        const char* const gb = as_pair(w < 3 ? (const char*)ea + (lane & 1) * 16 : (const char*)out + (size_t)node0 * 128 + (lane & 7) * 16, sbase + SM_PAIR + (tid & 127) * 8);
        WS(3);
        const uint32_t dm = ((NPB_MAX + lane) * 4 | (tag << 14)) * 0x10001u;
        const char* const gl = gs + ((tid & 127) >> 2) * (P1B + P2B) + t * 16;
        uint4 rl[5];
        #pragma unroll
        for (int i = 0; i < 5; i++) rl[i] = make_uint4(dm, dm, dm, ((tid & 127) >> 2) + 32 * i < nb ? 0 : dm);
        auto p2_ld = [&]() {
            if (P2L == 0 && tid == 448) {
                mbar_expect(sbase + SM_ABAR + 40, nb * (CE * 4));
                box_ld(sbase + SM_P2, &tm2, P1B / 4 + 64 + b * CE, 0, sbase + SM_ABAR + 40);
            }
        };
        asm volatile("cp.async.bulk.wait_group.read 0;" ::: "memory");
        asm volatile("bar.sync 6, 128;" ::: "memory");
        WSL(12);
        uint32_t spins = 0;
        while (true) {
            #pragma unroll
            for (int i = 0; i < 5; i++) ld_unit(rl[i], gl + i * (32 * (P1B + P2B)), (rl[i].w ^ dm) & 0xC000);
            if (spins == 0) {
                asm volatile("bar.sync 5, 512;" ::: "memory");
                x_ld(0, XDEP0);
                if (XPF == 1 && tid == 416 && nn > 0) asm volatile("cp.async.bulk.prefetch.L2.global [%0], %1;" :: "l"(x + (size_t)node0 * 64), "r"(nn * 128) : "memory");
            }
            if (!__any_sync(~0u, ((rl[0].w ^ dm) | (rl[1].w ^ dm) | (rl[2].w ^ dm) | (rl[3].w ^ dm) | (rl[4].w ^ dm)) & 0xC000)) break;
            if (++spins > (1u << 22)) __trap();
        }
        x_ld(XDEP0, XA);
        if (XPF == 2 && tid == 416 && nn > 0) asm volatile("cp.async.bulk.prefetch.L2.global [%0], %1;" :: "l"(x + (size_t)node0 * 64), "r"(nn * 128) : "memory");
        WS(4);
        const uint32_t db = sbase + SM_DEG - (tag << 14);
        auto count = [&](uint32_t e) {
            asm volatile("{\n.reg .pred p;\nsetp.eq.u32 p, %1, %2;\n@p red.shared.add.u32 [%0], 1;\n}" :: "r"(db + (e & 0xFFFF)), "r"(e >> 16), "r"(b) : "memory");
        };
        auto listed = [&](uint32_t e, uint32_t s, uint32_t k) {
            int n; asm volatile("atom.shared.inc.u32 %0, [%1], 0x7fffffff;" : "=r"(n) : "r"(sbase + SM_MISC) : "memory");
            if (n < XCAP) xlist[n] = (e & 0xFFFF) | (s << 16) | (k << 24); else misc[1] = 1;
        };
        uint32_t own = 0;
        #pragma unroll
        for (int i = 0; i < 5; i++) {
            const uint32_t bb = b << 16;
            if (__builtin_expect(min(min(rl[i].x ^ bb, rl[i].y ^ bb), min(rl[i].z ^ bb, rl[i].w ^ bb)) < 0x10000u, 0)) {
                own |= 1 << i;
                count(rl[i].x); count(rl[i].y); count(rl[i].z); count(rl[i].w);
            }
        }
        if (__builtin_expect(__any_sync(~0u, t == 3 && min(min(min(rl[0].w, rl[1].w), min(rl[2].w, rl[3].w)), rl[4].w) < 0x1000000u), 0)) {
            #pragma unroll 1
            for (int i = 0; i < 5; i++) {
                unsigned m = __ballot_sync(~0u, t == 3 && (i == 0 ? rl[0].w : i == 1 ? rl[1].w : i == 2 ? rl[2].w : i == 3 ? rl[3].w : rl[4].w) < 0x1000000u);
                while (m) {
                    const uint32_t s = w * 8 + ((__ffs(m) - 1) >> 2) + 32 * i; m &= m - 1;
                    uint2 v = make_uint2(0, 0);
                    do { ld_unit(v, gs + s * (P1B + P2B) + lane * 8, true); if (++spins > (1u << 22)) __trap(); } while (__any_sync(~0u, ((v.y >> 14) & 3) != tag));
                    if (v.y >> 16 == 255) misc[1] = 1;
                    if (lane >= 8) {
                        count(v.x); count(v.y);
                        if (v.x >> 16 == (uint32_t)b) listed(v.x, s, 2 * lane);
                        if (v.y >> 16 == (uint32_t)b) listed(v.y, s, 2 * lane + 1);
                    }
                    __syncwarp();
                }
            }
        }
        WS(11);
        if (ORDX == 0 || w != 2) asm volatile("bar.arrive 7, 512;" ::: "memory");
        else asm volatile("bar.sync 7, 512;" ::: "memory");
        if (ORDX != 3) p2_ld();
        x_ld(XA, XDEP);
        if (ORDX == 3) p2_ld();
        while (own != 0) {
            const int i = __ffs(own) - 1; own &= own - 1;
            const uint4 e = i == 0 ? rl[0] : i == 1 ? rl[1] : i == 2 ? rl[2] : i == 3 ? rl[3] : rl[4];
            const uint32_t s = (((tid & 127) >> 2) + 32 * i) << 16 | t << 26;
            const bool m0 = e.x >> 16 == (uint32_t)b, m1 = e.y >> 16 == (uint32_t)b, m2 = e.z >> 16 == (uint32_t)b, m3 = e.w >> 16 == (uint32_t)b;
            int n = atomicAdd(misc, m0 + m1 + m2 + m3);
            if (n + 4 > XCAP) { misc[1] = 1; n = 0; }
            if (m0) xlist[n++] = (e.x & 0xFFFF) | s;
            if (m1) xlist[n++] = (e.y & 0xFFFF) | s | 1 << 24;
            if (m2) xlist[n++] = (e.z & 0xFFFF) | s | 2 << 24;
            if (m3) xlist[n] = (e.w & 0xFFFF) | s | 3 << 24;
        }
        asm volatile("bar.sync 6, 128;" ::: "memory");
        WS(9);
        if (XDEP < 6 && tid == XT) {
            for (int k = XDEP; k < 6; k++) { mbar_wait(sbase + SM_XBAR + (k - XDEP) * 8, 0); x_ld(k, k + 1); }
        }
        __syncwarp();
        WS(10);
        WGD();
        const int r4 = lane >> 3, c8 = lane & 7;
        const uint32_t sb = __reduce_or_sync(~0u, sbase);
        if (w < 3) {
            const char* gx = ga; const char* ge = gb;
            const uint32_t gx0 = (uint32_t)(uint64_t)gx, ge0 = (uint32_t)(uint64_t)ge, hi = (uint64_t)gx >> 32, he = (uint64_t)ge >> 32;
            const int s = (lane >> 1) & 3;
            const uint32_t xs0 = sb + SM_XS + w * NSTAGE * XS_BYTES;
            const uint32_t es0 = sb + SM_ES + w * NSTAGE * ES_BYTES + r4 * 64 + (((lane ^ (r4 >> 1)) & 1) << 4) + (s >> 1) * 256 + (s & 1) * 32;
            const uint32_t bars = sb + SM_BARS + w * 96;
            const uint32_t xoffA = (2 * r4) * 128 + ((c8 ^ (2 * r4)) << 4), xoffB = (2 * r4 + 1) * 128 + ((c8 ^ (2 * r4 + 1)) << 4);
            uint64_t pol;
            asm volatile("createpolicy.fractional.L2::evict_first.b64 %0, 1.0;" : "=l"(pol));
            asm volatile("bar.arrive 2, 512;" ::: "memory");
            asm volatile("bar.sync 4, 480;" ::: "memory");
            {
                const uint2 m01 = lds64(sb + SM_MISC);
                #pragma unroll 1
                for (int id = tid - 384; T1W && id < NPB_MAX; id += 96) {
                    const uint2 d4 = lds64(sb + SM_SDEG + (id >> 2) * 8);
                    if (m01.y || !__any_sync(~0u, (d4.x & 0xFFFF) > 2 * NPMAX)) break;
                    tables<1>(smem, lds32(sb + SM_SORT + id * 4), d4, id, ngroups);
                }
                #pragma unroll 1
                for (int j = tid - 384; j < (m01.y ? 0 : (int)m01.x); j += 96) {
                    const uint32_t e = xlist[j], s = (e >> 16) & 0xFF;
                    uint32_t sl, v;
                    asm volatile("atom.shared.add.u32 %0, [%1], 4;" : "=r"(sl) : "r"(db + (e & 0xFFFF)) : "memory");
                    do {
                        asm volatile("ld.relaxed.gpu.global.u32 %0, [%1];" : "=r"(v) : "l"(gs + s * (P1B + P2B) + P1B + (e >> 24) * 4) : "memory");
                        if (++spins > (1u << 22)) __trap();
                    } while (((v >> 16) & 3) != tag);
                    if (sl < 4 * SLOT_CAP) {
                        sts32(sb + SM_EID + sl, s * ch + (v >> 19));
                        asm volatile("st.shared.u16 [%0], %1;" :: "r"(sb + SM_SRC + (sl >> 1)), "r"(v) : "memory");
                    }
                }
                __syncwarp();
            }
            uint32_t first = 1;
            WS(15);
            uint32_t ph = 1, cur = w;
            uint32_t hist = 96 * 0x010101u;
            auto done3 = [&]() { mbar_arrive(sb + SM_GBAR + ((hist >> 16) & 0xFF) * 8); };
            const bool go = misc[1] == 0 && nn > 0;
            const uint32_t ca = sb + SM_CLAIM + lane * 4, pa = sb + SM_TINFO + r4 * 8;
            uint32_t pw = lds32(pa + w * 32), brk = (lds32(pa + w * 32 + 4) >> 16) & C_BRK;
            const uint32_t se0 = sb + SM_EID + s * 4, xab = xoffB - xoffA, das = 2 * (xs0 + xoffA) + XS_BYTES, des = 2 * es0 + ES_BYTES, brs = 2 * bars + 48;
            uint32_t da = xs0 + xoffA, de = es0, br = bars;
            int itn = 0;
            #pragma unroll 1
            while (go) {
                const uint32_t pt = __reduce_or_sync(~0u, pw);
                uint32_t se, sx;
                asm("dp2a.lo.u32.u32 %0, %1, 4, %2;" : "=r"(se) : "r"(pw), "r"(se0));
                asm("dp2a.lo.u32.u32 %0, %1, 2, %2;" : "=r"(sx) : "r"(pw), "r"(sb + SM_SRC));
                const int dv = pw >> 27;
                const uint32_t db = da + xab;
                const uint32_t sel = (pt >> 16) & 15, nx = (pt >> 20) & 127;
                uint32_t g;
                auto claim = [&]() { asm volatile("atom.shared.add.u32 %0, [%1], %2;" : "=r"(g) : "r"(ca), "r"(nx == 0 ? 1u : 0u) : "memory"); };
                if (sel == 0) break;
                if (first) {
                    if (!G2 || first == 1) { asm volatile("bar.sync 3, 480;" ::: "memory"); WSL(6); }
                    else asm volatile("cp.async.wait_all;" ::: "memory");
                    first = G2 ? (first + first) & 3 : 0;
                }
                switch (sel) {
#define EGET(j, P, GEN) \
                            if (LO32) { if (!GEN && 2 * j + 2 < P) cpe<false>(he, de + j * 512, oe[j], ge0, 0, 0, pol); \
                                else if (2 * j + 1 < NPMAX || s < 2) cpe<true>(he, de + j * 512, oe[j], ge0, 4 * j + s, dv, pol); } \
                            else if (!GEN && 2 * j + 2 < P) cp16e(de + j * 512, ge, oe[j], pol); else if (2 * j + 1 < NPMAX || s < 2) cp16z<32>(de + j * 512, ge, oe[j], 4 * j + s, dv, pol);
#define CASE(L, P, GEN) case L: { \
                        uint32_t oe[(P + 1) / 2], o[P]; \
                        _Pragma("unroll") for (int j = 0; j < (P + 1) / 2; j++) if (j < PACE_E) oe[j] = lds32(se + j * 16); \
                        _Pragma("unroll") for (int j = 0; j < P; j++) if (j < PACE) o[j] = lds32(sx + j * 4); \
                        mbar_wait_h(br + 8, ph); \
                        if (!MIX) { _Pragma("unroll") for (int j = 0; j < (P + 1) / 2; j++) { EGET(j, P, GEN) if (j + PACE_E < (P + 1) / 2) oe[j + PACE_E] = lds32(se + (j + PACE_E) * 16); } } \
                        _Pragma("unroll") for (int j = 0; j < P - 1; j++) { \
                            if (MIX && j < (P + 1) / 2) { EGET(j, P, GEN) } \
                            if (LO32) { cpx<0, GEN>(hi, da + j * 1024, o[j], gx0, 2 * j, dv); cpx<1, GEN>(hi, db + j * 1024, o[j], gx0, 2 * j + 1, dv); } \
                            else if (GEN) { cp16z<128>(da + j * 1024, gx, o[j] & 0xFFFFu, 2 * j, dv, 0); cp16z<128>(db + j * 1024, gx, o[j] >> 16, 2 * j + 1, dv, 0); } \
                            else { cp16i<128>(da + j * 1024, gx, o[j] & 0xFFFFu); cp16i<128>(db + j * 1024, gx, o[j] >> 16); } \
                            if (j + PACE < P) o[j + PACE] = lds32(sx + (j + PACE) * 4); } \
                        if (LO32) { cpx<0, true>(hi, da + (P - 1) * 1024, o[P - 1], gx0, 2 * P - 2, dv); cpx<1, true>(hi, db + (P - 1) * 1024, o[P - 1], gx0, 2 * P - 1, dv); } \
                        else { cp16z<128>(da + (P - 1) * 1024, gx, o[P - 1] & 0xFFFFu, 2 * P - 2, dv, 0); cp16z<128>(db + (P - 1) * 1024, gx, o[P - 1] >> 16, 2 * P - 1, dv, 0); } \
                    } break;
                    CASE(4, 4, false) CASE(5, 5, false) CASE(6, 6, false) CASE(7, 7, false) CASE(8, 8, false) CASE(9, 9, false) CASE(10, 10, false) CASE(11, 11, false)
                    CASE(15, NPMAX, true) CASE(14, 8, true) default: CASE(13, 5, true)
#undef CASE
                }
                claim();
                mbar_cp_arrive(br);
                done3();
                g = __reduce_min_sync(~0u, g);
                {
                    const uint2 e = lds64(pa + (nx == 0 ? g : nx) * 32);
                    const uint2 v = tile_info(e.y);
                    pw = e.x;
                    asm volatile("st.shared.v2.u32 [%0], {%1, %2};" :: "r"(br + 16 + r4 * 8), "r"(v.x), "r"((v.y & ~C_BRK) | brk) : "memory");
                    brk = v.y & C_BRK;
                }
                mbar_arrive(br);
                hist = (hist << 8) | (nx == 0 ? cur : 96u);
                cur = nx == 0 ? g : cur;
                ph ^= br != bars; br = brs - br; da = das - da; de = des - de;
            }
            if (first == 1) asm volatile("bar.sync 3, 480;" ::: "memory");
            if (go) {
                mbar_wait(sb + SM_ABAR + 72, 0);
                const int g0 = 3 * max((ngroups + 2) / 3 - TR, 0) + w;
                uint32_t nd[TR]; uint4 xv[TR];
                #pragma unroll
                for (int k = 0; k < TR; k++) {
                    asm volatile("ld.shared.u16 %0, [%1];" : "=r"(nd[k]) : "r"(sb + SM_WL + (g0 + 3 * k) * 8 + r4 * 2) : "memory");
                    xv[k] = __ldg((const uint4*)(gx + (size_t)(node0 + (nd[k] == NONE ? 0u : nd[k])) * 128));
                }
                #pragma unroll 1
                for (int k = 0; k < 3; k++) {
                    mbar_wait(k < 2 ? br + 8 : sb + SM_ABAR + 48 + w * 8, k < 2 ? ph : 0);
                    done3(); hist <<= 8;
                    ph ^= br != bars; br = brs - br;
                }
                #pragma unroll
                for (int k = 0; k < TR; k++) {
                    const uint32_t ro = sb + nd[k] * 128 + ((c8 ^ (nd[k] & 7)) << 4);
                    const uint4 xu = lds128(ro + SM_XU);
                    uint4 a = make_uint4(0, 0, 0, 0);
                    if (g0 + 3 * k < misc[4]) { mbar_wait(sb + SM_GBAR + (g0 + 3 * k) * 8, 0); a = lds128(ro + SM_TAB); }
                    finish(a, xu, xv[k]);
                    if (nd[k] != NONE) *(uint4*)((char*)out + (size_t)(node0 + nd[k]) * 128 + c8 * 16) = a;
                }
            }
            cp_wait<0>();
        } else {
            const char* gx = ga; const char* ob = gb;
            asm volatile("bar.sync 2, 512;" ::: "memory");
            WS(15);
            if (b == 0 && lane == 0) asm volatile("red.relaxed.gpu.global.add.u32 [%0], 1;" :: "l"(gbar) : "memory");
            if (misc[1] == 0) mbar_wait(sb + SM_ABAR + 72, 0);
            const int rounds = misc[1] ? 0 : max((ngroups + 2) / 3 - TR, 0);
            const int gz = misc[4], fast = __reduce_min_sync(~0u, min(rounds, gz / 3));
            uint32_t wl = sb + SM_WL + r4 * 2, gbar = sb + SM_GBAR;
            auto row_at = [&](uint32_t a) { uint32_t n; asm volatile("ld.shared.u16 %0, [%1];" : "=r"(n) : "r"(a) : "memory"); return n; };
            auto fetch = [&](uint32_t n, uint4& v) {
                asm volatile("{\n.reg .b64 p;\nmad.wide.u32 p, %5, 128, %4;\nld.global.nc.L1::no_allocate.v4.u32 {%0,%1,%2,%3}, [p];\n}"
                             : "=r"(v.x), "=r"(v.y), "=r"(v.z), "=r"(v.w) : "l"(gx), "r"(n));
            };
            auto store = [&](uint32_t n, const uint4& a) {
                asm volatile("{\n.reg .b64 p;\nmad.wide.u32 p, %1, 128, %0;\nst.global.v4.u32 [p], {%2,%3,%4,%5};\n}" :: "l"(ob), "r"(n), "r"(a.x), "r"(a.y), "r"(a.z), "r"(a.w) : "memory");
            };
            uint32_t n0[3]; uint4 x0[3];
            if (fast) {
                #pragma unroll
                for (int r = 0; r < 3; r++) { n0[r] = row_at(wl + r * 8); fetch(n0[r], x0[r]); }
            }
            #pragma unroll 1
            for (int k = 0; k < fast; k++) {
                wl += 24;
                #pragma unroll
                for (int r = 0; r < 3; r++) {
                    const uint32_t nd = n0[r], ro = sb + nd * 128 + ((c8 ^ (nd & 7)) << 4);
                    const uint4 xu = lds128(ro + SM_XU);
                    n0[r] = row_at(wl + r * 8);
                    mbar_wait(gbar + r * 8, 0);
                    uint4 a = lds128(ro + SM_TAB);
                    finish(a, xu, x0[r]);
                    fetch(n0[r], x0[r]);
                    store(nd, a);
                }
                gbar += 24;
            }
            #pragma unroll 1
            for (int g = 3 * fast; g < 3 * rounds; g++) {
                const uint32_t nd = row_at(sb + SM_WL + r4 * 2 + g * 8), ro = sb + nd * 128 + ((c8 ^ (nd & 7)) << 4);
                uint4 xv, a = make_uint4(0, 0, 0, 0);
                fetch(nd, xv);
                if (g < gz) { mbar_wait(sb + SM_GBAR + g * 8, 0); a = lds128(ro + SM_TAB); }
                finish(a, lds128(ro + SM_XU), xv);
                store(nd, a);
            }
        }
    } else {
        asm volatile("setmaxnreg.inc.sync.aligned.u32 152;");
        uint32_t wf[40], wn[16];
        mbar_wait(sbase + SM_ABAR + 24, 0);
        {
            const uint32_t wo = sbase + SM_WR + (2 * t) * 128 + ((ch0 * 2) ^ (t * 32));
            #pragma unroll
            for (int ks = 0; ks < 9; ks++) {
                uint32_t wr[4];
                #pragma unroll
                for (int i = 0; i < 4; i++) wr[i] = lds32((wo ^ ((i & 1) * 16)) + (16 * ks + (i & 1) + 4 * (i & 2)) * 128);
                if (ks < 5) make_wfrag<true>(wf + 4 * ks, wr); else make_wfrag<false>(wf + 4 * ks, wr);
            }
            #pragma unroll
            for (int ks = 0; ks < 4; ks++) ldsm4t(wn + 4 * ks, sbase + SM_WR + (144 + 16 * ks + 8 * (lane >> 4) + (lane & 7)) * 128 + (((2 * w + ((lane >> 3) & 1)) ^ (lane & 7)) << 4));
            if (wg == 2) {
                const uint32_t a = sbase + SM_WC + (16 * w + q) * 32 + t * 4, sw = (q >> 2) << 4;
                sts32(a + sw, wf[16]); sts32(a + 256 + sw, wf[17]); sts32(a + (sw ^ 16), wf[18]); sts32(a + 256 + (sw ^ 16), wf[19]);
                asm volatile("fence.proxy.async.shared::cta;" ::: "memory");
            }
            #pragma unroll
            for (int i = 0; i < 36; i++) asm volatile("" : "+r"(wf[i]));
        }
        WS(9);
        constexpr int NU = 6;
        const uint32_t dm = ((NPB_MAX + lane) * 4 | (tag << 14)) * 0x10001u;
        const char* const g1 = gs + (tid >> 4) * (P1B + P2B) + 256 + b * (CE * 2) + (lane & 15) * 8;
        const bool last = SKIP ? 2 * warp + 24 * (NU - 1) < nb : true;
        uint2 r1[NU];
        #pragma unroll
        for (int i = 0; i < NU; i++) r1[i] = make_uint2(dm, (tid >> 4) + 24 * i < nb ? 0 : dm);
        uint32_t spins = 0;
        asm volatile("bar.sync 5, 512;" ::: "memory");
        while (true) {
            #pragma unroll
            for (int i = 0; i < NU; i++) ld_unit(r1[i], g1 + i * (24 * (P1B + P2B)), (r1[i].y ^ dm) & 0xC000);
            uint32_t bad = 0;
            #pragma unroll
            for (int i = 0; i < NU; i++) bad |= r1[i].y ^ dm;
            const bool more = __any_sync(~0u, bad & 0xC000);
            if (spins == 0) WS(2);
            if (!more) break;
            if (++spins > (1u << 22)) __trap();
        }
        WS(3);
        const uint32_t db = sbase + SM_DEG - (tag << 14);
        uint4 r2[NU];
        const char* const g2 = gs + (tid >> 4) * (P1B + P2B) + P1B + 256 + b * (CE * 4) + (lane & 15) * 16;
        auto p2_get = [&](int i0, int i1) {
            #pragma unroll
            for (int i = i0; i < i1; i++) {
                const bool some = (r1[i].x & 0x3FFF) < NPB_MAX * 4;
                r2[i] = make_uint4(0, 0, 0, some ? 0 : tag << 16);
                ld_unit(r2[i], g2 + i * (24 * (P1B + P2B)), some);
            }
        };
        if (P2L == 1) p2_get(0, NU);
        uint32_t rk[NU][4];
        #pragma unroll
        for (int i = 0; i < NU; i++) {
            #pragma unroll
            for (int k = 0; k < 4; k++) {
                asm("dp2a.lo.u32.u32 %0, %1, %2, %3;" : "=r"(rk[i][k]) : "r"(k < 2 ? r1[i].x : r1[i].y), "r"(k & 1 ? 0x100u : 1u), "r"(db));
                if (i < NU - 1 || last) asm volatile("red.shared.add.u32 [%0], 1;" :: "r"(MINV ? min(rk[i][k], sbase + SM_DEG + NPB_MAX * 4) : rk[i][k]) : "memory");
            }
        }
        if (P2L == 2) p2_get(0, NU);
        if (P2L == 4) p2_get(0, 3);
        WS(10);
        asm volatile("bar.sync 7, 512;" ::: "memory");
        WS(11);
        int mycls = 0, mycr = 0, dg = lds32(sbase + SM_DEG + tid * 4);
        if (tid < nn) {
            mycls = NCLS - 1 - (dg <= 40 ? dg : min(41 + ((dg - 41) >> 3), NCLS - 1)); mycr = atomicAdd(&cls[mycls], 1);
        }
        int s0 = 0;
        if (__builtin_expect(dg > 40, 0)) s0 = max(SLOT_CAP - ((dg + 1) & ~1) - atomicAdd(&misc[6], (dg + 1) & ~1), 0);
        if (P2L == 3) p2_get(0, NU);
        if (P2L == 4) p2_get(3, NU);
        asm volatile("bar.sync 1, 384;" ::: "memory");
        WS(12);
        {
            const uint2 c = lds64(sbase + SM_CLS + lane * 8);
            const int v0 = c.x * (lane > 11 ? ((64 - 2 * lane) << 16) + 1 : 1), v1 = c.y * (lane >= 11 ? ((62 - 2 * lane) << 16) + 1 : 1);
            int inc = v0 + v1;
            #pragma unroll
            for (int o = 1; o < 32; o <<= 1) { int y = __shfl_up_sync(~0u, inc, o); if (lane >= o) inc += y; }
            const int e0 = __shfl_sync(~0u, inc - v0 - v1, mycls >> 1), e1 = __shfl_sync(~0u, inc - v1, mycls >> 1);
            const int e = (mycls & 1) ? e1 : e0;
            if (tid < nn) {
                if (dg <= 40) s0 = min((e >> 16) + mycr * ((dg + 1) & ~1), SLOT_CAP - 40);
                sts32(sbase + SM_DEG + tid * 4, 4 * s0);
            }
            const uint32_t pos = tid < nn ? (e & 0xFFFF) + mycr : tid;
            sts32(sbase + SM_SORT + pos * 4, tid < nn ? (uint32_t)tid | ((uint32_t)s0 << 16) : NONE);
            asm volatile("st.shared.u16 [%0], %1;" :: "r"(sbase + SM_SDEG + pos * 2), "r"(min(dg, 65535)) : "memory");
            asm volatile("st.shared.u16 [%0], %1;" :: "r"(sbase + SM_WL + pos * 2), "r"(tid < nn ? tid : NONE) : "memory");
            if (tid == 383) { misc[4] = (nn - c.y + 3) >> 2; if ((inc >> 16) + misc[6] > SLOT_CAP - 40) misc[1] = 1; }
        }
        asm volatile("bar.sync 1, 384;" ::: "memory");
        WS(13);
        const int id = tid + TOFF < 384 ? tid + TOFF : tid + TOFF - 384;
        const uint32_t sv = lds32(sbase + SM_SORT + id * 4);
        const uint2 d4 = lds64(sbase + SM_SDEG + (id >> 2) * 8);
        const int slow = misc[1];
        #pragma unroll
        for (int i = 0; i < NU; i++) {
            if (i < NU - 1 || last) {
                #pragma unroll
                for (int k = 0; k < 4; k++) asm volatile("atom.shared.add.u32 %0, [%0], 4;" : "+r"(rk[i][k]) :: "memory");
            }
        }
        if (slow == 0) tables<0>(smem, sv, d4, id, ngroups);
        asm volatile("bar.arrive 4, 480;" ::: "memory");
        WS(14);
        if (P2L == 0) mbar_wait(sbase + SM_ABAR + 40, 0);
        WS(4);
        #pragma unroll
        for (int i = 0; i < NU; i++) if (P2L == 0) r2[i] = lds128(sbase + SM_P2 + (i < NU - 1 ? tid + 384 * i : min(tid + 384 * i, P2B / 16 - 1)) * 16);
        while (true) {
            uint32_t bad = 0;
            #pragma unroll
            for (int i = 0; i < NU; i++) bad |= r2[i].w ^ (tag << 16);
            if (__builtin_expect(!__any_sync(~0u, bad & 0x30000), 1)) break;
            #pragma unroll
            for (int i = 0; i < NU; i++)
                ld_unit(r2[i], g2 + i * (24 * (P1B + P2B)), (r2[i].w ^ (tag << 16)) & 0x30000);
            if (++spins > (1u << 22)) __trap();
        }
        WS(16);
        const uint32_t sbu = __reduce_or_sync(~0u, sbase);
        auto place = [&](uint32_t s4, uint32_t v, uint32_t eb) {
            asm volatile("{\n.reg .pred p;\nsetp.lt.u32 p, %0, %5;\n@p st.shared.u32 [%1], %2;\n@p st.shared.u16 [%3], %4;\n}"
                         :: "r"(s4), "r"(sbu + SM_EID + s4), "r"(eb + (v >> 19)), "r"(sbu + SM_SRC + (s4 >> 1)), "r"(v), "n"(4 * SLOT_CAP) : "memory");
        };
        #pragma unroll
        for (int i = 0; i < NU; i++) {
            const uint32_t eb = ((tid >> 4) + 24 * i) * ch;
            if (i < NU - 1 || last) { place(rk[i][0], r2[i].x, eb); place(rk[i][1], r2[i].y, eb); place(rk[i][2], r2[i].z, eb); place(rk[i][3], r2[i].w, eb); }
        }
        WS(1);
        WGD();
        asm volatile("bar.arrive 3, 480;" ::: "memory");
        {
        int lane;
        asm volatile("mov.u32 %0, %%laneid;" : "=r"(lane));
        const int q = lane >> 2, t = lane & 3, ch0 = 16 * w + 2 * q;
        const uint32_t sbase = sbu;
        { const uint2 z = lds64(sbase + SM_OH + 8); wf[37] = z.x; wf[38] = z.y; }
        const uint32_t c2 = __shfl_sync(~0u, ch0 * 2, lane), t8 = __shfl_sync(~0u, t * 8, lane);
        float g[4 * NPMAX], h[4 * NPMAX];
        float4 lgh[2 * NPMAX];
        float4 cyr = make_float4(0.f, 0.f, 0.f, 0.f);
        {
            const uint32_t mo = sbase + (8 * (lane >> 4) + (lane & 7)) * 128 + (((2 * w + ((lane >> 3) & 1)) ^ (lane & 7)) << 4);
            mbar_wait(sbase + SM_XBAR + wg * 16, 0); mbar_wait(sbase + SM_XBAR + wg * 16 + 8, 0);
            node_mma2(g, h, wn, desc_sw128(sbase + SM_XU + wg * 16384));
            TileMMA<8>::wait_g(g); TileMMA<8>::wait_h(h);
            #pragma unroll
            for (int ks = 0; ks < 4; ks++) ldsm4t(wn + 4 * ks, mo + SM_WR + (208 + 16 * ks) * 128);
            asm volatile("bar.sync 2, 512;" ::: "memory");
            WS(15);
            if (__builtin_expect(lds32(sbase + SM_MISC + 4) != 0, 0)) { slow_bin(x, ea, src, dst, wa, wb, wc, wu, wv, out, E, node0, nn, 384); return; }
            auto rows = [&](uint32_t p) {
                #pragma unroll
                for (int i = 0; i < 8; i++) {
                    const float* u = i < 4 ? g + 8 * i : h + 8 * (i - 4);
                    const uint32_t v[4] = {pack_bf16(u[0], u[1]), pack_bf16(u[2], u[3]), pack_bf16(u[4], u[5]), pack_bf16(u[6], u[7])};
                    stsm4t(p + i * 2048, v);
                }
            };
            rows(mo + SM_TAB + wg * 16384);
            node_mma2(g, h, wn, desc_sw128(sbase + SM_XU + wg * 16384));
            TileMMA<8>::wait_g(g); TileMMA<8>::wait_h(h);
            asm volatile("bar.sync 1, 384;" ::: "memory");
            rows(mo + SM_XU + wg * 16384);
            __syncwarp();
            if (lane == 0) mbar_arrive(sbase + SM_ABAR + 72);
            WS(6);
        }
        const uint64_t wcd = __reduce_or_sync(~0u, (((sbase + SM_WC) & 0x3FFFF) >> 4) | (8u << 16)) | EDHI;
        const uint32_t bar0 = __reduce_or_sync(~0u, sbase + SM_BARS + wg * 96);
        const uint32_t xd0 = __reduce_or_sync(~0u, (((sbase + SM_XS + wg * NSTAGE * XS_BYTES) & 0x3FFFF) >> 4) | (1u << 16));
        const uint32_t ed0 = __reduce_or_sync(~0u, (((sbase + SM_ES + wg * NSTAGE * ES_BYTES) & 0x3FFFF) >> 4) | (8u << 16));
        const uint64_t ohd = __reduce_or_sync(~0u, (((sbase + SM_OH) & 0x3FFFF) >> 4) | (8u << 16));
        const uint32_t tabx = __reduce_or_sync(~0u, sbase + SM_TAB);
        const uint32_t bars = __reduce_or_sync(~0u, 2 * bar0 + 48), xds = __reduce_or_sync(~0u, 2 * xd0 + XS_BYTES / 16), eds = __reduce_or_sync(~0u, 2 * ed0 + ES_BYTES / 16);
        uint32_t bar = bar0, xd = xd0, ed = ed0, ph = 0, code, w1, ta, pta = NONE * 128 + c2;
        float pn0 = 0.f, pd0 = 1.f, pn1 = 0.f, pd1 = 1.f;
        uint2 ni = tile_info(lds32(sbase + SM_TINFO + wg * 32 + t * 8 + 4));
        auto fetch_a = [&]() {
            ta = (ni.x & 0xFFFFu) ^ c2;
            wf[36] = lds32(tabx + ta); wf[39] = lds32(tabx + ta);
            code = __reduce_or_sync(~0u, ni.y);
        };
        auto emit = [&]() { sts32(tabx + pta, pack_bf16(pn0 * rcpf(pd0), pn1 * rcpf(pd1))); };
        auto carry = [&]() {
            if (w1 & C_CONT) { pn0 += cyr.x; pd0 += cyr.y; pn1 += cyr.z; pd1 += cyr.w; }
            if (w1 & C_MORE) { cyr = make_float4(pn0, pd0 - EPS2, pn1, pd1 - EPS2); pn0 = pn1 = 0.f; pta = NONE * 128 + c2; }
        };
        auto next = [&](uint32_t fb) {
            pta = ta;
            w1 = ni.y;
            ni = lds64(fb + 16 + t8);
        };
        fetch_a();
        while (true) {
            switch (code & 15) {
                default: goto finished;
#define TILE(P) { \
                    float dmin; \
                    do { \
                        mbar_wait_c(bar, ph); \
                        TileMMA<P>::issue(g, h, wf, xd | (0x40000040ull << 32), ed | EDHI, ohd, wcd); \
                        const uint32_t eb = bar + 8; \
                        ph ^= bar != bar0; bar = bars - bar; xd = xds - xd; ed = eds - ed; \
                          \
                        asm volatile("{\n.reg .pred p;\nsetp.eq.u32 p, %0, 77;\n@p trap;\n}" :: "r"(xds) : "memory"); \
                        emit(); next(eb - 8); \
                        TileMMA<P>::wait_g(g); fetch_a(); TileMMA<P>::wait_h(h); \
                        mbar_arrive(eb); \
                        float m1; \
                        asm("set.gt.f32.f32 %0, %1, 0f0000007F;" : "=f"(m1) : "f"(__uint_as_float(w1))); \
                        epi_fast<P>(g, h, m1, __uint_as_float(w1), pn0, pd0, pn1, pd1, dmin); \
                    } while (!(__any_sync(~0u, dmin < TAU * 2 * P) | ((code & 31) != P))); \
                    if (__builtin_expect(__any_sync(~0u, (int)w1 < 0 || dmin < TAU * 2 * P), 0)) { \
                        int dv; \
                        if (unpad(w1, P, g[P > 1 ? 4 * P - 7 : 0], g[P > 1 ? 4 * P - 5 : 0], pd0, pd1, dv)) { \
                            epi_dump<P>(g, h, lgh); \
                            const float4 r = epi_exact(lgh, P, dv); \
                            pn0 = r.x; pd0 = r.y; pn1 = r.z; pd1 = r.w; \
                        } \
                    } \
                    if (code & C_BRK) { carry(); if (P != 11 && (code & 15) == P) goto L##P; } \
                    if (P == 11) {         \
                        const uint32_t a = tabx + (SM_WC - SM_TAB) + (c2 & 0x60) * 16 + (c2 & 0x1C) * 8 + (t8 >> 1), sw = c2 & 16; \
                        wf[16] = lds32(a + sw); wf[17] = lds32(a + 256 + sw); wf[18] = lds32(a + (sw ^ 16)); wf[19] = lds32(a + 256 + (sw ^ 16)); \
                    } }
#define CASE(P, UP, DN) case P: L##P: TILE(P) \
                    if (P > 1 && (code & 15) == P - 1) goto L##DN; \
                    if ((code & 15) == UP) goto L##UP; \
                    break;
                CASE(11, 11, 10) CASE(10, 11, 9) CASE(9, 10, 8) CASE(8, 9, 7) CASE(7, 8, 6) CASE(6, 7, 5) CASE(5, 6, 4) CASE(4, 5, 3) CASE(3, 4, 2) CASE(2, 3, 1) CASE(1, 2, 1)
#undef CASE
#undef TILE
            }
        }
finished:
        emit();
        __syncwarp();
        if (lane == 0) mbar_arrive(sbase + SM_ABAR + 48 + wg * 8);
        }
    }
    WS(17); WG1();
}

}

extern "C" void kernel_launch(void* const* d_in, const int* in_sizes, int n_in, void* d_out, int out_size) {
    const __nv_bfloat16* x = (const __nv_bfloat16*)d_in[0];
    const __nv_bfloat16* ea = (const __nv_bfloat16*)d_in[1];
    const int* src = (const int*)d_in[2];
    const int* dst = (const int*)d_in[3];
    const __nv_bfloat16* wa = (const __nv_bfloat16*)d_in[4];
    const __nv_bfloat16* wb = (const __nv_bfloat16*)d_in[5];
    const __nv_bfloat16* wc = (const __nv_bfloat16*)d_in[6];
    const __nv_bfloat16* wu = (const __nv_bfloat16*)d_in[7];
    const __nv_bfloat16* wv = (const __nv_bfloat16*)d_in[8];
    __nv_bfloat16* out = (__nv_bfloat16*)d_out;
    int N = in_sizes[0] / 64, E = in_sizes[2];
    static int sms = 0;
    static CUtensorMap tm2;
    static bool tm_ok = false;
    typedef CUresult (*EncFn)(CUtensorMap*, CUtensorMapDataType, cuuint32_t, void*, const cuuint64_t*, const cuuint64_t*, const cuuint32_t*,
                              const cuuint32_t*, CUtensorMapInterleave, CUtensorMapSwizzle, CUtensorMapL2promotion, CUtensorMapFloatOOBfill);
    static void* fn = nullptr;
    static void* gp = nullptr; static void* gb = nullptr;
    if (!sms) {
        cudaDeviceGetAttribute(&sms, cudaDevAttrMultiProcessorCount, 0);
        cudaDriverEntryPointQueryResult qr;
        cudaGetDriverEntryPoint("cuTensorMapEncodeTiled", &fn, cudaEnableDefault, &qr);
        cudaGetSymbolAddress(&gp, g_str); cudaGetSymbolAddress(&gb, g_bar);
        if (fn && gp && gb) {
            const cuuint32_t rows = sms < NB_MAX ? sms : NB_MAX;
            cuuint64_t g2[2] = {(P1B + P2B) / 4, NB_MAX}, gs[1] = {P1B + P2B};
            cuuint32_t b2[2] = {CE, rows}, es[2] = {1, 1};
            tm_ok = ((EncFn)fn)(&tm2, CU_TENSOR_MAP_DATA_TYPE_UINT32, 2, gp, g2, gs, b2, es, CU_TENSOR_MAP_INTERLEAVE_NONE, CU_TENSOR_MAP_SWIZZLE_NONE,
                                CU_TENSOR_MAP_L2_PROMOTION_NONE, CU_TENSOR_MAP_FLOAT_OOB_FILL_NONE) == CUDA_SUCCESS;
        }
        cudaFuncSetAttribute(gcn_kernel<true>, cudaFuncAttributeMaxDynamicSharedMemorySize, SMEM_LAUNCH);
        cudaFuncSetAttribute(gcn_kernel<false>, cudaFuncAttributeMaxDynamicSharedMemorySize, SMEM_LAUNCH);
    }
    auto rows = [&](CUtensorMap* tm, const void* base, uint64_t n, uint32_t box) {
        cuuint64_t gd[2] = {64, n}, gs[1] = {128};
        cuuint32_t bx[2] = {64, box}, es[2] = {1, 1};
        return ((EncFn)fn)(tm, CU_TENSOR_MAP_DATA_TYPE_BFLOAT16, 2, (void*)base, gd, gs, bx, es, CU_TENSOR_MAP_INTERLEAVE_NONE, CU_TENSOR_MAP_SWIZZLE_128B,
                           CU_TENSOR_MAP_L2_PROMOTION_NONE, CU_TENSOR_MAP_FLOAT_OOB_FILL_NONE) == CUDA_SUCCESS;
    };
    const uintptr_t wp[4] = {(uintptr_t)wa, (uintptr_t)wb, (uintptr_t)wu, (uintptr_t)wv};
    uintptr_t w0 = wp[0], w1 = wp[0], wal = 0;
    for (int i = 1; i < 4; i++) { w0 = wp[i] < w0 ? wp[i] : w0; w1 = wp[i] > w1 ? wp[i] : w1; wal |= wp[i] - wp[0]; }
    int4 wrow = make_int4((int)((wp[0] - w0) >> 7), (int)((wp[1] - w0) >> 7), (int)((wp[2] - w0) >> 7), (int)((wp[3] - w0) >> 7));
    CUtensorMap tmw, tmc, tmx;
    const bool maps = tm_ok && N > 0 && !(wal & 127) && ((w1 - w0) >> 7) < (1u << 30) && rows(&tmw, (void*)w0, ((w1 - w0) >> 7) + 64, 64) && rows(&tmc, wc, 16, 16) && rows(&tmx, x, N, 64);
    int nb = sms < NB_MAX ? sms : NB_MAX;
    int npb = (N + nb - 1) / nb;
    int ch = (((E + nb - 1) / nb) + 3) & ~3;
    if (!maps || npb > NPB_MAX || ch > CH_MAX || (E & 3) || N > 65535 || npb < 2 || (((uintptr_t)src | (uintptr_t)dst | (uintptr_t)wa | (uintptr_t)wb | (uintptr_t)wc | (uintptr_t)wu | (uintptr_t)wv) & 15)) {
        int g = 1024, p = (N + g - 1) / g;
        slow_kernel<<<g, 256>>>(x, ea, src, dst, wa, wb, wc, wu, wv, out, N, E, p < 1 ? 1 : p);
        return;
    }
    uint32_t magic = (uint32_t)((1ull << 32) / (uint32_t)npb) + 1u;
    void* args[] = {&dst, &gb, &gp, &src, &E, &ch, &N, &npb, &magic, &x, &ea, &wa, &wb, &wc, &wu, &wv, &out, &wrow, &tm2, &tmw, &tmc, &tmx};
    const bool lo32 = ((uintptr_t)x >> 32) == (((uintptr_t)x + (size_t)N * 128 - 1) >> 32) && ((uintptr_t)ea >> 32) == (((uintptr_t)ea + (size_t)E * 32 - 1) >> 32);
    cudaLaunchCooperativeKernel(lo32 && !FORCE64 ? (const void*)gcn_kernel<true> : (const void*)gcn_kernel<false>, dim3(nb), dim3(THREADS), args, SMEM_LAUNCH, cudaStreamPerThread);
}
```

```cpp
#include <cuda_runtime.h>
#include <cuda.h>
#include <cuda_bf16.h>
#include <stdint.h>

#define NPMIN 4
#define PMIN 6
namespace {

constexpr int N_MAX = 65536;
constexpr int NPMAX = 11;
constexpr int THREADS = 512;
constexpr int EPT = 12;
constexpr int CH_MAX = THREADS * EPT;
constexpr int NB_MAX = 134;
constexpr int GAL = 128;
constexpr int CE = 64;
constexpr int P1B = (256 + NB_MAX * CE * 2 + GAL - 1) / GAL * GAL;
constexpr int P2B = (256 + NB_MAX * CE * 4 + GAL - 1) / GAL * GAL;
constexpr int NPB_MAX = 384;
constexpr int SLOT_CAP = 6784;
constexpr int TILE_CAP = 124;
constexpr int TILE_X = 8;
constexpr int NCLS = 64;
constexpr int XCAP = 128;
constexpr int NSTAGE = 2;
constexpr int TR = 2;
constexpr float LOG2E = 1.4426950408889634f;

__device__ __align__(128) uint4 g_str[NB_MAX * (P1B + P2B) / 16];
__device__ __align__(128) unsigned g_bar[32];
__device__ float g_slow[N_MAX * 128];

#define WS(k)
#define WGD()
#define FBT(k)
#define WSP(k)
#define WSL(k)
#define WSG(k)
#define WG0()
#define WG1()
#define SMEM_LAUNCH SMEM_BYTES
#define FORCE64 0
#define EDHI ((16ull << 32) | (3ull << 62))
template<int NP> struct TileMMA;
template<> struct TileMMA<4> {
  static __device__ __forceinline__ void issue(float* g, float* h, const uint32_t* w, uint64_t dx, uint64_t de, uint64_t dh, uint64_t dc) {
    asm volatile(
      "{\n.reg .b64 dx1, dx2, dx3;\n"
      "add.s64 dx1, %72, 2;\nadd.s64 dx2, %72, 4;\nadd.s64 dx3, %72, 6;\n"
      "wgmma.fence.sync.aligned;\n"
      "wgmma.mma_async.sync.aligned.m64n32k16.f32.bf16.bf16 {%0, %1, %2, %3, %4, %5, %6, %7, %8, %9, %10, %11, %12, %13, %14, %15}, {%68, %69, %70, %71}, %74, 0, 1, 1, 0;\n"
      "wgmma.mma_async.sync.aligned.m64n32k16.f32.bf16.bf16 {%0, %1, %2, %3, %4, %5, %6, %7, %8, %9, %10, %11, %12, %13, %14, %15}, {%48, %49, %50, %51}, %73, 1, 1, 1, 0;\n"
      "wgmma.mma_async.sync.aligned.m64n32k16.f32.bf16.bf16 {%0, %1, %2, %3, %4, %5, %6, %7, %8, %9, %10, %11, %12, %13, %14, %15}, {%32, %33, %34, %35}, %72, 1, 1, 1, 0;\n"
      "wgmma.mma_async.sync.aligned.m64n32k16.f32.bf16.bf16 {%0, %1, %2, %3, %4, %5, %6, %7, %8, %9, %10, %11, %12, %13, %14, %15}, {%36, %37, %38, %39}, dx1, 1, 1, 1, 0;\n"
      "wgmma.mma_async.sync.aligned.m64n32k16.f32.bf16.bf16 {%0, %1, %2, %3, %4, %5, %6, %7, %8, %9, %10, %11, %12, %13, %14, %15}, {%40, %41, %42, %43}, dx2, 1, 1, 1, 0;\n"
      "wgmma.mma_async.sync.aligned.m64n32k16.f32.bf16.bf16 {%0, %1, %2, %3, %4, %5, %6, %7, %8, %9, %10, %11, %12, %13, %14, %15}, {%44, %45, %46, %47}, dx3, 1, 1, 1, 0;\n"
      "wgmma.commit_group.sync.aligned;\n"
      "wgmma.mma_async.sync.aligned.m64n32k16.f32.bf16.bf16 {%16, %17, %18, %19, %20, %21, %22, %23, %24, %25, %26, %27, %28, %29, %30, %31}, {%52, %53, %54, %55}, %72, 0, 1, 1, 0;\n"
      "wgmma.mma_async.sync.aligned.m64n32k16.f32.bf16.bf16 {%16, %17, %18, %19, %20, %21, %22, %23, %24, %25, %26, %27, %28, %29, %30, %31}, {%56, %57, %58, %59}, dx1, 1, 1, 1, 0;\n"
      "wgmma.mma_async.sync.aligned.m64n32k16.f32.bf16.bf16 {%16, %17, %18, %19, %20, %21, %22, %23, %24, %25, %26, %27, %28, %29, %30, %31}, {%60, %61, %62, %63}, dx2, 1, 1, 1, 0;\n"
      "wgmma.mma_async.sync.aligned.m64n32k16.f32.bf16.bf16 {%16, %17, %18, %19, %20, %21, %22, %23, %24, %25, %26, %27, %28, %29, %30, %31}, {%64, %65, %66, %67}, dx3, 1, 1, 1, 0;\n"
      "wgmma.commit_group.sync.aligned;\n}\n"
      : "=f"(g[0]), "=f"(g[1]), "=f"(g[2]), "=f"(g[3]), "=f"(g[4]), "=f"(g[5]), "=f"(g[6]), "=f"(g[7]), "=f"(g[8]), "=f"(g[9]), "=f"(g[10]), "=f"(g[11]), "=f"(g[12]), "=f"(g[13]), "=f"(g[14]), "=f"(g[15]),
        "=f"(h[0]), "=f"(h[1]), "=f"(h[2]), "=f"(h[3]), "=f"(h[4]), "=f"(h[5]), "=f"(h[6]), "=f"(h[7]), "=f"(h[8]), "=f"(h[9]), "=f"(h[10]), "=f"(h[11]), "=f"(h[12]), "=f"(h[13]), "=f"(h[14]), "=f"(h[15])
      : "r"(w[0]), "r"(w[1]), "r"(w[2]), "r"(w[3]), "r"(w[4]), "r"(w[5]), "r"(w[6]), "r"(w[7]), "r"(w[8]), "r"(w[9]), "r"(w[10]), "r"(w[11]), "r"(w[12]), "r"(w[13]), "r"(w[14]), "r"(w[15]), "r"(w[16]), "r"(w[17]), "r"(w[18]), "r"(w[19]), "r"(w[20]), "r"(w[21]), "r"(w[22]), "r"(w[23]), "r"(w[24]), "r"(w[25]), "r"(w[26]), "r"(w[27]), "r"(w[28]), "r"(w[29]), "r"(w[30]), "r"(w[31]), "r"(w[32]), "r"(w[33]), "r"(w[34]), "r"(w[35]), "r"(w[36]), "r"(w[37]), "r"(w[38]), "r"(w[39]), "l"(dx), "l"(de), "l"(dh)
      : "memory");
  }
  static __device__ __forceinline__ void wait_g(float* g) {
    asm volatile("wgmma.wait_group.sync.aligned 1;\n"
      : "+f"(g[0]), "+f"(g[1]), "+f"(g[2]), "+f"(g[3]), "+f"(g[4]), "+f"(g[5]), "+f"(g[6]), "+f"(g[7]), "+f"(g[8]), "+f"(g[9]), "+f"(g[10]), "+f"(g[11]), "+f"(g[12]), "+f"(g[13]), "+f"(g[14]), "+f"(g[15])
      :: "memory");
  }
  static __device__ __forceinline__ void wait_h(float* h) {
    asm volatile("wgmma.wait_group.sync.aligned 0;\n"
      : "+f"(h[0]), "+f"(h[1]), "+f"(h[2]), "+f"(h[3]), "+f"(h[4]), "+f"(h[5]), "+f"(h[6]), "+f"(h[7]), "+f"(h[8]), "+f"(h[9]), "+f"(h[10]), "+f"(h[11]), "+f"(h[12]), "+f"(h[13]), "+f"(h[14]), "+f"(h[15])
      :: "memory");
  }
};
template<> struct TileMMA<5> {
  static __device__ __forceinline__ void issue(float* g, float* h, const uint32_t* w, uint64_t dx, uint64_t de, uint64_t dh, uint64_t dc) {
    asm volatile(
      "{\n.reg .b64 dx1, dx2, dx3;\n"
      "add.s64 dx1, %80, 2;\nadd.s64 dx2, %80, 4;\nadd.s64 dx3, %80, 6;\n"
      "wgmma.fence.sync.aligned;\n"
      "wgmma.mma_async.sync.aligned.m64n40k16.f32.bf16.bf16 {%0, %1, %2, %3, %4, %5, %6, %7, %8, %9, %10, %11, %12, %13, %14, %15, %16, %17, %18, %19}, {%76, %77, %78, %79}, %82, 0, 1, 1, 0;\n"
      "wgmma.mma_async.sync.aligned.m64n40k16.f32.bf16.bf16 {%0, %1, %2, %3, %4, %5, %6, %7, %8, %9, %10, %11, %12, %13, %14, %15, %16, %17, %18, %19}, {%56, %57, %58, %59}, %81, 1, 1, 1, 0;\n"
      "wgmma.mma_async.sync.aligned.m64n40k16.f32.bf16.bf16 {%0, %1, %2, %3, %4, %5, %6, %7, %8, %9, %10, %11, %12, %13, %14, %15, %16, %17, %18, %19}, {%40, %41, %42, %43}, %80, 1, 1, 1, 0;\n"
      "wgmma.mma_async.sync.aligned.m64n40k16.f32.bf16.bf16 {%0, %1, %2, %3, %4, %5, %6, %7, %8, %9, %10, %11, %12, %13, %14, %15, %16, %17, %18, %19}, {%44, %45, %46, %47}, dx1, 1, 1, 1, 0;\n"
      "wgmma.mma_async.sync.aligned.m64n40k16.f32.bf16.bf16 {%0, %1, %2, %3, %4, %5, %6, %7, %8, %9, %10, %11, %12, %13, %14, %15, %16, %17, %18, %19}, {%48, %49, %50, %51}, dx2, 1, 1, 1, 0;\n"
      "wgmma.mma_async.sync.aligned.m64n40k16.f32.bf16.bf16 {%0, %1, %2, %3, %4, %5, %6, %7, %8, %9, %10, %11, %12, %13, %14, %15, %16, %17, %18, %19}, {%52, %53, %54, %55}, dx3, 1, 1, 1, 0;\n"
      "wgmma.commit_group.sync.aligned;\n"
      "wgmma.mma_async.sync.aligned.m64n40k16.f32.bf16.bf16 {%20, %21, %22, %23, %24, %25, %26, %27, %28, %29, %30, %31, %32, %33, %34, %35, %36, %37, %38, %39}, {%60, %61, %62, %63}, %80, 0, 1, 1, 0;\n"
      "wgmma.mma_async.sync.aligned.m64n40k16.f32.bf16.bf16 {%20, %21, %22, %23, %24, %25, %26, %27, %28, %29, %30, %31, %32, %33, %34, %35, %36, %37, %38, %39}, {%64, %65, %66, %67}, dx1, 1, 1, 1, 0;\n"
      "wgmma.mma_async.sync.aligned.m64n40k16.f32.bf16.bf16 {%20, %21, %22, %23, %24, %25, %26, %27, %28, %29, %30, %31, %32, %33, %34, %35, %36, %37, %38, %39}, {%68, %69, %70, %71}, dx2, 1, 1, 1, 0;\n"
      "wgmma.mma_async.sync.aligned.m64n40k16.f32.bf16.bf16 {%20, %21, %22, %23, %24, %25, %26, %27, %28, %29, %30, %31, %32, %33, %34, %35, %36, %37, %38, %39}, {%72, %73, %74, %75}, dx3, 1, 1, 1, 0;\n"
      "wgmma.commit_group.sync.aligned;\n}\n"
      : "=f"(g[0]), "=f"(g[1]), "=f"(g[2]), "=f"(g[3]), "=f"(g[4]), "=f"(g[5]), "=f"(g[6]), "=f"(g[7]), "=f"(g[8]), "=f"(g[9]), "=f"(g[10]), "=f"(g[11]), "=f"(g[12]), "=f"(g[13]), "=f"(g[14]), "=f"(g[15]), "=f"(g[16]), "=f"(g[17]), "=f"(g[18]), "=f"(g[19]),
        "=f"(h[0]), "=f"(h[1]), "=f"(h[2]), "=f"(h[3]), "=f"(h[4]), "=f"(h[5]), "=f"(h[6]), "=f"(h[7]), "=f"(h[8]), "=f"(h[9]), "=f"(h[10]), "=f"(h[11]), "=f"(h[12]), "=f"(h[13]), "=f"(h[14]), "=f"(h[15]), "=f"(h[16]), "=f"(h[17]), "=f"(h[18]), "=f"(h[19])
      : "r"(w[0]), "r"(w[1]), "r"(w[2]), "r"(w[3]), "r"(w[4]), "r"(w[5]), "r"(w[6]), "r"(w[7]), "r"(w[8]), "r"(w[9]), "r"(w[10]), "r"(w[11]), "r"(w[12]), "r"(w[13]), "r"(w[14]), "r"(w[15]), "r"(w[16]), "r"(w[17]), "r"(w[18]), "r"(w[19]), "r"(w[20]), "r"(w[21]), "r"(w[22]), "r"(w[23]), "r"(w[24]), "r"(w[25]), "r"(w[26]), "r"(w[27]), "r"(w[28]), "r"(w[29]), "r"(w[30]), "r"(w[31]), "r"(w[32]), "r"(w[33]), "r"(w[34]), "r"(w[35]), "r"(w[36]), "r"(w[37]), "r"(w[38]), "r"(w[39]), "l"(dx), "l"(de), "l"(dh)
      : "memory");
  }
  static __device__ __forceinline__ void wait_g(float* g) {
    asm volatile("wgmma.wait_group.sync.aligned 1;\n"
      : "+f"(g[0]), "+f"(g[1]), "+f"(g[2]), "+f"(g[3]), "+f"(g[4]), "+f"(g[5]), "+f"(g[6]), "+f"(g[7]), "+f"(g[8]), "+f"(g[9]), "+f"(g[10]), "+f"(g[11]), "+f"(g[12]), "+f"(g[13]), "+f"(g[14]), "+f"(g[15]), "+f"(g[16]), "+f"(g[17]), "+f"(g[18]), "+f"(g[19])
      :: "memory");
  }
  static __device__ __forceinline__ void wait_h(float* h) {
    asm volatile("wgmma.wait_group.sync.aligned 0;\n"
      : "+f"(h[0]), "+f"(h[1]), "+f"(h[2]), "+f"(h[3]), "+f"(h[4]), "+f"(h[5]), "+f"(h[6]), "+f"(h[7]), "+f"(h[8]), "+f"(h[9]), "+f"(h[10]), "+f"(h[11]), "+f"(h[12]), "+f"(h[13]), "+f"(h[14]), "+f"(h[15]), "+f"(h[16]), "+f"(h[17]), "+f"(h[18]), "+f"(h[19])
      :: "memory");
  }
};
template<> struct TileMMA<6> {
  static __device__ __forceinline__ void issue(float* g, float* h, const uint32_t* w, uint64_t dx, uint64_t de, uint64_t dh, uint64_t dc) {
    asm volatile(
      "{\n.reg .b64 dx1, dx2, dx3;\n"
      "add.s64 dx1, %88, 2;\nadd.s64 dx2, %88, 4;\nadd.s64 dx3, %88, 6;\n"
      "wgmma.fence.sync.aligned;\n"
      "wgmma.mma_async.sync.aligned.m64n48k16.f32.bf16.bf16 {%0, %1, %2, %3, %4, %5, %6, %7, %8, %9, %10, %11, %12, %13, %14, %15, %16, %17, %18, %19, %20, %21, %22, %23}, {%84, %85, %86, %87}, %90, 0, 1, 1, 0;\n"
      "wgmma.mma_async.sync.aligned.m64n48k16.f32.bf16.bf16 {%0, %1, %2, %3, %4, %5, %6, %7, %8, %9, %10, %11, %12, %13, %14, %15, %16, %17, %18, %19, %20, %21, %22, %23}, {%64, %65, %66, %67}, %89, 1, 1, 1, 0;\n"
      "wgmma.mma_async.sync.aligned.m64n48k16.f32.bf16.bf16 {%0, %1, %2, %3, %4, %5, %6, %7, %8, %9, %10, %11, %12, %13, %14, %15, %16, %17, %18, %19, %20, %21, %22, %23}, {%48, %49, %50, %51}, %88, 1, 1, 1, 0;\n"
      "wgmma.mma_async.sync.aligned.m64n48k16.f32.bf16.bf16 {%0, %1, %2, %3, %4, %5, %6, %7, %8, %9, %10, %11, %12, %13, %14, %15, %16, %17, %18, %19, %20, %21, %22, %23}, {%52, %53, %54, %55}, dx1, 1, 1, 1, 0;\n"
      "wgmma.mma_async.sync.aligned.m64n48k16.f32.bf16.bf16 {%0, %1, %2, %3, %4, %5, %6, %7, %8, %9, %10, %11, %12, %13, %14, %15, %16, %17, %18, %19, %20, %21, %22, %23}, {%56, %57, %58, %59}, dx2, 1, 1, 1, 0;\n"
      "wgmma.mma_async.sync.aligned.m64n48k16.f32.bf16.bf16 {%0, %1, %2, %3, %4, %5, %6, %7, %8, %9, %10, %11, %12, %13, %14, %15, %16, %17, %18, %19, %20, %21, %22, %23}, {%60, %61, %62, %63}, dx3, 1, 1, 1, 0;\n"
      "wgmma.commit_group.sync.aligned;\n"
      "wgmma.mma_async.sync.aligned.m64n48k16.f32.bf16.bf16 {%24, %25, %26, %27, %28, %29, %30, %31, %32, %33, %34, %35, %36, %37, %38, %39, %40, %41, %42, %43, %44, %45, %46, %47}, {%68, %69, %70, %71}, %88, 0, 1, 1, 0;\n"
      "wgmma.mma_async.sync.aligned.m64n48k16.f32.bf16.bf16 {%24, %25, %26, %27, %28, %29, %30, %31, %32, %33, %34, %35, %36, %37, %38, %39, %40, %41, %42, %43, %44, %45, %46, %47}, {%72, %73, %74, %75}, dx1, 1, 1, 1, 0;\n"
      "wgmma.mma_async.sync.aligned.m64n48k16.f32.bf16.bf16 {%24, %25, %26, %27, %28, %29, %30, %31, %32, %33, %34, %35, %36, %37, %38, %39, %40, %41, %42, %43, %44, %45, %46, %47}, {%76, %77, %78, %79}, dx2, 1, 1, 1, 0;\n"
      "wgmma.mma_async.sync.aligned.m64n48k16.f32.bf16.bf16 {%24, %25, %26, %27, %28, %29, %30, %31, %32, %33, %34, %35, %36, %37, %38, %39, %40, %41, %42, %43, %44, %45, %46, %47}, {%80, %81, %82, %83}, dx3, 1, 1, 1, 0;\n"
      "wgmma.commit_group.sync.aligned;\n}\n"
      : "=f"(g[0]), "=f"(g[1]), "=f"(g[2]), "=f"(g[3]), "=f"(g[4]), "=f"(g[5]), "=f"(g[6]), "=f"(g[7]), "=f"(g[8]), "=f"(g[9]), "=f"(g[10]), "=f"(g[11]), "=f"(g[12]), "=f"(g[13]), "=f"(g[14]), "=f"(g[15]), "=f"(g[16]), "=f"(g[17]), "=f"(g[18]), "=f"(g[19]), "=f"(g[20]), "=f"(g[21]), "=f"(g[22]), "=f"(g[23]),
        "=f"(h[0]), "=f"(h[1]), "=f"(h[2]), "=f"(h[3]), "=f"(h[4]), "=f"(h[5]), "=f"(h[6]), "=f"(h[7]), "=f"(h[8]), "=f"(h[9]), "=f"(h[10]), "=f"(h[11]), "=f"(h[12]), "=f"(h[13]), "=f"(h[14]), "=f"(h[15]), "=f"(h[16]), "=f"(h[17]), "=f"(h[18]), "=f"(h[19]), "=f"(h[20]), "=f"(h[21]), "=f"(h[22]), "=f"(h[23])
      : "r"(w[0]), "r"(w[1]), "r"(w[2]), "r"(w[3]), "r"(w[4]), "r"(w[5]), "r"(w[6]), "r"(w[7]), "r"(w[8]), "r"(w[9]), "r"(w[10]), "r"(w[11]), "r"(w[12]), "r"(w[13]), "r"(w[14]), "r"(w[15]), "r"(w[16]), "r"(w[17]), "r"(w[18]), "r"(w[19]), "r"(w[20]), "r"(w[21]), "r"(w[22]), "r"(w[23]), "r"(w[24]), "r"(w[25]), "r"(w[26]), "r"(w[27]), "r"(w[28]), "r"(w[29]), "r"(w[30]), "r"(w[31]), "r"(w[32]), "r"(w[33]), "r"(w[34]), "r"(w[35]), "r"(w[36]), "r"(w[37]), "r"(w[38]), "r"(w[39]), "l"(dx), "l"(de), "l"(dh)
      : "memory");
  }
  static __device__ __forceinline__ void wait_g(float* g) {
    asm volatile("wgmma.wait_group.sync.aligned 1;\n"
      : "+f"(g[0]), "+f"(g[1]), "+f"(g[2]), "+f"(g[3]), "+f"(g[4]), "+f"(g[5]), "+f"(g[6]), "+f"(g[7]), "+f"(g[8]), "+f"(g[9]), "+f"(g[10]), "+f"(g[11]), "+f"(g[12]), "+f"(g[13]), "+f"(g[14]), "+f"(g[15]), "+f"(g[16]), "+f"(g[17]), "+f"(g[18]), "+f"(g[19]), "+f"(g[20]), "+f"(g[21]), "+f"(g[22]), "+f"(g[23])
      :: "memory");
  }
  static __device__ __forceinline__ void wait_h(float* h) {
    asm volatile("wgmma.wait_group.sync.aligned 0;\n"
      : "+f"(h[0]), "+f"(h[1]), "+f"(h[2]), "+f"(h[3]), "+f"(h[4]), "+f"(h[5]), "+f"(h[6]), "+f"(h[7]), "+f"(h[8]), "+f"(h[9]), "+f"(h[10]), "+f"(h[11]), "+f"(h[12]), "+f"(h[13]), "+f"(h[14]), "+f"(h[15]), "+f"(h[16]), "+f"(h[17]), "+f"(h[18]), "+f"(h[19]), "+f"(h[20]), "+f"(h[21]), "+f"(h[22]), "+f"(h[23])
      :: "memory");
  }
};
template<> struct TileMMA<7> {
  static __device__ __forceinline__ void issue(float* g, float* h, const uint32_t* w, uint64_t dx, uint64_t de, uint64_t dh, uint64_t dc) {
    asm volatile(
      "{\n.reg .b64 dx1, dx2, dx3;\n"
      "add.s64 dx1, %96, 2;\nadd.s64 dx2, %96, 4;\nadd.s64 dx3, %96, 6;\n"
      "wgmma.fence.sync.aligned;\n"
      "wgmma.mma_async.sync.aligned.m64n56k16.f32.bf16.bf16 {%0, %1, %2, %3, %4, %5, %6, %7, %8, %9, %10, %11, %12, %13, %14, %15, %16, %17, %18, %19, %20, %21, %22, %23, %24, %25, %26, %27}, {%92, %93, %94, %95}, %98, 0, 1, 1, 0;\n"
      "wgmma.mma_async.sync.aligned.m64n56k16.f32.bf16.bf16 {%0, %1, %2, %3, %4, %5, %6, %7, %8, %9, %10, %11, %12, %13, %14, %15, %16, %17, %18, %19, %20, %21, %22, %23, %24, %25, %26, %27}, {%72, %73, %74, %75}, %97, 1, 1, 1, 0;\n"
      "wgmma.mma_async.sync.aligned.m64n56k16.f32.bf16.bf16 {%0, %1, %2, %3, %4, %5, %6, %7, %8, %9, %10, %11, %12, %13, %14, %15, %16, %17, %18, %19, %20, %21, %22, %23, %24, %25, %26, %27}, {%56, %57, %58, %59}, %96, 1, 1, 1, 0;\n"
      "wgmma.mma_async.sync.aligned.m64n56k16.f32.bf16.bf16 {%0, %1, %2, %3, %4, %5, %6, %7, %8, %9, %10, %11, %12, %13, %14, %15, %16, %17, %18, %19, %20, %21, %22, %23, %24, %25, %26, %27}, {%60, %61, %62, %63}, dx1, 1, 1, 1, 0;\n"
      "wgmma.mma_async.sync.aligned.m64n56k16.f32.bf16.bf16 {%0, %1, %2, %3, %4, %5, %6, %7, %8, %9, %10, %11, %12, %13, %14, %15, %16, %17, %18, %19, %20, %21, %22, %23, %24, %25, %26, %27}, {%64, %65, %66, %67}, dx2, 1, 1, 1, 0;\n"
      "wgmma.mma_async.sync.aligned.m64n56k16.f32.bf16.bf16 {%0, %1, %2, %3, %4, %5, %6, %7, %8, %9, %10, %11, %12, %13, %14, %15, %16, %17, %18, %19, %20, %21, %22, %23, %24, %25, %26, %27}, {%68, %69, %70, %71}, dx3, 1, 1, 1, 0;\n"
      "wgmma.commit_group.sync.aligned;\n"
      "wgmma.mma_async.sync.aligned.m64n56k16.f32.bf16.bf16 {%28, %29, %30, %31, %32, %33, %34, %35, %36, %37, %38, %39, %40, %41, %42, %43, %44, %45, %46, %47, %48, %49, %50, %51, %52, %53, %54, %55}, {%76, %77, %78, %79}, %96, 0, 1, 1, 0;\n"
      "wgmma.mma_async.sync.aligned.m64n56k16.f32.bf16.bf16 {%28, %29, %30, %31, %32, %33, %34, %35, %36, %37, %38, %39, %40, %41, %42, %43, %44, %45, %46, %47, %48, %49, %50, %51, %52, %53, %54, %55}, {%80, %81, %82, %83}, dx1, 1, 1, 1, 0;\n"
      "wgmma.mma_async.sync.aligned.m64n56k16.f32.bf16.bf16 {%28, %29, %30, %31, %32, %33, %34, %35, %36, %37, %38, %39, %40, %41, %42, %43, %44, %45, %46, %47, %48, %49, %50, %51, %52, %53, %54, %55}, {%84, %85, %86, %87}, dx2, 1, 1, 1, 0;\n"
      "wgmma.mma_async.sync.aligned.m64n56k16.f32.bf16.bf16 {%28, %29, %30, %31, %32, %33, %34, %35, %36, %37, %38, %39, %40, %41, %42, %43, %44, %45, %46, %47, %48, %49, %50, %51, %52, %53, %54, %55}, {%88, %89, %90, %91}, dx3, 1, 1, 1, 0;\n"
      "wgmma.commit_group.sync.aligned;\n}\n"
      : "=f"(g[0]), "=f"(g[1]), "=f"(g[2]), "=f"(g[3]), "=f"(g[4]), "=f"(g[5]), "=f"(g[6]), "=f"(g[7]), "=f"(g[8]), "=f"(g[9]), "=f"(g[10]), "=f"(g[11]), "=f"(g[12]), "=f"(g[13]), "=f"(g[14]), "=f"(g[15]), "=f"(g[16]), "=f"(g[17]), "=f"(g[18]), "=f"(g[19]), "=f"(g[20]), "=f"(g[21]), "=f"(g[22]), "=f"(g[23]), "=f"(g[24]), "=f"(g[25]), "=f"(g[26]), "=f"(g[27]),
        "=f"(h[0]), "=f"(h[1]), "=f"(h[2]), "=f"(h[3]), "=f"(h[4]), "=f"(h[5]), "=f"(h[6]), "=f"(h[7]), "=f"(h[8]), "=f"(h[9]), "=f"(h[10]), "=f"(h[11]), "=f"(h[12]), "=f"(h[13]), "=f"(h[14]), "=f"(h[15]), "=f"(h[16]), "=f"(h[17]), "=f"(h[18]), "=f"(h[19]), "=f"(h[20]), "=f"(h[21]), "=f"(h[22]), "=f"(h[23]), "=f"(h[24]), "=f"(h[25]), "=f"(h[26]), "=f"(h[27])
      : "r"(w[0]), "r"(w[1]), "r"(w[2]), "r"(w[3]), "r"(w[4]), "r"(w[5]), "r"(w[6]), "r"(w[7]), "r"(w[8]), "r"(w[9]), "r"(w[10]), "r"(w[11]), "r"(w[12]), "r"(w[13]), "r"(w[14]), "r"(w[15]), "r"(w[16]), "r"(w[17]), "r"(w[18]), "r"(w[19]), "r"(w[20]), "r"(w[21]), "r"(w[22]), "r"(w[23]), "r"(w[24]), "r"(w[25]), "r"(w[26]), "r"(w[27]), "r"(w[28]), "r"(w[29]), "r"(w[30]), "r"(w[31]), "r"(w[32]), "r"(w[33]), "r"(w[34]), "r"(w[35]), "r"(w[36]), "r"(w[37]), "r"(w[38]), "r"(w[39]), "l"(dx), "l"(de), "l"(dh)
      : "memory");
  }
  static __device__ __forceinline__ void wait_g(float* g) {
    asm volatile("wgmma.wait_group.sync.aligned 1;\n"
      : "+f"(g[0]), "+f"(g[1]), "+f"(g[2]), "+f"(g[3]), "+f"(g[4]), "+f"(g[5]), "+f"(g[6]), "+f"(g[7]), "+f"(g[8]), "+f"(g[9]), "+f"(g[10]), "+f"(g[11]), "+f"(g[12]), "+f"(g[13]), "+f"(g[14]), "+f"(g[15]), "+f"(g[16]), "+f"(g[17]), "+f"(g[18]), "+f"(g[19]), "+f"(g[20]), "+f"(g[21]), "+f"(g[22]), "+f"(g[23]), "+f"(g[24]), "+f"(g[25]), "+f"(g[26]), "+f"(g[27])
      :: "memory");
  }
  static __device__ __forceinline__ void wait_h(float* h) {
    asm volatile("wgmma.wait_group.sync.aligned 0;\n"
      : "+f"(h[0]), "+f"(h[1]), "+f"(h[2]), "+f"(h[3]), "+f"(h[4]), "+f"(h[5]), "+f"(h[6]), "+f"(h[7]), "+f"(h[8]), "+f"(h[9]), "+f"(h[10]), "+f"(h[11]), "+f"(h[12]), "+f"(h[13]), "+f"(h[14]), "+f"(h[15]), "+f"(h[16]), "+f"(h[17]), "+f"(h[18]), "+f"(h[19]), "+f"(h[20]), "+f"(h[21]), "+f"(h[22]), "+f"(h[23]), "+f"(h[24]), "+f"(h[25]), "+f"(h[26]), "+f"(h[27])
      :: "memory");
  }
};
template<> struct TileMMA<8> {
  static __device__ __forceinline__ void issue(float* g, float* h, const uint32_t* w, uint64_t dx, uint64_t de, uint64_t dh, uint64_t dc) {
    asm volatile(
      "{\n.reg .b64 dx1, dx2, dx3;\n"
      "add.s64 dx1, %104, 2;\nadd.s64 dx2, %104, 4;\nadd.s64 dx3, %104, 6;\n"
      "wgmma.fence.sync.aligned;\n"
      "wgmma.mma_async.sync.aligned.m64n64k16.f32.bf16.bf16 {%0, %1, %2, %3, %4, %5, %6, %7, %8, %9, %10, %11, %12, %13, %14, %15, %16, %17, %18, %19, %20, %21, %22, %23, %24, %25, %26, %27, %28, %29, %30, %31}, {%100, %101, %102, %103}, %106, 0, 1, 1, 0;\n"
      "wgmma.mma_async.sync.aligned.m64n64k16.f32.bf16.bf16 {%0, %1, %2, %3, %4, %5, %6, %7, %8, %9, %10, %11, %12, %13, %14, %15, %16, %17, %18, %19, %20, %21, %22, %23, %24, %25, %26, %27, %28, %29, %30, %31}, {%80, %81, %82, %83}, %105, 1, 1, 1, 0;\n"
      "wgmma.mma_async.sync.aligned.m64n64k16.f32.bf16.bf16 {%0, %1, %2, %3, %4, %5, %6, %7, %8, %9, %10, %11, %12, %13, %14, %15, %16, %17, %18, %19, %20, %21, %22, %23, %24, %25, %26, %27, %28, %29, %30, %31}, {%64, %65, %66, %67}, %104, 1, 1, 1, 0;\n"
      "wgmma.mma_async.sync.aligned.m64n64k16.f32.bf16.bf16 {%0, %1, %2, %3, %4, %5, %6, %7, %8, %9, %10, %11, %12, %13, %14, %15, %16, %17, %18, %19, %20, %21, %22, %23, %24, %25, %26, %27, %28, %29, %30, %31}, {%68, %69, %70, %71}, dx1, 1, 1, 1, 0;\n"
      "wgmma.mma_async.sync.aligned.m64n64k16.f32.bf16.bf16 {%0, %1, %2, %3, %4, %5, %6, %7, %8, %9, %10, %11, %12, %13, %14, %15, %16, %17, %18, %19, %20, %21, %22, %23, %24, %25, %26, %27, %28, %29, %30, %31}, {%72, %73, %74, %75}, dx2, 1, 1, 1, 0;\n"
      "wgmma.mma_async.sync.aligned.m64n64k16.f32.bf16.bf16 {%0, %1, %2, %3, %4, %5, %6, %7, %8, %9, %10, %11, %12, %13, %14, %15, %16, %17, %18, %19, %20, %21, %22, %23, %24, %25, %26, %27, %28, %29, %30, %31}, {%76, %77, %78, %79}, dx3, 1, 1, 1, 0;\n"
      "wgmma.commit_group.sync.aligned;\n"
      "wgmma.mma_async.sync.aligned.m64n64k16.f32.bf16.bf16 {%32, %33, %34, %35, %36, %37, %38, %39, %40, %41, %42, %43, %44, %45, %46, %47, %48, %49, %50, %51, %52, %53, %54, %55, %56, %57, %58, %59, %60, %61, %62, %63}, {%84, %85, %86, %87}, %104, 0, 1, 1, 0;\n"
      "wgmma.mma_async.sync.aligned.m64n64k16.f32.bf16.bf16 {%32, %33, %34, %35, %36, %37, %38, %39, %40, %41, %42, %43, %44, %45, %46, %47, %48, %49, %50, %51, %52, %53, %54, %55, %56, %57, %58, %59, %60, %61, %62, %63}, {%88, %89, %90, %91}, dx1, 1, 1, 1, 0;\n"
      "wgmma.mma_async.sync.aligned.m64n64k16.f32.bf16.bf16 {%32, %33, %34, %35, %36, %37, %38, %39, %40, %41, %42, %43, %44, %45, %46, %47, %48, %49, %50, %51, %52, %53, %54, %55, %56, %57, %58, %59, %60, %61, %62, %63}, {%92, %93, %94, %95}, dx2, 1, 1, 1, 0;\n"
      "wgmma.mma_async.sync.aligned.m64n64k16.f32.bf16.bf16 {%32, %33, %34, %35, %36, %37, %38, %39, %40, %41, %42, %43, %44, %45, %46, %47, %48, %49, %50, %51, %52, %53, %54, %55, %56, %57, %58, %59, %60, %61, %62, %63}, {%96, %97, %98, %99}, dx3, 1, 1, 1, 0;\n"
      "wgmma.commit_group.sync.aligned;\n}\n"
      : "=f"(g[0]), "=f"(g[1]), "=f"(g[2]), "=f"(g[3]), "=f"(g[4]), "=f"(g[5]), "=f"(g[6]), "=f"(g[7]), "=f"(g[8]), "=f"(g[9]), "=f"(g[10]), "=f"(g[11]), "=f"(g[12]), "=f"(g[13]), "=f"(g[14]), "=f"(g[15]), "=f"(g[16]), "=f"(g[17]), "=f"(g[18]), "=f"(g[19]), "=f"(g[20]), "=f"(g[21]), "=f"(g[22]), "=f"(g[23]), "=f"(g[24]), "=f"(g[25]), "=f"(g[26]), "=f"(g[27]), "=f"(g[28]), "=f"(g[29]), "=f"(g[30]), "=f"(g[31]),
        "=f"(h[0]), "=f"(h[1]), "=f"(h[2]), "=f"(h[3]), "=f"(h[4]), "=f"(h[5]), "=f"(h[6]), "=f"(h[7]), "=f"(h[8]), "=f"(h[9]), "=f"(h[10]), "=f"(h[11]), "=f"(h[12]), "=f"(h[13]), "=f"(h[14]), "=f"(h[15]), "=f"(h[16]), "=f"(h[17]), "=f"(h[18]), "=f"(h[19]), "=f"(h[20]), "=f"(h[21]), "=f"(h[22]), "=f"(h[23]), "=f"(h[24]), "=f"(h[25]), "=f"(h[26]), "=f"(h[27]), "=f"(h[28]), "=f"(h[29]), "=f"(h[30]), "=f"(h[31])
      : "r"(w[0]), "r"(w[1]), "r"(w[2]), "r"(w[3]), "r"(w[4]), "r"(w[5]), "r"(w[6]), "r"(w[7]), "r"(w[8]), "r"(w[9]), "r"(w[10]), "r"(w[11]), "r"(w[12]), "r"(w[13]), "r"(w[14]), "r"(w[15]), "r"(w[16]), "r"(w[17]), "r"(w[18]), "r"(w[19]), "r"(w[20]), "r"(w[21]), "r"(w[22]), "r"(w[23]), "r"(w[24]), "r"(w[25]), "r"(w[26]), "r"(w[27]), "r"(w[28]), "r"(w[29]), "r"(w[30]), "r"(w[31]), "r"(w[32]), "r"(w[33]), "r"(w[34]), "r"(w[35]), "r"(w[36]), "r"(w[37]), "r"(w[38]), "r"(w[39]), "l"(dx), "l"(de), "l"(dh)
      : "memory");
  }
  static __device__ __forceinline__ void wait_g(float* g) {
    asm volatile("wgmma.wait_group.sync.aligned 1;\n"
      : "+f"(g[0]), "+f"(g[1]), "+f"(g[2]), "+f"(g[3]), "+f"(g[4]), "+f"(g[5]), "+f"(g[6]), "+f"(g[7]), "+f"(g[8]), "+f"(g[9]), "+f"(g[10]), "+f"(g[11]), "+f"(g[12]), "+f"(g[13]), "+f"(g[14]), "+f"(g[15]), "+f"(g[16]), "+f"(g[17]), "+f"(g[18]), "+f"(g[19]), "+f"(g[20]), "+f"(g[21]), "+f"(g[22]), "+f"(g[23]), "+f"(g[24]), "+f"(g[25]), "+f"(g[26]), "+f"(g[27]), "+f"(g[28]), "+f"(g[29]), "+f"(g[30]), "+f"(g[31])
      :: "memory");
  }
  static __device__ __forceinline__ void wait_h(float* h) {
    asm volatile("wgmma.wait_group.sync.aligned 0;\n"
      : "+f"(h[0]), "+f"(h[1]), "+f"(h[2]), "+f"(h[3]), "+f"(h[4]), "+f"(h[5]), "+f"(h[6]), "+f"(h[7]), "+f"(h[8]), "+f"(h[9]), "+f"(h[10]), "+f"(h[11]), "+f"(h[12]), "+f"(h[13]), "+f"(h[14]), "+f"(h[15]), "+f"(h[16]), "+f"(h[17]), "+f"(h[18]), "+f"(h[19]), "+f"(h[20]), "+f"(h[21]), "+f"(h[22]), "+f"(h[23]), "+f"(h[24]), "+f"(h[25]), "+f"(h[26]), "+f"(h[27]), "+f"(h[28]), "+f"(h[29]), "+f"(h[30]), "+f"(h[31])
      :: "memory");
  }
};
template<> struct TileMMA<9> {
  static __device__ __forceinline__ void issue(float* g, float* h, const uint32_t* w, uint64_t dx, uint64_t de, uint64_t dh, uint64_t dc) {
    asm volatile(
      "{\n.reg .b64 dx1, dx2, dx3;\n"
      "add.s64 dx1, %112, 2;\nadd.s64 dx2, %112, 4;\nadd.s64 dx3, %112, 6;\n"
      "wgmma.fence.sync.aligned;\n"
      "wgmma.mma_async.sync.aligned.m64n72k16.f32.bf16.bf16 {%0, %1, %2, %3, %4, %5, %6, %7, %8, %9, %10, %11, %12, %13, %14, %15, %16, %17, %18, %19, %20, %21, %22, %23, %24, %25, %26, %27, %28, %29, %30, %31, %32, %33, %34, %35}, {%108, %109, %110, %111}, %114, 0, 1, 1, 0;\n"
      "wgmma.mma_async.sync.aligned.m64n72k16.f32.bf16.bf16 {%0, %1, %2, %3, %4, %5, %6, %7, %8, %9, %10, %11, %12, %13, %14, %15, %16, %17, %18, %19, %20, %21, %22, %23, %24, %25, %26, %27, %28, %29, %30, %31, %32, %33, %34, %35}, {%88, %89, %90, %91}, %113, 1, 1, 1, 0;\n"
      "wgmma.mma_async.sync.aligned.m64n72k16.f32.bf16.bf16 {%0, %1, %2, %3, %4, %5, %6, %7, %8, %9, %10, %11, %12, %13, %14, %15, %16, %17, %18, %19, %20, %21, %22, %23, %24, %25, %26, %27, %28, %29, %30, %31, %32, %33, %34, %35}, {%72, %73, %74, %75}, %112, 1, 1, 1, 0;\n"
      "wgmma.mma_async.sync.aligned.m64n72k16.f32.bf16.bf16 {%0, %1, %2, %3, %4, %5, %6, %7, %8, %9, %10, %11, %12, %13, %14, %15, %16, %17, %18, %19, %20, %21, %22, %23, %24, %25, %26, %27, %28, %29, %30, %31, %32, %33, %34, %35}, {%76, %77, %78, %79}, dx1, 1, 1, 1, 0;\n"
      "wgmma.mma_async.sync.aligned.m64n72k16.f32.bf16.bf16 {%0, %1, %2, %3, %4, %5, %6, %7, %8, %9, %10, %11, %12, %13, %14, %15, %16, %17, %18, %19, %20, %21, %22, %23, %24, %25, %26, %27, %28, %29, %30, %31, %32, %33, %34, %35}, {%80, %81, %82, %83}, dx2, 1, 1, 1, 0;\n"
      "wgmma.mma_async.sync.aligned.m64n72k16.f32.bf16.bf16 {%0, %1, %2, %3, %4, %5, %6, %7, %8, %9, %10, %11, %12, %13, %14, %15, %16, %17, %18, %19, %20, %21, %22, %23, %24, %25, %26, %27, %28, %29, %30, %31, %32, %33, %34, %35}, {%84, %85, %86, %87}, dx3, 1, 1, 1, 0;\n"
      "wgmma.commit_group.sync.aligned;\n"
      "wgmma.mma_async.sync.aligned.m64n72k16.f32.bf16.bf16 {%36, %37, %38, %39, %40, %41, %42, %43, %44, %45, %46, %47, %48, %49, %50, %51, %52, %53, %54, %55, %56, %57, %58, %59, %60, %61, %62, %63, %64, %65, %66, %67, %68, %69, %70, %71}, {%92, %93, %94, %95}, %112, 0, 1, 1, 0;\n"
      "wgmma.mma_async.sync.aligned.m64n72k16.f32.bf16.bf16 {%36, %37, %38, %39, %40, %41, %42, %43, %44, %45, %46, %47, %48, %49, %50, %51, %52, %53, %54, %55, %56, %57, %58, %59, %60, %61, %62, %63, %64, %65, %66, %67, %68, %69, %70, %71}, {%96, %97, %98, %99}, dx1, 1, 1, 1, 0;\n"
      "wgmma.mma_async.sync.aligned.m64n72k16.f32.bf16.bf16 {%36, %37, %38, %39, %40, %41, %42, %43, %44, %45, %46, %47, %48, %49, %50, %51, %52, %53, %54, %55, %56, %57, %58, %59, %60, %61, %62, %63, %64, %65, %66, %67, %68, %69, %70, %71}, {%100, %101, %102, %103}, dx2, 1, 1, 1, 0;\n"
      "wgmma.mma_async.sync.aligned.m64n72k16.f32.bf16.bf16 {%36, %37, %38, %39, %40, %41, %42, %43, %44, %45, %46, %47, %48, %49, %50, %51, %52, %53, %54, %55, %56, %57, %58, %59, %60, %61, %62, %63, %64, %65, %66, %67, %68, %69, %70, %71}, {%104, %105, %106, %107}, dx3, 1, 1, 1, 0;\n"
      "wgmma.commit_group.sync.aligned;\n}\n"
      : "=f"(g[0]), "=f"(g[1]), "=f"(g[2]), "=f"(g[3]), "=f"(g[4]), "=f"(g[5]), "=f"(g[6]), "=f"(g[7]), "=f"(g[8]), "=f"(g[9]), "=f"(g[10]), "=f"(g[11]), "=f"(g[12]), "=f"(g[13]), "=f"(g[14]), "=f"(g[15]), "=f"(g[16]), "=f"(g[17]), "=f"(g[18]), "=f"(g[19]), "=f"(g[20]), "=f"(g[21]), "=f"(g[22]), "=f"(g[23]), "=f"(g[24]), "=f"(g[25]), "=f"(g[26]), "=f"(g[27]), "=f"(g[28]), "=f"(g[29]), "=f"(g[30]), "=f"(g[31]), "=f"(g[32]), "=f"(g[33]), "=f"(g[34]), "=f"(g[35]),
        "=f"(h[0]), "=f"(h[1]), "=f"(h[2]), "=f"(h[3]), "=f"(h[4]), "=f"(h[5]), "=f"(h[6]), "=f"(h[7]), "=f"(h[8]), "=f"(h[9]), "=f"(h[10]), "=f"(h[11]), "=f"(h[12]), "=f"(h[13]), "=f"(h[14]), "=f"(h[15]), "=f"(h[16]), "=f"(h[17]), "=f"(h[18]), "=f"(h[19]), "=f"(h[20]), "=f"(h[21]), "=f"(h[22]), "=f"(h[23]), "=f"(h[24]), "=f"(h[25]), "=f"(h[26]), "=f"(h[27]), "=f"(h[28]), "=f"(h[29]), "=f"(h[30]), "=f"(h[31]), "=f"(h[32]), "=f"(h[33]), "=f"(h[34]), "=f"(h[35])
      : "r"(w[0]), "r"(w[1]), "r"(w[2]), "r"(w[3]), "r"(w[4]), "r"(w[5]), "r"(w[6]), "r"(w[7]), "r"(w[8]), "r"(w[9]), "r"(w[10]), "r"(w[11]), "r"(w[12]), "r"(w[13]), "r"(w[14]), "r"(w[15]), "r"(w[16]), "r"(w[17]), "r"(w[18]), "r"(w[19]), "r"(w[20]), "r"(w[21]), "r"(w[22]), "r"(w[23]), "r"(w[24]), "r"(w[25]), "r"(w[26]), "r"(w[27]), "r"(w[28]), "r"(w[29]), "r"(w[30]), "r"(w[31]), "r"(w[32]), "r"(w[33]), "r"(w[34]), "r"(w[35]), "r"(w[36]), "r"(w[37]), "r"(w[38]), "r"(w[39]), "l"(dx), "l"(de), "l"(dh)
      : "memory");
  }
  static __device__ __forceinline__ void wait_g(float* g) {
    asm volatile("wgmma.wait_group.sync.aligned 1;\n"
      : "+f"(g[0]), "+f"(g[1]), "+f"(g[2]), "+f"(g[3]), "+f"(g[4]), "+f"(g[5]), "+f"(g[6]), "+f"(g[7]), "+f"(g[8]), "+f"(g[9]), "+f"(g[10]), "+f"(g[11]), "+f"(g[12]), "+f"(g[13]), "+f"(g[14]), "+f"(g[15]), "+f"(g[16]), "+f"(g[17]), "+f"(g[18]), "+f"(g[19]), "+f"(g[20]), "+f"(g[21]), "+f"(g[22]), "+f"(g[23]), "+f"(g[24]), "+f"(g[25]), "+f"(g[26]), "+f"(g[27]), "+f"(g[28]), "+f"(g[29]), "+f"(g[30]), "+f"(g[31]), "+f"(g[32]), "+f"(g[33]), "+f"(g[34]), "+f"(g[35])
      :: "memory");
  }
  static __device__ __forceinline__ void wait_h(float* h) {
    asm volatile("wgmma.wait_group.sync.aligned 0;\n"
      : "+f"(h[0]), "+f"(h[1]), "+f"(h[2]), "+f"(h[3]), "+f"(h[4]), "+f"(h[5]), "+f"(h[6]), "+f"(h[7]), "+f"(h[8]), "+f"(h[9]), "+f"(h[10]), "+f"(h[11]), "+f"(h[12]), "+f"(h[13]), "+f"(h[14]), "+f"(h[15]), "+f"(h[16]), "+f"(h[17]), "+f"(h[18]), "+f"(h[19]), "+f"(h[20]), "+f"(h[21]), "+f"(h[22]), "+f"(h[23]), "+f"(h[24]), "+f"(h[25]), "+f"(h[26]), "+f"(h[27]), "+f"(h[28]), "+f"(h[29]), "+f"(h[30]), "+f"(h[31]), "+f"(h[32]), "+f"(h[33]), "+f"(h[34]), "+f"(h[35])
      :: "memory");
  }
};
template<> struct TileMMA<10> {
  static __device__ __forceinline__ void issue(float* g, float* h, const uint32_t* w, uint64_t dx, uint64_t de, uint64_t dh, uint64_t dc) {
    asm volatile(
      "{\n.reg .b64 dx1, dx2, dx3;\n"
      "add.s64 dx1, %120, 2;\nadd.s64 dx2, %120, 4;\nadd.s64 dx3, %120, 6;\n"
      "wgmma.fence.sync.aligned;\n"
      "wgmma.mma_async.sync.aligned.m64n80k16.f32.bf16.bf16 {%0, %1, %2, %3, %4, %5, %6, %7, %8, %9, %10, %11, %12, %13, %14, %15, %16, %17, %18, %19, %20, %21, %22, %23, %24, %25, %26, %27, %28, %29, %30, %31, %32, %33, %34, %35, %36, %37, %38, %39}, {%116, %117, %118, %119}, %122, 0, 1, 1, 0;\n"
      "wgmma.mma_async.sync.aligned.m64n80k16.f32.bf16.bf16 {%0, %1, %2, %3, %4, %5, %6, %7, %8, %9, %10, %11, %12, %13, %14, %15, %16, %17, %18, %19, %20, %21, %22, %23, %24, %25, %26, %27, %28, %29, %30, %31, %32, %33, %34, %35, %36, %37, %38, %39}, {%96, %97, %98, %99}, %121, 1, 1, 1, 0;\n"
      "wgmma.mma_async.sync.aligned.m64n80k16.f32.bf16.bf16 {%0, %1, %2, %3, %4, %5, %6, %7, %8, %9, %10, %11, %12, %13, %14, %15, %16, %17, %18, %19, %20, %21, %22, %23, %24, %25, %26, %27, %28, %29, %30, %31, %32, %33, %34, %35, %36, %37, %38, %39}, {%80, %81, %82, %83}, %120, 1, 1, 1, 0;\n"
      "wgmma.mma_async.sync.aligned.m64n80k16.f32.bf16.bf16 {%0, %1, %2, %3, %4, %5, %6, %7, %8, %9, %10, %11, %12, %13, %14, %15, %16, %17, %18, %19, %20, %21, %22, %23, %24, %25, %26, %27, %28, %29, %30, %31, %32, %33, %34, %35, %36, %37, %38, %39}, {%84, %85, %86, %87}, dx1, 1, 1, 1, 0;\n"
      "wgmma.mma_async.sync.aligned.m64n80k16.f32.bf16.bf16 {%0, %1, %2, %3, %4, %5, %6, %7, %8, %9, %10, %11, %12, %13, %14, %15, %16, %17, %18, %19, %20, %21, %22, %23, %24, %25, %26, %27, %28, %29, %30, %31, %32, %33, %34, %35, %36, %37, %38, %39}, {%88, %89, %90, %91}, dx2, 1, 1, 1, 0;\n"
      "wgmma.mma_async.sync.aligned.m64n80k16.f32.bf16.bf16 {%0, %1, %2, %3, %4, %5, %6, %7, %8, %9, %10, %11, %12, %13, %14, %15, %16, %17, %18, %19, %20, %21, %22, %23, %24, %25, %26, %27, %28, %29, %30, %31, %32, %33, %34, %35, %36, %37, %38, %39}, {%92, %93, %94, %95}, dx3, 1, 1, 1, 0;\n"
      "wgmma.commit_group.sync.aligned;\n"
      "wgmma.mma_async.sync.aligned.m64n80k16.f32.bf16.bf16 {%40, %41, %42, %43, %44, %45, %46, %47, %48, %49, %50, %51, %52, %53, %54, %55, %56, %57, %58, %59, %60, %61, %62, %63, %64, %65, %66, %67, %68, %69, %70, %71, %72, %73, %74, %75, %76, %77, %78, %79}, {%100, %101, %102, %103}, %120, 0, 1, 1, 0;\n"
      "wgmma.mma_async.sync.aligned.m64n80k16.f32.bf16.bf16 {%40, %41, %42, %43, %44, %45, %46, %47, %48, %49, %50, %51, %52, %53, %54, %55, %56, %57, %58, %59, %60, %61, %62, %63, %64, %65, %66, %67, %68, %69, %70, %71, %72, %73, %74, %75, %76, %77, %78, %79}, {%104, %105, %106, %107}, dx1, 1, 1, 1, 0;\n"
      "wgmma.mma_async.sync.aligned.m64n80k16.f32.bf16.bf16 {%40, %41, %42, %43, %44, %45, %46, %47, %48, %49, %50, %51, %52, %53, %54, %55, %56, %57, %58, %59, %60, %61, %62, %63, %64, %65, %66, %67, %68, %69, %70, %71, %72, %73, %74, %75, %76, %77, %78, %79}, {%108, %109, %110, %111}, dx2, 1, 1, 1, 0;\n"
      "wgmma.mma_async.sync.aligned.m64n80k16.f32.bf16.bf16 {%40, %41, %42, %43, %44, %45, %46, %47, %48, %49, %50, %51, %52, %53, %54, %55, %56, %57, %58, %59, %60, %61, %62, %63, %64, %65, %66, %67, %68, %69, %70, %71, %72, %73, %74, %75, %76, %77, %78, %79}, {%112, %113, %114, %115}, dx3, 1, 1, 1, 0;\n"
      "wgmma.commit_group.sync.aligned;\n}\n"
      : "=f"(g[0]), "=f"(g[1]), "=f"(g[2]), "=f"(g[3]), "=f"(g[4]), "=f"(g[5]), "=f"(g[6]), "=f"(g[7]), "=f"(g[8]), "=f"(g[9]), "=f"(g[10]), "=f"(g[11]), "=f"(g[12]), "=f"(g[13]), "=f"(g[14]), "=f"(g[15]), "=f"(g[16]), "=f"(g[17]), "=f"(g[18]), "=f"(g[19]), "=f"(g[20]), "=f"(g[21]), "=f"(g[22]), "=f"(g[23]), "=f"(g[24]), "=f"(g[25]), "=f"(g[26]), "=f"(g[27]), "=f"(g[28]), "=f"(g[29]), "=f"(g[30]), "=f"(g[31]), "=f"(g[32]), "=f"(g[33]), "=f"(g[34]), "=f"(g[35]), "=f"(g[36]), "=f"(g[37]), "=f"(g[38]), "=f"(g[39]),
        "=f"(h[0]), "=f"(h[1]), "=f"(h[2]), "=f"(h[3]), "=f"(h[4]), "=f"(h[5]), "=f"(h[6]), "=f"(h[7]), "=f"(h[8]), "=f"(h[9]), "=f"(h[10]), "=f"(h[11]), "=f"(h[12]), "=f"(h[13]), "=f"(h[14]), "=f"(h[15]), "=f"(h[16]), "=f"(h[17]), "=f"(h[18]), "=f"(h[19]), "=f"(h[20]), "=f"(h[21]), "=f"(h[22]), "=f"(h[23]), "=f"(h[24]), "=f"(h[25]), "=f"(h[26]), "=f"(h[27]), "=f"(h[28]), "=f"(h[29]), "=f"(h[30]), "=f"(h[31]), "=f"(h[32]), "=f"(h[33]), "=f"(h[34]), "=f"(h[35]), "=f"(h[36]), "=f"(h[37]), "=f"(h[38]), "=f"(h[39])
      : "r"(w[0]), "r"(w[1]), "r"(w[2]), "r"(w[3]), "r"(w[4]), "r"(w[5]), "r"(w[6]), "r"(w[7]), "r"(w[8]), "r"(w[9]), "r"(w[10]), "r"(w[11]), "r"(w[12]), "r"(w[13]), "r"(w[14]), "r"(w[15]), "r"(w[16]), "r"(w[17]), "r"(w[18]), "r"(w[19]), "r"(w[20]), "r"(w[21]), "r"(w[22]), "r"(w[23]), "r"(w[24]), "r"(w[25]), "r"(w[26]), "r"(w[27]), "r"(w[28]), "r"(w[29]), "r"(w[30]), "r"(w[31]), "r"(w[32]), "r"(w[33]), "r"(w[34]), "r"(w[35]), "r"(w[36]), "r"(w[37]), "r"(w[38]), "r"(w[39]), "l"(dx), "l"(de), "l"(dh)
      : "memory");
  }
  static __device__ __forceinline__ void wait_g(float* g) {
    asm volatile("wgmma.wait_group.sync.aligned 1;\n"
      : "+f"(g[0]), "+f"(g[1]), "+f"(g[2]), "+f"(g[3]), "+f"(g[4]), "+f"(g[5]), "+f"(g[6]), "+f"(g[7]), "+f"(g[8]), "+f"(g[9]), "+f"(g[10]), "+f"(g[11]), "+f"(g[12]), "+f"(g[13]), "+f"(g[14]), "+f"(g[15]), "+f"(g[16]), "+f"(g[17]), "+f"(g[18]), "+f"(g[19]), "+f"(g[20]), "+f"(g[21]), "+f"(g[22]), "+f"(g[23]), "+f"(g[24]), "+f"(g[25]), "+f"(g[26]), "+f"(g[27]), "+f"(g[28]), "+f"(g[29]), "+f"(g[30]), "+f"(g[31]), "+f"(g[32]), "+f"(g[33]), "+f"(g[34]), "+f"(g[35]), "+f"(g[36]), "+f"(g[37]), "+f"(g[38]), "+f"(g[39])
      :: "memory");
  }
  static __device__ __forceinline__ void wait_h(float* h) {
    asm volatile("wgmma.wait_group.sync.aligned 0;\n"
      : "+f"(h[0]), "+f"(h[1]), "+f"(h[2]), "+f"(h[3]), "+f"(h[4]), "+f"(h[5]), "+f"(h[6]), "+f"(h[7]), "+f"(h[8]), "+f"(h[9]), "+f"(h[10]), "+f"(h[11]), "+f"(h[12]), "+f"(h[13]), "+f"(h[14]), "+f"(h[15]), "+f"(h[16]), "+f"(h[17]), "+f"(h[18]), "+f"(h[19]), "+f"(h[20]), "+f"(h[21]), "+f"(h[22]), "+f"(h[23]), "+f"(h[24]), "+f"(h[25]), "+f"(h[26]), "+f"(h[27]), "+f"(h[28]), "+f"(h[29]), "+f"(h[30]), "+f"(h[31]), "+f"(h[32]), "+f"(h[33]), "+f"(h[34]), "+f"(h[35]), "+f"(h[36]), "+f"(h[37]), "+f"(h[38]), "+f"(h[39])
      :: "memory");
  }
};
template<> struct TileMMA<11> {
  static __device__ __forceinline__ void issue(float* g, float* h, const uint32_t* w, uint64_t dx, uint64_t de, uint64_t dh, uint64_t dc) {
    asm volatile(
      "{\n.reg .b64 dx1, dx2, dx3;\n"
      "add.s64 dx1, %124, 2;\nadd.s64 dx2, %124, 4;\nadd.s64 dx3, %124, 6;\n"
      "wgmma.fence.sync.aligned;\n"
      "wgmma.mma_async.sync.aligned.m64n88k16.f32.bf16.bf16 {%0, %1, %2, %3, %4, %5, %6, %7, %8, %9, %10, %11, %12, %13, %14, %15, %16, %17, %18, %19, %20, %21, %22, %23, %24, %25, %26, %27, %28, %29, %30, %31, %32, %33, %34, %35, %36, %37, %38, %39, %40, %41, %42, %43}, {%120, %121, %122, %123}, %126, 0, 1, 1, 0;\n"
      "wgmma.mma_async.sync.aligned.m64n88k16.f32.bf16.bf16 {%0, %1, %2, %3, %4, %5, %6, %7, %8, %9, %10, %11, %12, %13, %14, %15, %16, %17, %18, %19, %20, %21, %22, %23, %24, %25, %26, %27, %28, %29, %30, %31, %32, %33, %34, %35, %36, %37, %38, %39, %40, %41, %42, %43}, %127, %125, 1, 1, 1, 0, 0;\n"
      "wgmma.mma_async.sync.aligned.m64n88k16.f32.bf16.bf16 {%0, %1, %2, %3, %4, %5, %6, %7, %8, %9, %10, %11, %12, %13, %14, %15, %16, %17, %18, %19, %20, %21, %22, %23, %24, %25, %26, %27, %28, %29, %30, %31, %32, %33, %34, %35, %36, %37, %38, %39, %40, %41, %42, %43}, {%88, %89, %90, %91}, %124, 1, 1, 1, 0;\n"
      "wgmma.mma_async.sync.aligned.m64n88k16.f32.bf16.bf16 {%0, %1, %2, %3, %4, %5, %6, %7, %8, %9, %10, %11, %12, %13, %14, %15, %16, %17, %18, %19, %20, %21, %22, %23, %24, %25, %26, %27, %28, %29, %30, %31, %32, %33, %34, %35, %36, %37, %38, %39, %40, %41, %42, %43}, {%92, %93, %94, %95}, dx1, 1, 1, 1, 0;\n"
      "wgmma.mma_async.sync.aligned.m64n88k16.f32.bf16.bf16 {%0, %1, %2, %3, %4, %5, %6, %7, %8, %9, %10, %11, %12, %13, %14, %15, %16, %17, %18, %19, %20, %21, %22, %23, %24, %25, %26, %27, %28, %29, %30, %31, %32, %33, %34, %35, %36, %37, %38, %39, %40, %41, %42, %43}, {%96, %97, %98, %99}, dx2, 1, 1, 1, 0;\n"
      "wgmma.mma_async.sync.aligned.m64n88k16.f32.bf16.bf16 {%0, %1, %2, %3, %4, %5, %6, %7, %8, %9, %10, %11, %12, %13, %14, %15, %16, %17, %18, %19, %20, %21, %22, %23, %24, %25, %26, %27, %28, %29, %30, %31, %32, %33, %34, %35, %36, %37, %38, %39, %40, %41, %42, %43}, {%100, %101, %102, %103}, dx3, 1, 1, 1, 0;\n"
      "wgmma.commit_group.sync.aligned;\n"
      "wgmma.mma_async.sync.aligned.m64n88k16.f32.bf16.bf16 {%44, %45, %46, %47, %48, %49, %50, %51, %52, %53, %54, %55, %56, %57, %58, %59, %60, %61, %62, %63, %64, %65, %66, %67, %68, %69, %70, %71, %72, %73, %74, %75, %76, %77, %78, %79, %80, %81, %82, %83, %84, %85, %86, %87}, {%104, %105, %106, %107}, %124, 0, 1, 1, 0;\n"
      "wgmma.mma_async.sync.aligned.m64n88k16.f32.bf16.bf16 {%44, %45, %46, %47, %48, %49, %50, %51, %52, %53, %54, %55, %56, %57, %58, %59, %60, %61, %62, %63, %64, %65, %66, %67, %68, %69, %70, %71, %72, %73, %74, %75, %76, %77, %78, %79, %80, %81, %82, %83, %84, %85, %86, %87}, {%108, %109, %110, %111}, dx1, 1, 1, 1, 0;\n"
      "wgmma.mma_async.sync.aligned.m64n88k16.f32.bf16.bf16 {%44, %45, %46, %47, %48, %49, %50, %51, %52, %53, %54, %55, %56, %57, %58, %59, %60, %61, %62, %63, %64, %65, %66, %67, %68, %69, %70, %71, %72, %73, %74, %75, %76, %77, %78, %79, %80, %81, %82, %83, %84, %85, %86, %87}, {%112, %113, %114, %115}, dx2, 1, 1, 1, 0;\n"
      "wgmma.mma_async.sync.aligned.m64n88k16.f32.bf16.bf16 {%44, %45, %46, %47, %48, %49, %50, %51, %52, %53, %54, %55, %56, %57, %58, %59, %60, %61, %62, %63, %64, %65, %66, %67, %68, %69, %70, %71, %72, %73, %74, %75, %76, %77, %78, %79, %80, %81, %82, %83, %84, %85, %86, %87}, {%116, %117, %118, %119}, dx3, 1, 1, 1, 0;\n"
      "wgmma.commit_group.sync.aligned;\n}\n"
      : "=f"(g[0]), "=f"(g[1]), "=f"(g[2]), "=f"(g[3]), "=f"(g[4]), "=f"(g[5]), "=f"(g[6]), "=f"(g[7]), "=f"(g[8]), "=f"(g[9]), "=f"(g[10]), "=f"(g[11]), "=f"(g[12]), "=f"(g[13]), "=f"(g[14]), "=f"(g[15]), "=f"(g[16]), "=f"(g[17]), "=f"(g[18]), "=f"(g[19]), "=f"(g[20]), "=f"(g[21]), "=f"(g[22]), "=f"(g[23]), "=f"(g[24]), "=f"(g[25]), "=f"(g[26]), "=f"(g[27]), "=f"(g[28]), "=f"(g[29]), "=f"(g[30]), "=f"(g[31]), "=f"(g[32]), "=f"(g[33]), "=f"(g[34]), "=f"(g[35]), "=f"(g[36]), "=f"(g[37]), "=f"(g[38]), "=f"(g[39]), "=f"(g[40]), "=f"(g[41]), "=f"(g[42]), "=f"(g[43]),
        "=f"(h[0]), "=f"(h[1]), "=f"(h[2]), "=f"(h[3]), "=f"(h[4]), "=f"(h[5]), "=f"(h[6]), "=f"(h[7]), "=f"(h[8]), "=f"(h[9]), "=f"(h[10]), "=f"(h[11]), "=f"(h[12]), "=f"(h[13]), "=f"(h[14]), "=f"(h[15]), "=f"(h[16]), "=f"(h[17]), "=f"(h[18]), "=f"(h[19]), "=f"(h[20]), "=f"(h[21]), "=f"(h[22]), "=f"(h[23]), "=f"(h[24]), "=f"(h[25]), "=f"(h[26]), "=f"(h[27]), "=f"(h[28]), "=f"(h[29]), "=f"(h[30]), "=f"(h[31]), "=f"(h[32]), "=f"(h[33]), "=f"(h[34]), "=f"(h[35]), "=f"(h[36]), "=f"(h[37]), "=f"(h[38]), "=f"(h[39]), "=f"(h[40]), "=f"(h[41]), "=f"(h[42]), "=f"(h[43])
      : "r"(w[0]), "r"(w[1]), "r"(w[2]), "r"(w[3]), "r"(w[4]), "r"(w[5]), "r"(w[6]), "r"(w[7]), "r"(w[8]), "r"(w[9]), "r"(w[10]), "r"(w[11]), "r"(w[12]), "r"(w[13]), "r"(w[14]), "r"(w[15]), "r"(w[20]), "r"(w[21]), "r"(w[22]), "r"(w[23]), "r"(w[24]), "r"(w[25]), "r"(w[26]), "r"(w[27]), "r"(w[28]), "r"(w[29]), "r"(w[30]), "r"(w[31]), "r"(w[32]), "r"(w[33]), "r"(w[34]), "r"(w[35]), "r"(w[36]), "r"(w[37]), "r"(w[38]), "r"(w[39]), "l"(dx), "l"(de), "l"(dh), "l"(dc)
      : "memory");
  }
  static __device__ __forceinline__ void wait_g(float* g) {
    asm volatile("wgmma.wait_group.sync.aligned 1;\n"
      : "+f"(g[0]), "+f"(g[1]), "+f"(g[2]), "+f"(g[3]), "+f"(g[4]), "+f"(g[5]), "+f"(g[6]), "+f"(g[7]), "+f"(g[8]), "+f"(g[9]), "+f"(g[10]), "+f"(g[11]), "+f"(g[12]), "+f"(g[13]), "+f"(g[14]), "+f"(g[15]), "+f"(g[16]), "+f"(g[17]), "+f"(g[18]), "+f"(g[19]), "+f"(g[20]), "+f"(g[21]), "+f"(g[22]), "+f"(g[23]), "+f"(g[24]), "+f"(g[25]), "+f"(g[26]), "+f"(g[27]), "+f"(g[28]), "+f"(g[29]), "+f"(g[30]), "+f"(g[31]), "+f"(g[32]), "+f"(g[33]), "+f"(g[34]), "+f"(g[35]), "+f"(g[36]), "+f"(g[37]), "+f"(g[38]), "+f"(g[39]), "+f"(g[40]), "+f"(g[41]), "+f"(g[42]), "+f"(g[43])
      :: "memory");
  }
  static __device__ __forceinline__ void wait_h(float* h) {
    asm volatile("wgmma.wait_group.sync.aligned 0;\n"
      : "+f"(h[0]), "+f"(h[1]), "+f"(h[2]), "+f"(h[3]), "+f"(h[4]), "+f"(h[5]), "+f"(h[6]), "+f"(h[7]), "+f"(h[8]), "+f"(h[9]), "+f"(h[10]), "+f"(h[11]), "+f"(h[12]), "+f"(h[13]), "+f"(h[14]), "+f"(h[15]), "+f"(h[16]), "+f"(h[17]), "+f"(h[18]), "+f"(h[19]), "+f"(h[20]), "+f"(h[21]), "+f"(h[22]), "+f"(h[23]), "+f"(h[24]), "+f"(h[25]), "+f"(h[26]), "+f"(h[27]), "+f"(h[28]), "+f"(h[29]), "+f"(h[30]), "+f"(h[31]), "+f"(h[32]), "+f"(h[33]), "+f"(h[34]), "+f"(h[35]), "+f"(h[36]), "+f"(h[37]), "+f"(h[38]), "+f"(h[39]), "+f"(h[40]), "+f"(h[41]), "+f"(h[42]), "+f"(h[43])
      :: "memory");
  }
};
__device__ __forceinline__ void node_mma2(float* u, float* a, const uint32_t* w, uint64_t dx) {
    asm volatile(
      "{\n.reg .b64 dx1, dx2, dx3, dy0, dy1, dy2, dy3;\n"
      "add.s64 dx1, %80, 2;\nadd.s64 dx2, %80, 4;\nadd.s64 dx3, %80, 6;\n"
      "add.s64 dy0, %80, 512;\nadd.s64 dy1, %80, 514;\nadd.s64 dy2, %80, 516;\nadd.s64 dy3, %80, 518;\n"
      "wgmma.fence.sync.aligned;\n"
      "wgmma.mma_async.sync.aligned.m64n64k16.f32.bf16.bf16 {%0, %1, %2, %3, %4, %5, %6, %7, %8, %9, %10, %11, %12, %13, %14, %15, %16, %17, %18, %19, %20, %21, %22, %23, %24, %25, %26, %27, %28, %29, %30, %31}, {%64, %65, %66, %67}, %80, 0, 1, 1, 0;\n"
      "wgmma.mma_async.sync.aligned.m64n64k16.f32.bf16.bf16 {%0, %1, %2, %3, %4, %5, %6, %7, %8, %9, %10, %11, %12, %13, %14, %15, %16, %17, %18, %19, %20, %21, %22, %23, %24, %25, %26, %27, %28, %29, %30, %31}, {%68, %69, %70, %71}, dx1, 1, 1, 1, 0;\n"
      "wgmma.mma_async.sync.aligned.m64n64k16.f32.bf16.bf16 {%0, %1, %2, %3, %4, %5, %6, %7, %8, %9, %10, %11, %12, %13, %14, %15, %16, %17, %18, %19, %20, %21, %22, %23, %24, %25, %26, %27, %28, %29, %30, %31}, {%72, %73, %74, %75}, dx2, 1, 1, 1, 0;\n"
      "wgmma.mma_async.sync.aligned.m64n64k16.f32.bf16.bf16 {%0, %1, %2, %3, %4, %5, %6, %7, %8, %9, %10, %11, %12, %13, %14, %15, %16, %17, %18, %19, %20, %21, %22, %23, %24, %25, %26, %27, %28, %29, %30, %31}, {%76, %77, %78, %79}, dx3, 1, 1, 1, 0;\n"
      "wgmma.commit_group.sync.aligned;\n"
      "wgmma.mma_async.sync.aligned.m64n64k16.f32.bf16.bf16 {%32, %33, %34, %35, %36, %37, %38, %39, %40, %41, %42, %43, %44, %45, %46, %47, %48, %49, %50, %51, %52, %53, %54, %55, %56, %57, %58, %59, %60, %61, %62, %63}, {%64, %65, %66, %67}, dy0, 0, 1, 1, 0;\n"
      "wgmma.mma_async.sync.aligned.m64n64k16.f32.bf16.bf16 {%32, %33, %34, %35, %36, %37, %38, %39, %40, %41, %42, %43, %44, %45, %46, %47, %48, %49, %50, %51, %52, %53, %54, %55, %56, %57, %58, %59, %60, %61, %62, %63}, {%68, %69, %70, %71}, dy1, 1, 1, 1, 0;\n"
      "wgmma.mma_async.sync.aligned.m64n64k16.f32.bf16.bf16 {%32, %33, %34, %35, %36, %37, %38, %39, %40, %41, %42, %43, %44, %45, %46, %47, %48, %49, %50, %51, %52, %53, %54, %55, %56, %57, %58, %59, %60, %61, %62, %63}, {%72, %73, %74, %75}, dy2, 1, 1, 1, 0;\n"
      "wgmma.mma_async.sync.aligned.m64n64k16.f32.bf16.bf16 {%32, %33, %34, %35, %36, %37, %38, %39, %40, %41, %42, %43, %44, %45, %46, %47, %48, %49, %50, %51, %52, %53, %54, %55, %56, %57, %58, %59, %60, %61, %62, %63}, {%76, %77, %78, %79}, dy3, 1, 1, 1, 0;\n"
      "wgmma.commit_group.sync.aligned;\n}\n"
      : "=f"(u[0]), "=f"(u[1]), "=f"(u[2]), "=f"(u[3]), "=f"(u[4]), "=f"(u[5]), "=f"(u[6]), "=f"(u[7]), "=f"(u[8]), "=f"(u[9]), "=f"(u[10]), "=f"(u[11]), "=f"(u[12]), "=f"(u[13]), "=f"(u[14]), "=f"(u[15]), "=f"(u[16]), "=f"(u[17]), "=f"(u[18]), "=f"(u[19]), "=f"(u[20]), "=f"(u[21]), "=f"(u[22]), "=f"(u[23]), "=f"(u[24]), "=f"(u[25]), "=f"(u[26]), "=f"(u[27]), "=f"(u[28]), "=f"(u[29]), "=f"(u[30]), "=f"(u[31]),
        "=f"(a[0]), "=f"(a[1]), "=f"(a[2]), "=f"(a[3]), "=f"(a[4]), "=f"(a[5]), "=f"(a[6]), "=f"(a[7]), "=f"(a[8]), "=f"(a[9]), "=f"(a[10]), "=f"(a[11]), "=f"(a[12]), "=f"(a[13]), "=f"(a[14]), "=f"(a[15]), "=f"(a[16]), "=f"(a[17]), "=f"(a[18]), "=f"(a[19]), "=f"(a[20]), "=f"(a[21]), "=f"(a[22]), "=f"(a[23]), "=f"(a[24]), "=f"(a[25]), "=f"(a[26]), "=f"(a[27]), "=f"(a[28]), "=f"(a[29]), "=f"(a[30]), "=f"(a[31])
      : "r"(w[0]), "r"(w[1]), "r"(w[2]), "r"(w[3]), "r"(w[4]), "r"(w[5]), "r"(w[6]), "r"(w[7]), "r"(w[8]), "r"(w[9]), "r"(w[10]), "r"(w[11]), "r"(w[12]), "r"(w[13]), "r"(w[14]), "r"(w[15]), "l"(dx)
      : "memory");
}

__device__ __forceinline__ uint32_t smem_u32(const void* p) { return (uint32_t)__cvta_generic_to_shared(p); }
__device__ __forceinline__ float ex2f(float x) { float y; asm("ex2.approx.ftz.f32 %0, %1;" : "=f"(y) : "f"(x)); return y; }
__device__ __forceinline__ float rcpf(float x) { float y; asm("rcp.approx.ftz.f32 %0, %1;" : "=f"(y) : "f"(x)); return y; }
__device__ __forceinline__ uint32_t pack_bf16(float lo, float hi) {
    uint32_t r; asm("cvt.rn.bf16x2.f32 %0, %1, %2;" : "=r"(r) : "f"(hi), "f"(lo)); return r;
}
__device__ __forceinline__ float bf_lo(uint32_t v) { return __uint_as_float(v << 16); }
__device__ __forceinline__ float bf_hi(uint32_t v) { return __uint_as_float(v & 0xFFFF0000u); }
template<int STRIDE>
__device__ __forceinline__ void cp16i(uint32_t dst, const char* base, uint32_t idx) {
    asm volatile("{\n.reg .b64 a;\nmad.wide.u32 a, %2, %3, %1;\ncp.async.cg.shared.global [%0], [a], 16;\n}\n" :: "r"(dst), "l"(base), "r"(idx), "n"(STRIDE) : "memory");
}
__device__ __forceinline__ void cp16e(uint32_t dst, const char* base, uint32_t idx, uint64_t pol) {
    asm volatile("{\n.reg .b64 a;\nmad.wide.u32 a, %2, 32, %1;\ncp.async.cg.shared.global.L2::cache_hint [%0], [a], 16, %3;\n}\n" :: "r"(dst), "l"(base), "r"(idx), "l"(pol) : "memory");
}
template<int STRIDE>
__device__ __forceinline__ void cp16z(uint32_t dst, const char* base, uint32_t idx, int k, int n, uint64_t pol) {
    if (STRIDE == 32)
        asm volatile("{\n.reg .b64 a;\n.reg .pred p;\nsetp.ge.s32 p, %3, %4;\nmad.wide.u32 a, %2, 32, %1;\ncp.async.cg.shared.global.L2::cache_hint [%0], [a], 16, p, %5;\n}\n"
                     :: "r"(dst), "l"(base), "r"(idx), "r"(k), "r"(n), "l"(pol) : "memory");
    else
        asm volatile("{\n.reg .b64 a;\n.reg .pred p;\nsetp.ge.s32 p, %3, %4;\nmad.wide.u32 a, %2, 128, %1;\ncp.async.cg.shared.global [%0], [a], 16, p;\n}\n"
                     :: "r"(dst), "l"(base), "r"(idx), "r"(k), "r"(n) : "memory");
}
template<int HI, bool Z>
__device__ __forceinline__ void cpx(uint32_t hi, uint32_t dst, uint32_t p, uint32_t lo, int k, int n) {
    if (Z) asm volatile("{\n.reg .b32 l;\n.reg .b64 a;\n.reg .pred q;\nsetp.ge.s32 q, %5, %6;\ndp2a.lo.u32.u32 l, %1, %2, %3;\nmov.b64 a, {l, %0};\ncp.async.cg.shared.global [%4], [a], 16, q;\n}\n"
                        :: "r"(hi), "r"(p), "r"(HI ? 0x8000u : 0x80u), "r"(lo), "r"(dst), "r"(k), "r"(n) : "memory");
    else asm volatile("{\n.reg .b32 l;\n.reg .b64 a;\ndp2a.lo.u32.u32 l, %1, %2, %3;\nmov.b64 a, {l, %0};\ncp.async.cg.shared.global [%4], [a], 16;\n}\n"
                      :: "r"(hi), "r"(p), "r"(HI ? 0x8000u : 0x80u), "r"(lo), "r"(dst) : "memory");
}
template<bool Z>
__device__ __forceinline__ void cpe(uint32_t hi, uint32_t dst, uint32_t idx, uint32_t lo, int k, int n, uint64_t pol) {
    if (Z) asm volatile("{\n.reg .b32 l;\n.reg .b64 a;\n.reg .pred q;\nsetp.ge.s32 q, %5, %6;\nmad.lo.u32 l, %1, 32, %2;\nmov.b64 a, {l, %0};\ncp.async.cg.shared.global.L2::cache_hint [%3], [a], 16, q, %4;\n}\n"
                        :: "r"(hi), "r"(idx), "r"(lo), "r"(dst), "l"(pol), "r"(k), "r"(n) : "memory");
    else asm volatile("{\n.reg .b32 l;\n.reg .b64 a;\nmad.lo.u32 l, %1, 32, %2;\nmov.b64 a, {l, %0};\ncp.async.cg.shared.global.L2::cache_hint [%3], [a], 16, %4;\n}\n"
                      :: "r"(hi), "r"(idx), "r"(lo), "r"(dst), "l"(pol) : "memory");
}
template<int N> __device__ __forceinline__ void cp_wait() { asm volatile("cp.async.wait_group %0;" :: "n"(N) : "memory"); }
__device__ __forceinline__ void mbar_init(uint32_t bar, int cnt) { asm volatile("mbarrier.init.shared.b64 [%0], %1;" :: "r"(bar), "r"(cnt) : "memory"); }
__device__ __forceinline__ void mbar_arrive(uint32_t bar) { asm volatile("mbarrier.arrive.shared.b64 _, [%0];" :: "r"(bar) : "memory"); }
__device__ __forceinline__ void mbar_expect(uint32_t bar, uint32_t bytes) { asm volatile("mbarrier.arrive.expect_tx.shared.b64 _, [%0], %1;" :: "r"(bar), "r"(bytes) : "memory"); }
__device__ __forceinline__ void mbar_cp_arrive(uint32_t bar) { asm volatile("cp.async.mbarrier.arrive.noinc.shared.b64 [%0];" :: "r"(bar) : "memory"); }
__device__ __forceinline__ void mbar_wait(uint32_t bar, uint32_t parity) {
    asm volatile("{\n.reg .pred p;\n.reg .u32 n;\nmbarrier.try_wait.parity.shared.b64 p, [%0], %1;\n@p bra DONE_%=;\nmov.u32 n, 0;\n"
                 "WAIT_%=:\nmbarrier.try_wait.parity.shared.b64 p, [%0], %1, 0x100000;\n@p bra DONE_%=;\n"
                 "add.u32 n, n, 1;\nsetp.lt.u32 p, n, 0x400000;\n@p bra WAIT_%=;\ntrap;\nDONE_%=:\n}\n"
                 :: "r"(bar), "r"(parity) : "memory");
}
__device__ __forceinline__ void mbar_wait_c(uint32_t bar, uint32_t parity) {
    asm volatile("{\n.reg .pred p;\nWAIT_%=:\nmbarrier.try_wait.parity.shared.b64 p, [%0], %1;\n@p bra DONE_%=;\nbra WAIT_%=;\nDONE_%=:\n}\n"
                 :: "r"(bar), "r"(parity) : "memory");
}
__device__ __forceinline__ void mbar_wait_h(uint32_t bar, uint32_t parity) {
    asm volatile("{\n.reg .pred p;\nWAIT_%=:\nmbarrier.try_wait.parity.shared.b64 p, [%0], %1, 0x100000;\n@p bra DONE_%=;\nbra WAIT_%=;\nDONE_%=:\n}\n"
                 :: "r"(bar), "r"(parity) : "memory");
}
__device__ __forceinline__ uint32_t lds32(uint32_t a) { uint32_t v; asm volatile("ld.shared.u32 %0, [%1];" : "=r"(v) : "r"(a) : "memory"); return v; }
__device__ __forceinline__ void sts32(uint32_t a, uint32_t v) { asm volatile("st.shared.u32 [%0], %1;" :: "r"(a), "r"(v) : "memory"); }
__device__ __forceinline__ uint2 lds64(uint32_t a) { uint2 v; asm volatile("ld.shared.v2.u32 {%0,%1}, [%2];" : "=r"(v.x), "=r"(v.y) : "r"(a) : "memory"); return v; }
__device__ __forceinline__ uint4 lds128(uint32_t a) { uint4 v; asm volatile("ld.shared.v4.u32 {%0,%1,%2,%3}, [%4];" : "=r"(v.x), "=r"(v.y), "=r"(v.z), "=r"(v.w) : "r"(a) : "memory"); return v; }
__device__ __forceinline__ void sts128(uint32_t a, uint4 v) { asm volatile("st.shared.v4.u32 [%0], {%1,%2,%3,%4};" :: "r"(a), "r"(v.x), "r"(v.y), "r"(v.z), "r"(v.w) : "memory"); }
__device__ __forceinline__ void ldsm4t(uint32_t* v, uint32_t a) {
    asm volatile("ldmatrix.sync.aligned.m8n8.x4.trans.shared.b16 {%0,%1,%2,%3}, [%4];" : "=r"(v[0]), "=r"(v[1]), "=r"(v[2]), "=r"(v[3]) : "r"(a) : "memory");
}
__device__ __forceinline__ void stsm4t(uint32_t a, const uint32_t* v) {
    asm volatile("stmatrix.sync.aligned.m8n8.x4.trans.shared.b16 [%0], {%1,%2,%3,%4};" :: "r"(a), "r"(v[0]), "r"(v[1]), "r"(v[2]), "r"(v[3]) : "memory");
}
__device__ __forceinline__ int atoms_inc(uint32_t a) { int v; asm volatile("atom.shared.add.u32 %0, [%1], 1;" : "=r"(v) : "r"(a) : "memory"); return v; }
__device__ __forceinline__ bool elect_one() {
    uint32_t el;
    asm volatile("{\n.reg .pred p;\nelect.sync _|p, 0xffffffff;\nselp.u32 %0, 1, 0, p;\n}" : "=r"(el));
    return el != 0;
}
__device__ __forceinline__ float tanhf_a(float x) { float y; asm("tanh.approx.f32 %0, %1;" : "=f"(y) : "f"(x)); return y; }
__device__ __forceinline__ const char* as_pair(const void* p, uint32_t scratch) {
    const char* r;
    asm volatile("st.shared.u64 [%1], %2;\nld.volatile.shared.u64 %0, [%1];" : "=l"(r) : "r"(scratch), "l"(p) : "memory");
    return r;
}
__device__ __forceinline__ void ld_unit(uint4& v, const char* p, bool ok) {
    asm volatile("{\n.reg .pred q;\nsetp.ne.u32 q, %5, 0;\n@q ld.relaxed.gpu.global.v4.u32 {%0,%1,%2,%3}, [%4];\n}"
                 : "+r"(v.x), "+r"(v.y), "+r"(v.z), "+r"(v.w) : "l"(p), "r"((uint32_t)ok) : "memory");
}
__device__ __forceinline__ void ld_unit(uint2& v, const char* p, bool ok) {
    asm volatile("{\n.reg .pred q;\nsetp.ne.u32 q, %3, 0;\n@q ld.relaxed.gpu.global.v2.u32 {%0,%1}, [%2];\n}"
                 : "+r"(v.x), "+r"(v.y) : "l"(p), "r"((uint32_t)ok) : "memory");
}
__device__ __forceinline__ void bulk_ld(uint32_t dst, const void* src, int bytes, uint32_t bar) {
    mbar_expect(bar, bytes);
    if (bytes > 0) asm volatile("cp.async.bulk.shared::cluster.global.mbarrier::complete_tx::bytes [%0], [%1], %2, [%3];" :: "r"(dst), "l"(src), "r"(bytes), "r"(bar) : "memory");
}
__device__ __forceinline__ void bulk_st(void* dst, uint32_t src, int bytes) {
    asm volatile("cp.async.bulk.global.shared::cta.bulk_group [%0], [%1], %2;" :: "l"(dst), "r"(src), "r"(bytes) : "memory");
}

__device__ __forceinline__ void finish(uint4& a, const uint4& xu, const uint4& xv) {
    asm("{\n.reg .b32 z;\nfma.rn.relu.bf16x2 z, %0, %3, %1;\nadd.rn.bf16x2 %0, z, %2;\n}" : "+r"(a.x) : "r"(xu.x), "r"(xv.x), "r"(0x3F803F80u));
    asm("{\n.reg .b32 z;\nfma.rn.relu.bf16x2 z, %0, %3, %1;\nadd.rn.bf16x2 %0, z, %2;\n}" : "+r"(a.y) : "r"(xu.y), "r"(xv.y), "r"(0x3F803F80u));
    asm("{\n.reg .b32 z;\nfma.rn.relu.bf16x2 z, %0, %3, %1;\nadd.rn.bf16x2 %0, z, %2;\n}" : "+r"(a.z) : "r"(xu.z), "r"(xv.z), "r"(0x3F803F80u));
    asm("{\n.reg .b32 z;\nfma.rn.relu.bf16x2 z, %0, %3, %1;\nadd.rn.bf16x2 %0, z, %2;\n}" : "+r"(a.w) : "r"(xu.w), "r"(xv.w), "r"(0x3F803F80u));
}

__device__ __forceinline__ void node_rows(uint32_t p, const float* a) {
    #pragma unroll
    for (int i = 0; i < 4; i++) {
        const float* u = a + 8 * i;
        const uint32_t v[4] = {pack_bf16(u[0], u[1]), pack_bf16(u[2], u[3]), pack_bf16(u[4], u[5]), pack_bf16(u[6], u[7])};
        stsm4t(p + i * 2048, v);
    }
}

constexpr float EPS2 = 2e-6f;
constexpr float TAU = 2.5e-5f;

template<bool HALF>
__device__ __forceinline__ void make_wfrag(uint32_t* f, const uint32_t* v) {
    const uint32_t v0 = v[0], v1 = v[1], v2 = v[2], v3 = v[3];
    f[0] = __byte_perm(v0, v1, 0x5410); f[1] = __byte_perm(v0, v1, 0x7632);
    f[2] = __byte_perm(v2, v3, 0x5410); f[3] = __byte_perm(v2, v3, 0x7632);
    if (HALF) {
        #pragma unroll
        for (int i = 0; i < 4; i++) asm("mul.rn.bf16x2 %0, %0, %1;" : "+r"(f[i]) : "r"(0x3F003F00u));
    }
}

template<int NP>
__device__ __forceinline__ void epi_fast(const float* g, const float* h, float m1, float m2,
                                         float& n0, float& d0, float& n1, float& d1, float& dmin)
{
    constexpr int JC = NP >= 6 ? NP - 1 - 2 : NP >= 4 ? NP - 2 : NP - 1;
    constexpr int JT = NP < 3 ? -1 : JC < NP - 1 ? JC : NP - 2;
    #pragma unroll
    for (int j = 0; j < NP; j++) {
        float t0 = tanhf_a(g[4*j+0]), t1 = tanhf_a(g[4*j+1]), t2 = tanhf_a(g[4*j+2]), t3 = tanhf_a(g[4*j+3]);
        auto add_d = [&]() {
            if (j == 0) { d0 = t0 + (2.f * (JT + 1) + EPS2); d1 = t2 + (2.f * (JT + 1) + EPS2); } else { d0 += t0; d1 += t2; }
            d0 += t1; d1 += t3;
        };
        if (j <= JT) add_d();
        if (j == NP - 1) { t0 = fmaf(t0, m1, m1); t1 = fmaf(t1, m2, m2); t2 = fmaf(t2, m1, m1); t3 = fmaf(t3, m2, m2); }
        else { t0 += 1.f; t1 += 1.f; t2 += 1.f; t3 += 1.f; }
        if (j > JT) add_d();
        if (j == 0) { n0 = t0 * h[0]; n1 = t2 * h[2]; } else { n0 = fmaf(t0, h[4*j], n0); n1 = fmaf(t2, h[4*j+2], n1); }
        n0 = fmaf(t1, h[4*j+1], n0); n1 = fmaf(t3, h[4*j+3], n1);
        if (j == JC) dmin = fminf(d0, d1);
    }
}

__device__ __noinline__ float4 epi_exact(const float4* gh, int np, int dv)
{
    float n0 = 0.f, d0 = EPS2, n1 = 0.f, d1 = EPS2;
    #pragma unroll 2
    for (int j = 0; j < np; j++) {
        const float4 g = gh[j], h = gh[NPMAX + j];
        const float ma = (2 * j < dv) ? 2.f : 0.f, mb = (2 * j + 1 < dv) ? 2.f : 0.f;
        const float e0 = ma * rcpf(1.f + ex2f(-2.f * LOG2E * g.x)), e1 = mb * rcpf(1.f + ex2f(-2.f * LOG2E * g.y));
        const float e2 = ma * rcpf(1.f + ex2f(-2.f * LOG2E * g.z)), e3 = mb * rcpf(1.f + ex2f(-2.f * LOG2E * g.w));
        d0 += e0 + e1; n0 = fmaf(e0, h.x, fmaf(e1, h.y, n0));
        d1 += e2 + e3; n1 = fmaf(e2, h.z, fmaf(e3, h.w, n1));
    }
    return make_float4(n0, d0, n1, d1);
}
template<int NP>
__device__ __forceinline__ void epi_dump(const float* g, const float* h, float4* gh) {
    #pragma unroll
    for (int i = 0; i < NP; i++) {
        gh[i] = make_float4(g[4*i], g[4*i+1], g[4*i+2], g[4*i+3]);
        gh[NPMAX + i] = make_float4(h[4*i], h[4*i+1], h[4*i+2], h[4*i+3]);
    }
}

__device__ __noinline__ void slow_bin(const __nv_bfloat16* x, const __nv_bfloat16* ea, const int* src, const int* dst,
                                      const __nv_bfloat16* wa, const __nv_bfloat16* wb, const __nv_bfloat16* wc,
                                      const __nv_bfloat16* wu, const __nv_bfloat16* wv, __nv_bfloat16* out,
                                      int E, int node0, int nn, int nthr)
{
    const int tid = threadIdx.x, lane = tid & 31;
    for (int i = tid; i < nn * 128; i += nthr) g_slow[(size_t)node0 * 128 + i] = 0.f;
    asm volatile("bar.sync 1, %0;" :: "r"(nthr) : "memory");
    for (int e0 = (tid >> 5) * 32; e0 < E; e0 += nthr) {
        int d = (e0 + lane < E) ? dst[e0 + lane] - node0 : -1;
        unsigned m = __ballot_sync(~0u, d >= 0 && d < nn);
        while (m) {
            int l = __ffs(m) - 1; m &= m - 1;
            int e = e0 + l, n = node0 + __shfl_sync(~0u, d, l), s = src[e];
            float g0 = 0, g1 = 0, h0 = 0, h1 = 0;
            for (int k = 0; k < 64; k++) {
                float xs = __bfloat162float(x[(size_t)s * 64 + k]), xd = __bfloat162float(x[(size_t)n * 64 + k]);
                uint32_t b2 = *(const uint32_t*)(wb + k * 64 + 2 * lane), v2 = *(const uint32_t*)(wv + k * 64 + 2 * lane);
                uint32_t a2 = *(const uint32_t*)(wa + k * 64 + 2 * lane);
                g0 = fmaf(xs, bf_lo(b2), fmaf(xd, bf_lo(a2), g0)); g1 = fmaf(xs, bf_hi(b2), fmaf(xd, bf_hi(a2), g1));
                h0 = fmaf(xs, bf_lo(v2), h0); h1 = fmaf(xs, bf_hi(v2), h1);
            }
            for (int k = 0; k < 16; k++) {
                float ev = __bfloat162float(ea[(size_t)e * 16 + k]);
                uint32_t c2 = *(const uint32_t*)(wc + k * 64 + 2 * lane);
                g0 = fmaf(ev, bf_lo(c2), g0); g1 = fmaf(ev, bf_hi(c2), g1);
            }
            float s0 = rcpf(1.f + ex2f(-LOG2E * g0)), s1 = rcpf(1.f + ex2f(-LOG2E * g1));
            float* acc = g_slow + (size_t)n * 128 + 4 * lane;
            atomicAdd(acc + 0, s0 * h0); atomicAdd(acc + 1, s0);
            atomicAdd(acc + 2, s1 * h1); atomicAdd(acc + 3, s1);
        }
    }
    __threadfence();
    asm volatile("bar.sync 1, %0;" :: "r"(nthr) : "memory");
    for (int i = tid; i < nn * 32; i += nthr) {
        int n = node0 + (i >> 5), cp = i & 31;
        float4 a = __ldcg((const float4*)(g_slow + (size_t)n * 128 + 4 * cp));
        float u0 = 0, u1 = 0;
        for (int k = 0; k < 64; k++) {
            float xd = __bfloat162float(x[(size_t)n * 64 + k]);
            uint32_t w2 = *(const uint32_t*)(wu + k * 64 + 2 * cp);
            u0 = fmaf(xd, bf_lo(w2), u0); u1 = fmaf(xd, bf_hi(w2), u1);
        }
        uint32_t xv = *(const uint32_t*)(x + (size_t)n * 64 + 2 * cp);
        float z0 = u0 + a.x / (a.y + 1e-6f), z1 = u1 + a.z / (a.w + 1e-6f);
        *(uint32_t*)(out + (size_t)n * 64 + 2 * cp) = pack_bf16(bf_lo(xv) + fmaxf(z0, 0.f), bf_hi(xv) + fmaxf(z1, 0.f));
    }
}

__global__ void __launch_bounds__(256) slow_kernel(const __nv_bfloat16* x, const __nv_bfloat16* ea, const int* src, const int* dst,
        const __nv_bfloat16* wa, const __nv_bfloat16* wb, const __nv_bfloat16* wc, const __nv_bfloat16* wu, const __nv_bfloat16* wv,
        __nv_bfloat16* out, int N, int E, int npb)
{
    int node0 = blockIdx.x * npb;
    slow_bin(x, ea, src, dst, wa, wb, wc, wu, wv, out, E, node0, max(0, min(npb, N - node0)), 256);
}

constexpr int XS_BYTES = NPMAX * 1024;
constexpr int ES_BYTES = NPMAX * 256;
constexpr int SM_XS = 0;
constexpr int SM_XU = SM_XS + 3 * NSTAGE * XS_BYTES;
constexpr int SM_TAB = SM_XU + NPB_MAX * 128;
constexpr int SM_ES = SM_TAB + (NPB_MAX + 2) * 128;
constexpr int SM_WC = SM_ES + 3 * NSTAGE * ES_BYTES;
constexpr int SM_OH = SM_WC + 2048;
constexpr int SM_EID = SM_OH + 256;
constexpr int SM_SRC = SM_EID + (SLOT_CAP + 32) * 4;
constexpr int SM_TINFO = SM_SRC + (SLOT_CAP + 32) * 2;
constexpr int SM_MISC = SM_TINFO + TILE_CAP * 32;
constexpr int SM_CLAIM = SM_TAB + (NPB_MAX + 1) * 128;
constexpr int SM_BARS = SM_MISC + 32 * 4;
constexpr int SM_ABAR = SM_BARS + 6 * 48;
constexpr int SM_XBAR = SM_ABAR + 10 * 8;
constexpr int SM_GBAR = SM_XBAR + 4 * 8;
constexpr int SM_WL = SM_GBAR + 97 * 8;
constexpr int WST = 9;
constexpr int SMEM_BYTES = SM_WL + (96 + WST) * 8;
constexpr int SM_P2 = 0, SM_P1 = 6 * 384 * 16;
constexpr int SM_DEG = SM_P1 + P1B;
constexpr int SM_CNT = SM_DEG + 512 * 4;
constexpr int SM_CLS = SM_CNT + 512 * 4;
constexpr int SM_HIST = SM_CLS + NCLS * 4;
constexpr int SM_XLIST = SM_HIST + 136 * 4;
constexpr int SM_SORT = SM_XLIST + XCAP * 8;
constexpr int SM_BASE = SM_SORT + NPB_MAX * 4;
constexpr int SM_PAIR = SM_BASE + (NPB_MAX + 4) * 2;
constexpr int SM_IDX = SM_EID;
constexpr int SM_WR = SM_TAB;
static_assert(TILE_CAP <= 128 && TR >= 2 && SM_ES % 256 == 0 && NSTAGE == 2 && SM_BARS % 16 == 0 && SM_TINFO % 16 == 0 && SM_EID % 128 == 0 && SM_TAB % 1024 == 0 && SM_XU % 1024 == 0 && SM_TINFO % 8 == 0 && SM_OH % 16 == 0 && SM_SORT % 16 == 0 && SM_PAIR % 8 == 0, "align");
static_assert(P1B % 16 == 0 && P2B <= SM_P1 && NB_MAX <= 6 * 24 && SM_PAIR + 128 * 8 <= SM_XU && CH_MAX * 4 <= SM_SRC - SM_EID && SM_DEG >= 3 << 14, "alias");
static_assert(SMEM_BYTES <= 232448, "smem");
constexpr uint32_t C_BRK = 16  , C_CONT = 32, C_MORE = 64;
constexpr uint32_t ONE_F = 0x3F800000u;
constexpr int NONE = NPB_MAX;

__device__ __forceinline__ uint2 tile_info(uint32_t e) {
    const uint32_t y = (uint32_t)((int)e >> 16) & (ONE_F | 0x1FFFu);
    return make_uint2(e, (e & 0x1F000000u) ? y | 0x80000000u : y);
}
__device__ __forceinline__ bool unpad(uint32_t w1, int np, float ga, float gb, float& d0, float& d1, int& dv) {
    const int pad = (int)w1 < 0 ? (w1 >> 8) & 31 : 0;
    dv = 2 * np - 2 - pad + ((int)w1 > 127) + ((int)w1 >= (int)ONE_F);
    float t0 = TAU * 2 * np, t1 = t0;
    if (pad) {
        t0 = fmaxf(t0, d0 * (1.f / 1024)); t1 = fmaxf(t1, d1 * (1.f / 1024));
        asm volatile("tanh.approx.f32 %0, %0;\ntanh.approx.f32 %1, %1;" : "+f"(ga), "+f"(gb));
        d0 -= pad * (1.f + ga); d1 -= pad * (1.f + gb);
    }
    if (dv == 0) { d0 = d1 = EPS2; t0 = t1 = 0.f; }
    return __any_sync(~0u, d0 < t0 || d1 < t1);
}
__device__ __forceinline__ uint64_t desc_sw128(uint32_t a) {
    return (uint64_t)((a & 0x3FFFF) >> 4) | ((uint64_t)1 << 16) | ((uint64_t)64 << 32) | ((uint64_t)1 << 62);
}

__device__ __forceinline__ uint32_t sel(bool c, uint32_t a, uint32_t b) {
    uint32_t r; asm("{\n.reg .pred p;\nsetp.ne.u32 p, %1, 0;\nselp.b32 %0, %2, %3, p;\n}" : "=r"(r) : "r"((uint32_t)c), "r"(a), "r"(b)); return r;
}
__device__ __forceinline__ void tile_entry(uint8_t* smem, uint32_t sv, int dg, int mn, int t, int tl, int np, int done, uint32_t flags, int next) {
    const uint32_t nd = sv & 0xFFFF, w0 = nd * 128 + ((nd & 7) << 4);
    const int dv = min(max(dg - done, 0), 2 * np), r = 2 * np - dv;
    const bool gen = mn - done < 2 * np - 2;
    const uint32_t w1 = (uint32_t)np | flags | sel(gen || flags, C_BRK, 0u) | sel(r < 2, 0x8000u >> (8 * r), (r - 2) << 8);
    *(uint2*)(smem + SM_TINFO + tl * 32 + t * 8) = make_uint2(sel(dv, (sv >> 16) + done, 0) | (sel(gen, 13 + (np > 5) + (np > 8), np) << 16) | (next << 20) | ((uint32_t)dv << 27), w0 | sel(np, w1 << 16, 0u));
}
__device__ __noinline__ void tiles_many(uint8_t* smem, uint32_t sv, int dg, int mn, int id, int left, unsigned sm) {
    int* misc = (int*)(smem + SM_MISC);
    int nt = (left + NPMAX - 1) / NPMAX, tl = id >> 2, done = 0, nx = 0;
    if ((id & 3) == 0) { nx = atomicAdd(&misc[5], nt - 1); if (nx + nt - 1 > TILE_CAP) misc[1] = 1; }
    nx = __shfl_sync(sm, nx, id & 28);
    if (nx + nt - 1 > TILE_CAP) left = 0;
    uint32_t cont = 0;
    #pragma unroll 1
    while (left > 0) {
        const int np = (left + nt - 1) / nt;
        left -= np; nt--;
        tile_entry(smem, sv, dg, mn, id & 3, tl, np, done, cont | (left > 0 ? C_MORE : 0u), left > 0 ? nx : 0);
        tl = nx++; cont = C_CONT; done += 2 * np;
    }
}
__device__ __forceinline__ void tables(uint8_t* smem, uint32_t sbase, int id0, int ngroups) {
    const int t = id0 & 3;
    uint4 s4[3];
    uint32_t me[3], sv[3];
    #pragma unroll
    for (int k = 0; k < 3; k++) { s4[k] = lds128(sbase + SM_SORT + (id0 & ~3) * 4 + k * 512); me[k] = lds32(sbase + SM_SORT + id0 * 4 + k * 512); }
    #pragma unroll
    for (int k = 0; k < 3; k++) asm volatile("ld.shared.u16 %0, [%1];" : "=r"(sv[k]) : "r"(sbase + SM_BASE + (me[k] & 0xFFFF) * 2) : "memory");
    int mn[3], left[3];
    uint32_t more = 0;
    #pragma unroll
    for (int k = 0; k < 3; k++) {
        const int g = (id0 >> 2) + 32 * k, nx = ngroups + 4 + g;
        sv[k] = sv[k] << 16 | (me[k] & 0xFFFF);
        mn[k] = min(min(s4[k].x, s4[k].y), min(s4[k].z, s4[k].w)) >> 16;
        left[k] = ((max(max(s4[k].x, s4[k].y), max(s4[k].z, s4[k].w)) >> 16) + 1) >> 1;
        const bool two = left[k] > NPMAX;
        more |= two << k;
        tile_entry(smem, sv[k], me[k] >> 16, mn[k], t, sel(g >= ngroups + 4, ngroups, g), sel(two, min((left[k] + 1) >> 1, NPMAX), sel(left[k], max(left[k], NPMIN), 0)), 0, sel(two, C_MORE, 0u), sel(two, nx & 127, 0));
    }
    #pragma unroll 1
    for (int id = id0; __any_sync(~0u, more); id += 128) {
        const int nx = ngroups + 4 + (id >> 2);
        const bool odd = left[0] > 2 * NPMAX || ((more & 1) && nx >= TILE_CAP - TILE_X);
        const unsigned sm = __ballot_sync(~0u, odd);
        if (__builtin_expect(odd, 0)) tiles_many(smem, sv[0], me[0] >> 16, mn[0], id, left[0], sm);
        else if (more & 1) tile_entry(smem, sv[0], me[0] >> 16, mn[0], t, nx, left[0] >> 1, (left[0] + 1) & ~1, C_CONT, 0);
        __syncwarp();
        more >>= 1;
        sv[0] = sv[1]; sv[1] = sv[2]; me[0] = me[1]; me[1] = me[2]; mn[0] = mn[1]; mn[1] = mn[2]; left[0] = left[1]; left[1] = left[2];
    }
}
__device__ __forceinline__ uint32_t to_list(uint32_t sbase, uint32_t e, uint32_t bin) {
    uint32_t j; asm volatile("atom.shared.inc.u32 %0, [%1], 0x7fffffff;" : "=r"(j) : "r"(sbase + SM_MISC + 8) : "memory");
    j = min(j, 63u);
    sts32(sbase + SM_P1 + j * 4, e | ((j < 63 ? bin : 255u) << 16));
    return j;
}

template<bool LO32>
__global__ void __launch_bounds__(THREADS, 1)
gcn_kernel(const int* __restrict__ dst, unsigned* gbar, char* gs, const int* __restrict__ src, int E, int ch, int N, int npb, uint32_t magic,
           const __nv_bfloat16* __restrict__ x, const __nv_bfloat16* __restrict__ ea,
           const __nv_bfloat16* __restrict__ wa, const __nv_bfloat16* __restrict__ wb, const __nv_bfloat16* __restrict__ wc,
           const __nv_bfloat16* __restrict__ wu, const __nv_bfloat16* __restrict__ wv,
           __nv_bfloat16* out, int4 wrow, const __grid_constant__ CUtensorMap tm2, const __grid_constant__ CUtensorMap tmw,
           const __grid_constant__ CUtensorMap tmc, const __grid_constant__ CUtensorMap tmx)
{
    extern __shared__ __align__(1024) uint8_t smem[];
    int* cls = (int*)(smem + SM_CLS);
    int* misc = (int*)(smem + SM_MISC);
    uint32_t* xlist = (uint32_t*)(smem + SM_XLIST);
    WG0(); WS(0);
    const uint32_t sbase = smem_u32(smem);
    const int tid = threadIdx.x, lane = tid & 31;
    const int b = blockIdx.x, nb = gridDim.x;
    const int cnt = max(0, min(ch, E - b * ch));
    const int node0 = b * npb;
    auto src_ld = [&]() { bulk_ld(sbase + SM_XU, src + b * ch, cnt * 4, sbase + SM_ABAR + 32); };
    auto box_ld = [&](uint32_t dst, const CUtensorMap* tm, int col, int row, uint32_t bar) {
        asm volatile("cp.async.bulk.tensor.2d.shared::cluster.global.mbarrier::complete_tx::bytes [%0], [%1, {%3, %4}], [%2];"
            :: "r"(dst), "l"((uint64_t)tm), "r"(bar), "r"(col), "r"(row) : "memory");
    };
    auto w_ld = [&]() {
        mbar_expect(sbase + SM_ABAR + 24, 272 * 128);
        box_ld(sbase + SM_WR, &tmw, 0, wrow.y, sbase + SM_ABAR + 24); box_ld(sbase + SM_WR + 64 * 128, &tmc, 0, 0, sbase + SM_ABAR + 24);
        box_ld(sbase + SM_WR + 80 * 128, &tmw, 0, wrow.w, sbase + SM_ABAR + 24); box_ld(sbase + SM_WR + 144 * 128, &tmw, 0, wrow.x, sbase + SM_ABAR + 24);
        box_ld(sbase + SM_WR + 208 * 128, &tmw, 0, wrow.z, sbase + SM_ABAR + 24);
    };
    auto x_ld = [&](int k) {
        mbar_expect(sbase + SM_XBAR + k * 8, 16384);
        box_ld(sbase + SM_XU + k * 16384, &tmx, 0, node0 + 128 * k, sbase + SM_XBAR + k * 8);
    };
    if (tid >= 384) {
        if (elect_one()) {
            const int v = (tid >> 5) & 3;
            mbar_init(sbase + SM_ABAR + v * 8, 1);
            asm volatile("fence.mbarrier_init.release.cluster;" ::: "memory");
            if (v < 3) bulk_ld(sbase + SM_IDX + v * 8192, dst + b * ch + v * 2048, min(max(cnt * 4 - v * 8192, 0), 8192), sbase + SM_ABAR + v * 8);
            else {
                mbar_init(sbase + SM_ABAR + 32, 1); mbar_init(sbase + SM_ABAR + 40, 1); mbar_init(sbase + SM_GBAR + 96 * 8, 32); mbar_init(sbase + SM_ABAR + 72, 384); mbar_init(sbase + SM_XBAR + 24, 512);
            }
            #pragma unroll 8
            for (int i = 0; i < 24; i++) mbar_init(sbase + SM_GBAR + (v * 24 + i) * 8, 32);
            if (tid < 480) {
                #pragma unroll
                for (int i = 0; i < 2; i++) { mbar_init(sbase + SM_BARS + (v * 2 + i) * 48, 64); mbar_init(sbase + SM_BARS + (v * 2 + i) * 48 + 8, 128); }
                mbar_init(sbase + SM_ABAR + 48 + v * 8, 4); mbar_init(sbase + SM_XBAR + v * 8, 1);
            }
            asm volatile("fence.mbarrier_init.release.cluster;" ::: "memory");
        }
    }
    if (tid >= 128 && tid < 132) asm volatile("prefetch.tensormap [%0];" :: "l"((uint64_t)(tid == 128 ? &tmw : tid == 129 ? &tmc : tid == 130 ? &tm2 : &tmx)) : "memory");
    uint32_t tag = 0;
    if (tid < 32) asm volatile("ld.relaxed.gpu.global.u32 %0, [%1];" : "=r"(tag) : "l"(gbar));
    const int warp = (int)__reduce_max_sync(~0u, (unsigned)tid >> 5);
    const int wg = warp >> 2, w = warp & 3;
    const int q = lane >> 2, t = lane & 3;
    const int ch0 = 16 * w + 2 * q;
    const int nn = max(0, min(npb, N - node0));
    if (sbase & 1023) __trap();

    sts32(sbase + (tid < NPB_MAX ? SM_DEG : SM_CNT) + tid * 4, tid < NPB_MAX ? 0 : 0x80000000u);
    if (tid < NCLS + NB_MAX) cls[tid] = tid < NCLS ? 0 : (tid - NCLS) * CE + 64;
    else if (wg == 2) {
        if (w < 2) {
            *(uint32_t*)(smem + SM_OH + (tid & 63) * 4) = t != (q >> 1) ? 0u : (w == 0 ? 0x00003F00u : 0x3F000000u);
        } else if (w == 2) *(uint32_t*)(smem + SM_TAB + NPB_MAX * 128 + lane * 4) = 0u;
        else misc[lane] = lane == 5 ? TILE_CAP - TILE_X : 0;
    }
    if (warp == 13 && lane < WST * 2) sts32(sbase + SM_WL + 768 + lane * 4, NONE * 0x10001u);
    if (warp == 14) sts32(sbase + SM_TINFO + 96 * 32 + lane * 4, 0);
    if (warp == 15) sts32(sbase + SM_CLAIM + lane * 4, lane == 0 ? 3 : 0x40000000);
    if (tid == 0) sts32(sbase + SM_PAIR, tag);
    if (wg < 3) { asm volatile("bar.sync 1, 384;" ::: "memory"); tag = lds32(sbase + SM_PAIR); }
    tag = (tag & 1) | 2;
    if (wg < 3) {
        const uint32_t d0 = ((NPB_MAX + ((2 * lane) & 15) + 16 * (b & 1)) * 4 | (tag << 14)) * 0x10001u, d1 = d0 + 0x40004u, d2 = tag << 16;
        #pragma unroll 1
        for (int i = tid; i < P1B / 16; i += 384) {
            sts128(sbase + SM_P1 + i * 16, make_uint4(d0, d0, d1, d1));
            sts128(sbase + SM_P2 + i * 16, make_uint4(d2, d2, d2, d2)); sts128(sbase + SM_P2 + (P2B - P1B) + i * 16, make_uint4(d2, d2, d2, d2));
        }
    }
    if (warp == 15 && elect_one()) w_ld();
    WS(1);
    __syncthreads();
    if (wg == 3) tag = lds32(sbase + SM_P2) >> 16;

    uint32_t ent[EPT];
    #pragma unroll
    for (int v = 0; v < EPT / 4; v++) {
        mbar_wait_c(sbase + SM_ABAR + v * 8, 0);
        if (v == 0 && warp == 15 && elect_one()) src_ld();
        const uint32_t off = v * (THREADS * 4) + tid * 4;
        if (off < (uint32_t)cnt) {
            const uint32_t ia = sbase + SM_IDX + off * 4;
            const uint4 u = lds128(ia);
            uint32_t dv[4] = {u.x, u.y, u.z, u.w}, ps[4], ck[4];
            uint32_t* en = ent + 4 * v;
            #pragma unroll
            for (int k = 0; k < 4; k++) {
                dv[k] = min(dv[k], (uint32_t)(nb * npb - 1));
                ps[k] = __umulhi(dv[k], magic); en[k] = atoms_inc(sbase + SM_HIST + ps[k] * 4);
            }
            #pragma unroll
            for (int k = 0; k < 4; k++) {
                dv[k] = (dv[k] - ps[k] * npb) * 4 + (tag << 14);
                ck[k] = en[k] - ps[k] * CE;
                en[k] ^= ps[k] * 4 & 60;
            }
            if (__builtin_expect(max(max(ck[0], ck[1]), max(ck[2], ck[3])) >= 64 + CE, 0)) {
                #pragma unroll
                for (int k = 0; k < 4; k++) if (ck[k] >= 64 + CE) en[k] = to_list(sbase, dv[k], ps[k]);
            }
            #pragma unroll
            for (int k = 0; k < 4; k++)
                asm volatile("{\n.reg .pred p;\nsetp.ge.u32 p, %2, 64;\n@p st.shared.u16 [%0], %1;\n}" :: "r"(sbase + SM_P1 + 128 + en[k] * 2), "r"(dv[k]), "r"(en[k]) : "memory");
        }
    }
    WS(5);
    __syncthreads();
    auto send = [&](int o, uint32_t a, int bytes) {
        if (warp == 14 && elect_one()) {
            asm volatile("fence.proxy.async.shared::cta;" ::: "memory");
            bulk_st(gs + b * (P1B + P2B) + o, a, bytes);
            asm volatile("cp.async.bulk.commit_group;" ::: "memory");
        }
    };
    send(0, sbase + SM_P1, 256 + nb * (CE * 2));
    mbar_wait_c(sbase + SM_ABAR + 32, 0);
    #pragma unroll
    for (int v = 0; v < EPT / 4; v++) {
        const uint32_t off = v * (THREADS * 4) + tid * 4;
        if (off < (uint32_t)cnt) {
            const uint4 sv = lds128(sbase + SM_XU + off * 4);
            const uint32_t* uu = ent + 4 * v;
            const uint32_t ss[4] = {sv.x, sv.y, sv.z, sv.w};
            #pragma unroll
            for (int k = 0; k < 4; k++) sts32(sbase + SM_P2 + uu[k] * 4, (ss[k] & 0xFFFF) | (((off + k) << 19) + (tag << 16)));
        }
    }
    WS(7);
    __syncthreads();
    send(P1B, sbase + SM_P2, 256 + nb * (CE * 4));
    WSL(8);

    const int ngroups = (nn + 3) >> 2;
    if (wg == 3) {
        asm volatile("setmaxnreg.dec.sync.aligned.u32 56;");
        WS(2);
        const char* const ga = as_pair((const char*)x + (w < 3 ? 0 : (size_t)node0 * 128) + (lane & 7) * 16, sbase + SM_PAIR + (tid & 127) * 8);
        const char* const gb = as_pair(w < 3 ? (const char*)ea + (lane & 1) * 16 : (const char*)out + (size_t)node0 * 128 + (lane & 7) * 16, sbase + SM_PAIR + (tid & 127) * 8);
        WS(3);
        const uint32_t dm = ((NPB_MAX + lane) * 4 | (tag << 14)) * 0x10001u;
        const uint32_t db = sbase + SM_DEG - (tag << 14);
        const char* gl = gs + ((tid & 127) >> 2) * (P1B + P2B) + t * 16;
        uint4 rl[5];
        #pragma unroll
        for (int i = 0; i < 5; i++) rl[i].w = ((tid & 127) >> 2) + 32 * i < nb ? 0 : dm;
        auto p2_ld = [&]() {
            mbar_expect(sbase + SM_ABAR + 40, nb * (CE * 4));
            box_ld(sbase + SM_P2, &tm2, P1B / 4 + 64 + b * CE, 0, sbase + SM_ABAR + 40);
        };
        asm volatile("cp.async.bulk.wait_group.read 0;" ::: "memory");
        asm volatile("bar.sync 6, 128;" ::: "memory");
        WSL(12);
        uint32_t spins = 0;
        #pragma unroll 1
        for (int r = 0;; r++) {
            #pragma unroll
            for (int i = 0; i < 5; i++) rl[i].x = rl[i].y = rl[i].z = dm;
            while (true) {
                #pragma unroll
                for (int i = 0; i < 5; i++) ld_unit(rl[i], gl + i * (32 * (P1B + P2B)), (rl[i].w ^ dm) & 0xC000);
                if (spins == 0) asm volatile("bar.sync 5, 512;" ::: "memory");
                if (++spins > (1u << 22)) __trap();
                if (!__any_sync(~0u, ((rl[0].w ^ dm) | (rl[1].w ^ dm) | (rl[2].w ^ dm) | (rl[3].w ^ dm) | (rl[4].w ^ dm)) & 0xC000)) break;
            }
            if (r == 0 && w == 2 && elect_one()) x_ld(0);
            WS(4);
            uint32_t own = 0;
            #pragma unroll
            for (int i = 0; i < 5; i++) {
                const uint32_t bb = b << 16;
                own |= (min(min(rl[i].x ^ bb, rl[i].y ^ bb), min(rl[i].z ^ bb, rl[i].w ^ bb)) < 0x10000u) << i;
            }
            while (own != 0) {
                const int i = __ffs(own) - 1; own &= own - 1;
                const uint4 u = i == 0 ? rl[0] : i == 1 ? rl[1] : i == 2 ? rl[2] : i == 3 ? rl[3] : rl[4];
                const uint32_t e[4] = {u.x ^ (b << 16), u.y ^ (b << 16), u.z ^ (b << 16), u.w ^ (b << 16)};
                const uint32_t s = (((tid & 127) >> 2) + 32 * i << 16) + (4 * r + t << 26);
                int n;
                asm volatile("atom.shared.add.u32 %0, [%1], %2;" : "=r"(n) : "r"(sbase + SM_MISC), "r"((e[0] < 0x10000u) + (e[1] < 0x10000u) + (e[2] < 0x10000u) + (e[3] < 0x10000u)) : "memory");
                #pragma unroll
                for (int k = 0; k < 4; k++) asm volatile("red.shared.add.u32 [%0], 1;" :: "r"(db + min(e[k], dm & 0xFFFF)) : "memory");
                if (n + 4 > XCAP) { misc[1] = 1; n = 0; }
                #pragma unroll
                for (int k = 0; k < 4; k++) if (e[k] < 0x10000u) xlist[n++] = e[k] | (s + (k << 24));
            }
            __syncwarp();
            if (__builtin_expect(!__any_sync(~0u, t == 3 && min(min(min(rl[0].w, rl[1].w), min(rl[2].w, rl[3].w)), rl[4].w) < 0x1000000u), 1)) break;
            if (r == 3) { misc[1] = 1; break; }
            #pragma unroll
            for (int i = 0; i < 5; i++) rl[i].w = __shfl_sync(~0u, rl[i].w, lane | 3) < 0x1000000u ? 0 : dm;
            gl += 64;
        }
        WS(11);
        asm volatile("bar.sync 7, 512;" ::: "memory");
        auto rest_ld = [&]() {
            if (w == 2 && elect_one()) {
                p2_ld();
                x_ld(1); x_ld(2);
            }
            __syncwarp();
        };
        WS(9);
        {
            int dg[3], cl[3], cr[3];
            #pragma unroll
            for (int k = 0; k < 3; k++) dg[k] = lds32(sbase + SM_DEG + ((tid & 127) + 128 * k) * 4);
            const uint2 m01 = lds64(sbase + SM_MISC);
            const int xi = (tid + 96) & 127, nx = m01.y ? 0 : m01.x;
            const uint32_t xe = xlist[xi];
            #pragma unroll
            for (int k = 0; k < 3; k++) {
                cl[k] = NCLS - 1 - (dg[k] <= 40 ? dg[k] : min(41 + ((dg[k] - 41) >> 3), NCLS - 1));
                cr[k] = atoms_inc(sbase + ((tid & 127) + 128 * k < nn ? SM_CLS + cl[k] * 4 : SM_DEG + NPB_MAX * 4));
            }
            rest_ld();
            asm volatile("bar.sync 6, 128;" ::: "memory");
            WS(13);
            const uint2 c = lds64(sbase + SM_CLS + lane * 8);
            uint32_t inc = c.x + c.y;
            #pragma unroll
            for (int o = 1; o < 32; o <<= 1) { const uint32_t y = __shfl_up_sync(~0u, inc, o); if (lane >= o) inc += y; }
            inc = (inc - c.x - c.y) | (inc - c.y) << 16;
            #pragma unroll
            for (int k = 0; k < 3; k++) {
                const int id = (tid & 127) + 128 * k;
                const uint32_t e = __shfl_sync(~0u, inc, cl[k] >> 1);
                const uint32_t pos = id < nn ? (cl[k] & 1 ? e >> 16 : e & 0xFFFF) + cr[k] : id, nd = id < nn ? id : NONE;
                sts32(sbase + SM_SORT + pos * 4, nd | min(dg[k], 65535) << 16);
                asm volatile("st.shared.u16 [%0], %1;" :: "r"(sbase + SM_WL + pos * 2), "r"(nd) : "memory");
            }
            if (tid == 511) misc[4] = (nn - c.y + 3) >> 2;
            asm volatile("bar.sync 4, 512;" ::: "memory");
            WS(14);
            uint32_t xs = 0x80000000u, xv = tag << 16;
            auto x_get = [&]() { asm volatile("ld.relaxed.gpu.global.u32 %0, [%1];" : "=r"(xv) : "l"(gs + ((xe >> 16) & 0xFF) * (P1B + P2B) + P1B + (xe >> 24) * 4) : "memory"); };
            if (xi < nx) {
                asm volatile("atom.shared.add.u32 %0, [%1], 4;" : "=r"(xs) : "r"(db + (SM_CNT - SM_DEG) + (xe & 0xFFFF)) : "memory");
                x_get();
            }
            tables(smem, sbase, (tid + 32) & 127, ngroups);
            __syncwarp();
            while (__any_sync(~0u, ((xv >> 16) & 3) != tag)) { if (((xv >> 16) & 3) != tag) x_get(); if (++spins > (1u << 22)) __trap(); }
            if (xs < 4 * SLOT_CAP) {
                sts32(sbase + SM_EID + xs, ((xe >> 16) & 0xFF) * ch + (xv >> 19));
                asm volatile("st.shared.u16 [%0], %1;" :: "r"(sbase + SM_SRC + (xs >> 1)), "r"(xv) : "memory");
            }
            mbar_arrive(sbase + SM_XBAR + 24);
            asm volatile("bar.sync 6, 128;" ::: "memory");
        }
        WS(10);
        WGD();
        const int r4 = lane >> 3, c8 = lane & 7;
        const uint32_t sb = __reduce_or_sync(~0u, sbase);
        if (w < 3) {
            const char* gx = ga; const char* ge = gb;
            const uint32_t gx0 = (uint32_t)(uint64_t)gx, ge0 = (uint32_t)(uint64_t)ge, hi = (uint64_t)gx >> 32, he = (uint64_t)ge >> 32;
            const int s = (lane >> 1) & 3;
            const uint32_t xs0 = sb + SM_XS + w * NSTAGE * XS_BYTES;
            const uint32_t es0 = sb + SM_ES + w * NSTAGE * ES_BYTES + r4 * 64 + (((lane ^ (r4 >> 1)) & 1) << 4) + (s >> 1) * 256 + (s & 1) * 32;
            const uint32_t bars = sb + SM_BARS + w * 96;
            const uint32_t xoffA = (2 * r4) * 128 + ((c8 ^ (2 * r4)) << 4), xoffB = (2 * r4 + 1) * 128 + ((c8 ^ (2 * r4 + 1)) << 4);
            uint64_t pol;
            asm volatile("createpolicy.fractional.L2::evict_first.b64 %0, 1.0;" : "=l"(pol));
            uint32_t first = 1;
            WS(15);
            uint32_t ph = 1, cur = w;
            uint32_t hist = 96 * 0x010101u;
            auto done3 = [&]() { mbar_arrive(sb + SM_GBAR + ((hist >> 16) & 0xFF) * 8); };
            const uint32_t ca = sb + SM_CLAIM + lane * 4, pa = sb + SM_TINFO + r4 * 8;
            const uint2 p0 = lds64(pa + w * 32);
            const bool go = lds32(sb + SM_MISC + 4) == 0 && nn > 0;
            uint32_t pw = go ? p0.x : 0, brk = (p0.y >> 16) & C_BRK;
            const uint32_t se0 = sb + SM_EID + s * 4, xab = xoffB - xoffA, das = 2 * (xs0 + xoffA) + XS_BYTES, des = 2 * es0 + ES_BYTES, brs = 2 * bars + 48;
            uint32_t da = xs0 + xoffA, de = es0, br = bars;
            #pragma unroll 1
            while (true) {
                const uint32_t pt = __reduce_or_sync(~0u, pw);
                uint32_t se, sx;
                asm("dp2a.lo.u32.u32 %0, %1, 4, %2;" : "=r"(se) : "r"(pw), "r"(se0));
                asm("dp2a.lo.u32.u32 %0, %1, 2, %2;" : "=r"(sx) : "r"(pw), "r"(sb + SM_SRC));
                const int dv = pw >> 27;
                const uint32_t db = da + xab;
                const uint32_t sel = (pt >> 16) & 15, nx = (pt >> 20) & 127;
                uint32_t g;
                auto claim = [&]() { asm volatile("atom.shared.add.u32 %0, [%1], %2;" : "=r"(g) : "r"(ca), "r"(nx == 0 ? 1u : 0u) : "memory"); };
                if (sel == 0) break;
                if (first) { asm volatile("bar.sync 3, 480;" ::: "memory"); first = 0; WSL(6); }
                switch (sel) {
#define CASE(L, P, GEN) case L: { \
                        uint32_t oe[(P + 1) / 2], o[P]; \
                        _Pragma("unroll") for (int j = 0; j < (P + 1) / 2; j++) oe[j] = lds32(se + j * 16); \
                        _Pragma("unroll") for (int j = 0; j < P; j++) o[j] = lds32(sx + j * 4); \
                        mbar_wait_h(br + 8, ph); \
                        _Pragma("unroll") for (int j = 0; j < (P + 1) / 2; j++) \
                            if (LO32) { if (!GEN && 2 * j + 2 < P) cpe<false>(he, de + j * 512, oe[j], ge0, 0, 0, pol); \
                                else if (2 * j + 1 < NPMAX || s < 2) cpe<true>(he, de + j * 512, oe[j], ge0, 4 * j + s, dv, pol); } \
                            else if (!GEN && 2 * j + 2 < P) cp16e(de + j * 512, ge, oe[j], pol); else if (2 * j + 1 < NPMAX || s < 2) cp16z<32>(de + j * 512, ge, oe[j], 4 * j + s, dv, pol); \
                        _Pragma("unroll") for (int j = 0; j < P - 1; j++) { \
                            if (LO32) { cpx<0, GEN>(hi, da + j * 1024, o[j], gx0, 2 * j, dv); cpx<1, GEN>(hi, db + j * 1024, o[j], gx0, 2 * j + 1, dv); } \
                            else if (GEN) { cp16z<128>(da + j * 1024, gx, o[j] & 0xFFFFu, 2 * j, dv, 0); cp16z<128>(db + j * 1024, gx, o[j] >> 16, 2 * j + 1, dv, 0); } \
                            else { cp16i<128>(da + j * 1024, gx, o[j] & 0xFFFFu); cp16i<128>(db + j * 1024, gx, o[j] >> 16); } } \
                        if (LO32) { cpx<0, true>(hi, da + (P - 1) * 1024, o[P - 1], gx0, 2 * P - 2, dv); cpx<1, true>(hi, db + (P - 1) * 1024, o[P - 1], gx0, 2 * P - 1, dv); } \
                        else { cp16z<128>(da + (P - 1) * 1024, gx, o[P - 1] & 0xFFFFu, 2 * P - 2, dv, 0); cp16z<128>(db + (P - 1) * 1024, gx, o[P - 1] >> 16, 2 * P - 1, dv, 0); } \
                    } break;
                    CASE(6, 6, false) CASE(7, 7, false) CASE(8, 8, false) CASE(9, 9, false) CASE(10, 10, false) CASE(11, 11, false)
                    CASE(15, NPMAX, true) CASE(14, 8, true) default: CASE(13, 5, true)
#undef CASE
                }
                claim();
                mbar_cp_arrive(br);
                done3();
                g = __reduce_min_sync(~0u, g);
                {
                    const uint2 e = lds64(pa + (nx == 0 ? g : nx) * 32);
                    const uint2 v = tile_info(e.y);
                    pw = e.x;
                    asm volatile("st.shared.v2.u32 [%0], {%1, %2};" :: "r"(br + 16 + r4 * 8), "r"(v.x), "r"((v.y & ~C_BRK) | brk) : "memory");
                    brk = v.y & C_BRK;
                }
                mbar_arrive(br);
                hist = (hist << 8) | (nx == 0 ? cur : 96u);
                cur = nx == 0 ? g : cur;
                ph ^= br != bars; br = brs - br; da = das - da; de = des - de;
            }
            if (first) asm volatile("bar.sync 3, 480;" ::: "memory");
            if (go) {
                mbar_wait(sb + SM_ABAR + 72, 0);
                const int g0 = 3 * max((ngroups + 2) / 3 - TR, 0) + w;
                uint32_t nd[TR]; uint4 xv[TR];
                #pragma unroll
                for (int k = 0; k < TR; k++) {
                    asm volatile("ld.shared.u16 %0, [%1];" : "=r"(nd[k]) : "r"(sb + SM_WL + (g0 + 3 * k) * 8 + r4 * 2) : "memory");
                    xv[k] = __ldg((const uint4*)(gx + (size_t)(node0 + (nd[k] == NONE ? 0u : nd[k])) * 128));
                }
                #pragma unroll 1
                for (int k = 0; k < 3; k++) {
                    mbar_wait(k < 2 ? br + 8 : sb + SM_ABAR + 48 + w * 8, k < 2 ? ph : 0);
                    done3(); hist <<= 8;
                    ph ^= br != bars; br = brs - br;
                }
                #pragma unroll
                for (int k = 0; k < TR; k++) {
                    const uint32_t ro = sb + nd[k] * 128 + ((c8 ^ (nd[k] & 7)) << 4);
                    const uint4 xu = lds128(ro + SM_XU);
                    uint4 a = make_uint4(0, 0, 0, 0);
                    if (g0 + 3 * k < misc[4]) { mbar_wait(sb + SM_GBAR + (g0 + 3 * k) * 8, 0); a = lds128(ro + SM_TAB); }
                    finish(a, xu, xv[k]);
                    if (nd[k] != NONE) *(uint4*)((char*)out + (size_t)(node0 + nd[k]) * 128 + c8 * 16) = a;
                }
            }
            cp_wait<0>();
        } else {
            const char* gx = ga; const char* ob = gb;
            mbar_wait(sb + SM_ABAR + 72, 0);
            WS(15);
            if (b == 0 && lane == 0) asm volatile("red.relaxed.gpu.global.add.u32 [%0], 1;" :: "l"(gbar) : "memory");
            const int rounds = misc[1] ? 0 : max((ngroups + 2) / 3 - TR, 0);
            const int gz = misc[4], fast = __reduce_min_sync(~0u, min(rounds, gz / 3));
            uint32_t wl = sb + SM_WL + r4 * 2, gbar = sb + SM_GBAR;
            auto row_at = [&](uint32_t a) { uint32_t n; asm volatile("ld.shared.u16 %0, [%1];" : "=r"(n) : "r"(a) : "memory"); return n; };
            auto fetch = [&](uint32_t n, uint4& v) {
                asm volatile("{\n.reg .b64 p;\nmad.wide.u32 p, %5, 128, %4;\nld.global.nc.L1::no_allocate.v4.u32 {%0,%1,%2,%3}, [p];\n}"
                             : "=r"(v.x), "=r"(v.y), "=r"(v.z), "=r"(v.w) : "l"(gx), "r"(n));
            };
            auto store = [&](uint32_t n, const uint4& a) {
                asm volatile("{\n.reg .b64 p;\nmad.wide.u32 p, %1, 128, %0;\nst.global.v4.u32 [p], {%2,%3,%4,%5};\n}" :: "l"(ob), "r"(n), "r"(a.x), "r"(a.y), "r"(a.z), "r"(a.w) : "memory");
            };
            uint32_t n0[3]; uint4 x0[3];
            if (fast) {
                #pragma unroll
                for (int r = 0; r < 3; r++) { n0[r] = row_at(wl + r * 8); fetch(n0[r], x0[r]); }
            }
            #pragma unroll 1
            for (int k = 0; k < fast; k++) {
                wl += 24;
                #pragma unroll
                for (int r = 0; r < 3; r++) {
                    const uint32_t nd = n0[r], ro = sb + nd * 128 + ((c8 ^ (nd & 7)) << 4);
                    const uint4 xu = lds128(ro + SM_XU);
                    n0[r] = row_at(wl + r * 8);
                    mbar_wait(gbar + r * 8, 0);
                    uint4 a = lds128(ro + SM_TAB);
                    finish(a, xu, x0[r]);
                    fetch(n0[r], x0[r]);
                    store(nd, a);
                }
                gbar += 24;
            }
            #pragma unroll 1
            for (int g = 3 * fast; g < 3 * rounds; g++) {
                const uint32_t nd = row_at(sb + SM_WL + r4 * 2 + g * 8), ro = sb + nd * 128 + ((c8 ^ (nd & 7)) << 4);
                uint4 xv, a = make_uint4(0, 0, 0, 0);
                fetch(nd, xv);
                if (g < gz) { mbar_wait(sb + SM_GBAR + g * 8, 0); a = lds128(ro + SM_TAB); }
                finish(a, lds128(ro + SM_XU), xv);
                store(nd, a);
            }
        }
    } else {
        asm volatile("setmaxnreg.inc.sync.aligned.u32 152;");
        float4 lgh[2 * NPMAX];
        uint32_t wf[40], wn[16], wt[16];
        const uint32_t mo0 = sbase + SM_TAB + (8 * (lane >> 4) + (lane & 7)) * 128 + (((2 * w + ((lane >> 3) & 1)) ^ (lane & 7)) << 4);
        mbar_wait_c(sbase + SM_ABAR + 24, 0);
        {
            const uint32_t wo = sbase + SM_WR + (2 * t) * 128 + ((ch0 * 2) ^ (t * 32));
            #pragma unroll
            for (int ks = 0; ks < 9; ks++) {
                uint32_t wr[4];
                #pragma unroll
                for (int i = 0; i < 4; i++) wr[i] = lds32((wo ^ ((i & 1) * 16)) + (16 * ks + (i & 1) + 4 * (i & 2)) * 128);
                if (ks < 5) make_wfrag<true>(wf + 4 * ks, wr); else make_wfrag<false>(wf + 4 * ks, wr);
            }
            #pragma unroll
            for (int ks = 0; ks < 4; ks++) { ldsm4t(wn + 4 * ks, mo0 + (144 + 16 * ks) * 128); ldsm4t(wt + 4 * ks, mo0 + (208 + 16 * ks) * 128); }
            if (wg == 2) {
                const uint32_t a = sbase + SM_WC + (16 * w + q) * 32 + t * 4, sw = (q >> 2) << 4;
                sts32(a + sw, wf[16]); sts32(a + 256 + sw, wf[17]); sts32(a + (sw ^ 16), wf[18]); sts32(a + 256 + (sw ^ 16), wf[19]);
                asm volatile("fence.proxy.async.shared::cta;" ::: "memory");
            }
            #pragma unroll
            for (int i = 0; i < 36; i++) asm volatile("" : "+r"(wf[i]));
        }
        WS(9);
        constexpr int NU = 6;
        const uint32_t dm = ((NPB_MAX + lane) * 4 | (tag << 14)) * 0x10001u;
        const char* const g1 = gs + (tid >> 4) * (P1B + P2B) + 256 + b * (CE * 2) + (lane & 15) * 8;
        const bool last = 2 * warp + 24 * (NU - 1) < nb;
        uint2 r1[NU];
        #pragma unroll
        for (int i = 0; i < NU; i++) r1[i] = make_uint2(dm, (tid >> 4) + 24 * i < nb ? 0 : dm);
        uint32_t spins = 0;
        asm volatile("bar.sync 5, 512;" ::: "memory");
        while (true) {
            #pragma unroll
            for (int i = 0; i < NU; i++) ld_unit(r1[i], g1 + i * (24 * (P1B + P2B)), (r1[i].y ^ dm) & 0xC000);
            #pragma unroll
            for (int i = 0; i < 4; i++) sts128(mo0 + wg * 16384 + 8192 + i * 2048, make_uint4(wt[4*i], wt[4*i+1], wt[4*i+2], wt[4*i+3]));
            uint32_t bad = 0;
            #pragma unroll
            for (int i = 0; i < NU; i++) bad |= r1[i].y ^ dm;
            const bool more = __any_sync(~0u, bad & 0xC000);
            if (spins == 0) WS(2);
            if (!more) break;
            if (++spins > (1u << 22)) __trap();
        }
        WS(3);
        const uint32_t db = sbase + SM_DEG - (tag << 14);
        uint32_t rk[NU][4];
        #pragma unroll
        for (int i = 0; i < NU; i++) {
            #pragma unroll
            for (int k = 0; k < 4; k++) {
                asm("dp2a.lo.u32.u32 %0, %1, %2, %3;" : "=r"(rk[i][k]) : "r"(k < 2 ? r1[i].x : r1[i].y), "r"(k & 1 ? 0x100u : 1u), "r"(db));
                if (i < NU - 1 || last) asm volatile("red.shared.add.u32 [%0], 1;" :: "r"(rk[i][k]) : "memory");
            }
        }
        WS(10);
        asm volatile("bar.sync 7, 512;" ::: "memory");
        WS(11);
        {
            const uint32_t ev = (lds32(sbase + SM_DEG + tid * 4) + 1) & ~1u;
            uint32_t inc = ev, base = 0;
            #pragma unroll
            for (int o = 1; o < 32; o <<= 1) { const uint32_t y = __shfl_up_sync(~0u, inc, o); if (lane >= o) inc += y; }
            if (lane == 31) {
                asm volatile("atom.shared.add.u32 %0, [%1], %2;" : "=r"(base) : "r"(sbase + SM_MISC + 24), "r"(inc) : "memory");
                if (base + inc > SLOT_CAP) misc[1] = 1;
            }
            const uint32_t s0 = min(__shfl_sync(~0u, base, 31) + inc - ev, SLOT_CAP);
            sts32(sbase + SM_CNT + tid * 4, 4 * s0);
            asm volatile("st.shared.u16 [%0], %1;" :: "r"(sbase + SM_BASE + tid * 2), "r"(s0) : "memory");
        }
        asm volatile("bar.arrive 4, 512;" ::: "memory");
        asm volatile("bar.sync 1, 384;" ::: "memory");
        WS(13);
        #pragma unroll
        for (int i = 0; i < NU; i++) {
            if (i < NU - 1 || last) {
                #pragma unroll
                for (int k = 0; k < 4; k++) asm volatile("atom.shared.add.u32 %0, [%0+%1], 4;" : "+r"(rk[i][k]) : "n"(SM_CNT - SM_DEG) : "memory");
            }
        }
        WS(14);
        uint4 r2[NU];
        mbar_wait_c(sbase + SM_ABAR + 40, 0);
        WS(4);
        #pragma unroll
        for (int i = 0; i < NU; i++) r2[i] = lds128(sbase + SM_P2 + (i < NU - 1 ? tid + 384 * i : min(tid + 384 * i, P2B / 16 - 1)) * 16);
        while (true) {
            uint32_t bad = 0;
            #pragma unroll
            for (int i = 0; i < NU; i++) bad |= r2[i].w ^ (tag << 16);
            if (__builtin_expect(!__any_sync(~0u, bad & 0x30000), 1)) break;
            #pragma unroll
            for (int i = 0; i < NU; i++)
                ld_unit(r2[i], g1 + (P1B + b * (CE * 2) + (lane & 15) * 8 + i * (24 * (P1B + P2B))), (r2[i].w ^ (tag << 16)) & 0x30000);
            if (++spins > (1u << 22)) __trap();
        }
        WS(16);
        const uint32_t sbu = __reduce_or_sync(~0u, sbase);
        auto place = [&](uint32_t s4, uint32_t v, uint32_t eb) {
            asm volatile("{\n.reg .pred p;\nsetp.lt.u32 p, %0, %5;\n@p st.shared.u32 [%1], %2;\n@p st.shared.u16 [%3], %4;\n}"
                         :: "r"(s4), "r"(sbu + SM_EID + s4), "r"(eb + (v >> 19)), "r"(sbu + SM_SRC + (s4 >> 1)), "r"(v), "n"(4 * SLOT_CAP) : "memory");
        };
        #pragma unroll
        for (int i = 0; i < NU; i++) {
            const uint32_t eb = ((tid >> 4) + 24 * i) * ch;
            if (i < NU - 1 || last) { place(rk[i][0], r2[i].x, eb); place(rk[i][1], r2[i].y, eb); place(rk[i][2], r2[i].z, eb); place(rk[i][3], r2[i].w, eb); }
        }
        WS(1);
        WGD();
        asm volatile("bar.arrive 3, 480;" ::: "memory");
        {
        int lane;
        asm volatile("mov.u32 %0, %%laneid;" : "=r"(lane));
        const int q = lane >> 2, t = lane & 3, ch0 = 16 * w + 2 * q;
        const uint32_t sbase = sbu;
        { const uint2 z = lds64(sbase + SM_OH + 8); wf[37] = z.x; wf[38] = z.y; }
        const uint32_t c2 = __shfl_sync(~0u, ch0 * 2, lane), t8 = __shfl_sync(~0u, t * 8, lane);
        float g[4 * NPMAX], h[4 * NPMAX];
        float4 cyr = make_float4(0.f, 0.f, 0.f, 0.f);
        {
            const uint32_t mo = sbase + (8 * (lane >> 4) + (lane & 7)) * 128 + (((2 * w + ((lane >> 3) & 1)) ^ (lane & 7)) << 4);
            mbar_wait_c(sbase + SM_XBAR + wg * 8, 0);
            WSP(4);
            node_mma2(g, h, wn, desc_sw128(sbase + SM_XU + wg * 16384));
            TileMMA<8>::wait_g(g);
            node_rows(mo + SM_TAB + wg * 16384, g);
            TileMMA<8>::wait_h(h);
            WSP(5);
            #pragma unroll
            for (int i = 0; i < 4; i++) {
                const uint4 f = lds128(mo + SM_TAB + wg * 16384 + 8192 + i * 2048);
                wn[4*i] = f.x; wn[4*i+1] = f.y; wn[4*i+2] = f.z; wn[4*i+3] = f.w;
            }
            __syncwarp();
            node_rows(mo + SM_TAB + wg * 16384 + 8192, h);
            mbar_arrive(sbase + SM_XBAR + 24);
            WSP(2);
            node_mma2(g, h, wn, desc_sw128(sbase + SM_XU + wg * 16384));
            TileMMA<8>::wait_g(g);
            asm volatile("bar.sync %0, 128;" :: "r"(8 + wg) : "memory");
            node_rows(mo + SM_XU + wg * 16384, g);
            TileMMA<8>::wait_h(h);
            WSP(3);
            asm volatile("bar.sync %0, 128;" :: "r"(8 + wg) : "memory");
            node_rows(mo + SM_XU + wg * 16384 + 8192, h);
            mbar_arrive(sbase + SM_ABAR + 72);
            mbar_wait_c(sbase + SM_XBAR + 24, 0);
            if (__builtin_expect(lds32(sbase + SM_MISC + 4) != 0, 0)) { slow_bin(x, ea, src, dst, wa, wb, wc, wu, wv, out, E, node0, nn, 384); return; }
            WS(6);
        }
        const uint64_t wcd = __reduce_or_sync(~0u, (((sbase + SM_WC) & 0x3FFFF) >> 4) | (8u << 16)) | EDHI;
        const uint32_t bar0 = __reduce_or_sync(~0u, sbase + SM_BARS + wg * 96);
        const uint32_t xd0 = __reduce_or_sync(~0u, (((sbase + SM_XS + wg * NSTAGE * XS_BYTES) & 0x3FFFF) >> 4) | (1u << 16));
        const uint32_t ed0 = __reduce_or_sync(~0u, (((sbase + SM_ES + wg * NSTAGE * ES_BYTES) & 0x3FFFF) >> 4) | (8u << 16));
        const uint64_t ohd = __reduce_or_sync(~0u, (((sbase + SM_OH) & 0x3FFFF) >> 4) | (8u << 16));
        const uint32_t tabx = __reduce_or_sync(~0u, sbase + SM_TAB);
        const uint32_t bars = __reduce_or_sync(~0u, 2 * bar0 + 48), xds = __reduce_or_sync(~0u, 2 * xd0 + XS_BYTES / 16), eds = __reduce_or_sync(~0u, 2 * ed0 + ES_BYTES / 16);
        uint32_t bar = bar0, xd = xd0, ed = ed0, ph = 0, code, w1, ta, pta = NONE * 128 + c2;
        float pn0 = 0.f, pd0 = 1.f, pn1 = 0.f, pd1 = 1.f;
        uint2 ni = tile_info(lds32(sbase + SM_TINFO + wg * 32 + t * 8 + 4));
        auto fetch_a = [&]() {
            ta = (ni.x & 0xFFFFu) ^ c2;
            wf[36] = lds32(tabx + ta); wf[39] = lds32(tabx + ta);
            code = __reduce_or_sync(~0u, ni.y);
        };
        auto emit = [&]() { sts32(tabx + pta, pack_bf16(pn0 * rcpf(pd0), pn1 * rcpf(pd1))); };
        auto carry = [&]() {
            if (w1 & C_CONT) { pn0 += cyr.x; pd0 += cyr.y; pn1 += cyr.z; pd1 += cyr.w; }
            if (w1 & C_MORE) { cyr = make_float4(pn0, pd0 - EPS2, pn1, pd1 - EPS2); pn0 = pn1 = 0.f; pta = NONE * 128 + c2; }
        };
        auto next = [&](uint32_t fb) {
            pta = ta;
            w1 = ni.y;
            ni = lds64(fb + 16 + t8);
        };
        fetch_a();
        while (true) {
            switch (code & 15) {
                default: goto finished;
#define TILE(P) { \
                    float dmin; \
                    do { \
                        mbar_wait_c(bar, ph); \
                        TileMMA<P>::issue(g, h, wf, xd | (0x40000040ull << 32), ed | EDHI, ohd, wcd); \
                        const uint32_t eb = bar + 8; \
                        ph ^= bar != bar0; bar = bars - bar; xd = xds - xd; ed = eds - ed; \
                          \
                        asm volatile("{\n.reg .pred p;\nsetp.eq.u32 p, %0, 77;\n@p trap;\n}" :: "r"(xds) : "memory"); \
                        emit(); next(eb - 8); \
                        TileMMA<P>::wait_g(g); fetch_a(); TileMMA<P>::wait_h(h); \
                        mbar_arrive(eb); \
                        float m1; \
                        asm("set.gt.f32.f32 %0, %1, 0f0000007F;" : "=f"(m1) : "f"(__uint_as_float(w1))); \
                        epi_fast<P>(g, h, m1, __uint_as_float(w1), pn0, pd0, pn1, pd1, dmin); \
                    } while (!(__any_sync(~0u, dmin < TAU * 2 * P) | ((code & 31) != P))); \
                    if (__builtin_expect(__any_sync(~0u, (int)w1 < 0 || dmin < TAU * 2 * P), 0)) { \
                        int dv; \
                        if (unpad(w1, P, g[P > 1 ? 4 * P - 7 : 0], g[P > 1 ? 4 * P - 5 : 0], pd0, pd1, dv)) { \
                            FBT(2); \
                            epi_dump<P>(g, h, lgh); \
                            FBT(3); \
                            const float4 r = epi_exact(lgh, P, dv); \
                            pn0 = r.x; pd0 = r.y; pn1 = r.z; pd1 = r.w; \
                            if (pd0 != 77.f) FBT(4); \
                        } \
                    } \
                    if (code & C_BRK) { carry(); if (P != 11 && (code & 15) == P) goto L##P; } \
                    if (P == 11) {         \
                        const uint32_t a = tabx + (SM_WC - SM_TAB) + (c2 & 0x60) * 16 + (c2 & 0x1C) * 8 + (t8 >> 1), sw = c2 & 16; \
                        wf[16] = lds32(a + sw); wf[17] = lds32(a + 256 + sw); wf[18] = lds32(a + (sw ^ 16)); wf[19] = lds32(a + 256 + (sw ^ 16)); \
                    } }
#define CASE(P, UP, DN) case P: L##P: TILE(P) \
                    if (P > NPMIN && (code & 15) == P - 1) goto L##DN; \
                    if ((code & 15) == UP) goto L##UP; \
                    break;
                CASE(11, 11, 10) CASE(10, 11, 9) CASE(9, 10, 8) CASE(8, 9, 7) CASE(7, 8, 6) CASE(6, 7, 5) CASE(5, 6, 4) CASE(4, 5, 4)
#undef CASE
#undef TILE
            }
        }
finished:
        emit();
        __syncwarp();
        if (lane == 0) mbar_arrive(sbase + SM_ABAR + 48 + wg * 8);
        }
    }
    WS(17); WG1();
}

}

extern "C" void kernel_launch(void* const* d_in, const int* in_sizes, int n_in, void* d_out, int out_size) {
    const __nv_bfloat16* x = (const __nv_bfloat16*)d_in[0];
    const __nv_bfloat16* ea = (const __nv_bfloat16*)d_in[1];
    const int* src = (const int*)d_in[2];
    const int* dst = (const int*)d_in[3];
    const __nv_bfloat16* wa = (const __nv_bfloat16*)d_in[4];
    const __nv_bfloat16* wb = (const __nv_bfloat16*)d_in[5];
    const __nv_bfloat16* wc = (const __nv_bfloat16*)d_in[6];
    const __nv_bfloat16* wu = (const __nv_bfloat16*)d_in[7];
    const __nv_bfloat16* wv = (const __nv_bfloat16*)d_in[8];
    __nv_bfloat16* out = (__nv_bfloat16*)d_out;
    int N = in_sizes[0] / 64, E = in_sizes[2];
    static int sms = 0;
    static CUtensorMap tm2;
    static bool tm_ok = false;
    typedef CUresult (*EncFn)(CUtensorMap*, CUtensorMapDataType, cuuint32_t, void*, const cuuint64_t*, const cuuint64_t*, const cuuint32_t*,
                              const cuuint32_t*, CUtensorMapInterleave, CUtensorMapSwizzle, CUtensorMapL2promotion, CUtensorMapFloatOOBfill);
    static void* fn = nullptr;
    static void* gp = nullptr; static void* gb = nullptr;
    if (!sms) {
        cudaDeviceGetAttribute(&sms, cudaDevAttrMultiProcessorCount, 0);
        cudaDriverEntryPointQueryResult qr;
        cudaGetDriverEntryPoint("cuTensorMapEncodeTiled", &fn, cudaEnableDefault, &qr);
        cudaGetSymbolAddress(&gp, g_str); cudaGetSymbolAddress(&gb, g_bar);
        if (fn && gp && gb) {
            const cuuint32_t rows = sms < NB_MAX ? sms : NB_MAX;
            cuuint64_t g2[2] = {(P1B + P2B) / 4, NB_MAX}, gs[1] = {P1B + P2B};
            cuuint32_t b2[2] = {CE, rows}, es[2] = {1, 1};
            tm_ok = ((EncFn)fn)(&tm2, CU_TENSOR_MAP_DATA_TYPE_UINT32, 2, gp, g2, gs, b2, es, CU_TENSOR_MAP_INTERLEAVE_NONE, CU_TENSOR_MAP_SWIZZLE_NONE,
                                CU_TENSOR_MAP_L2_PROMOTION_NONE, CU_TENSOR_MAP_FLOAT_OOB_FILL_NONE) == CUDA_SUCCESS;
        }
        cudaFuncSetAttribute(gcn_kernel<true>, cudaFuncAttributeMaxDynamicSharedMemorySize, SMEM_LAUNCH);
        cudaFuncSetAttribute(gcn_kernel<false>, cudaFuncAttributeMaxDynamicSharedMemorySize, SMEM_LAUNCH);
    }
    auto rows = [&](CUtensorMap* tm, const void* base, uint64_t n, uint32_t box) {
        cuuint64_t gd[2] = {64, n}, gs[1] = {128};
        cuuint32_t bx[2] = {64, box}, es[2] = {1, 1};
        return ((EncFn)fn)(tm, CU_TENSOR_MAP_DATA_TYPE_BFLOAT16, 2, (void*)base, gd, gs, bx, es, CU_TENSOR_MAP_INTERLEAVE_NONE, CU_TENSOR_MAP_SWIZZLE_128B,
                           CU_TENSOR_MAP_L2_PROMOTION_NONE, CU_TENSOR_MAP_FLOAT_OOB_FILL_NONE) == CUDA_SUCCESS;
    };
    const uintptr_t wp[4] = {(uintptr_t)wa, (uintptr_t)wb, (uintptr_t)wu, (uintptr_t)wv};
    uintptr_t w0 = wp[0], w1 = wp[0], wal = 0;
    for (int i = 1; i < 4; i++) { w0 = wp[i] < w0 ? wp[i] : w0; w1 = wp[i] > w1 ? wp[i] : w1; wal |= wp[i] - wp[0]; }
    int4 wrow = make_int4((int)((wp[0] - w0) >> 7), (int)((wp[1] - w0) >> 7), (int)((wp[2] - w0) >> 7), (int)((wp[3] - w0) >> 7));
    CUtensorMap tmw, tmc, tmx;
    const bool maps = tm_ok && N > 0 && !(wal & 127) && ((w1 - w0) >> 7) < (1u << 30) && rows(&tmw, (void*)w0, ((w1 - w0) >> 7) + 64, 64) && rows(&tmc, wc, 16, 16) && rows(&tmx, x, N, 128);
    int nb = sms < NB_MAX ? sms : NB_MAX;
    int npb = (N + nb - 1) / nb;
    int ch = (((E + nb - 1) / nb) + 3) & ~3;
    if (!maps || npb > NPB_MAX || ch > CH_MAX || (E & 3) || N > 65535 || npb < 2 || (((uintptr_t)src | (uintptr_t)dst | (uintptr_t)wa | (uintptr_t)wb | (uintptr_t)wc | (uintptr_t)wu | (uintptr_t)wv) & 15)) {
        int g = 1024, p = (N + g - 1) / g;
        slow_kernel<<<g, 256>>>(x, ea, src, dst, wa, wb, wc, wu, wv, out, N, E, p < 1 ? 1 : p);
        return;
    }
    uint32_t magic = (uint32_t)((1ull << 32) / (uint32_t)npb) + 1u;
    void* args[] = {&dst, &gb, &gp, &src, &E, &ch, &N, &npb, &magic, &x, &ea, &wa, &wb, &wc, &wu, &wv, &out, &wrow, &tm2, &tmw, &tmc, &tmx};
    const bool lo32 = ((uintptr_t)x >> 32) == (((uintptr_t)x + (size_t)N * 128 - 1) >> 32) && ((uintptr_t)ea >> 32) == (((uintptr_t)ea + (size_t)E * 32 - 1) >> 32);
    cudaLaunchCooperativeKernel(lo32 && !FORCE64 ? (const void*)gcn_kernel<true> : (const void*)gcn_kernel<false>, dim3(nb), dim3(THREADS), args, SMEM_LAUNCH, cudaStreamPerThread);
}
```

```cpp
#include <cuda_runtime.h>
#include <cuda.h>
#include <cuda_bf16.h>
#include <stdint.h>

namespace {

constexpr int N_MAX = 65536;
constexpr int NPMIN = 4;
constexpr int NPMAX = 11;
constexpr int THREADS = 512;
constexpr int EPT = 12;
constexpr int CH_MAX = THREADS * EPT;
constexpr int NB_MAX = 134;
constexpr int GAL = 128;
constexpr int CE = 64;
constexpr int P1B = (256 + NB_MAX * CE * 2 + GAL - 1) / GAL * GAL;
constexpr int P2B = (256 + NB_MAX * CE * 4 + GAL - 1) / GAL * GAL;
constexpr int NPB_MAX = 384;
constexpr int SLOT_CAP = 6784;
constexpr int TILE_CAP = 124;
constexpr int TILE_X = 8;
constexpr int NCLS = 64;
constexpr int XCAP = 128;
constexpr int NSTAGE = 2;
constexpr int TR = 2;
constexpr float LOG2E = 1.4426950408889634f;

__device__ __align__(128) uint4 g_str[NB_MAX * (P1B + P2B) / 16];
__device__ __align__(128) unsigned g_bar[32];
__device__ float g_slow[N_MAX * 128];

#define WS(k)
#define WGD()
#define FBT(k)
#define WSP(k)
#define WSL(k)
#define WSG(k)
#define WG0()
#define WG1()
#define SMEM_LAUNCH SMEM_BYTES
#define FORCE64 0
#define EDHI ((16ull << 32) | (3ull << 62))
template<int NP> struct TileMMA;
template<> struct TileMMA<4> {
  static __device__ __forceinline__ void issue(float* g, float* h, const uint32_t* w, uint64_t dx, uint64_t de, uint64_t dh, uint64_t dc) {
    asm volatile(
      "{\n.reg .b64 dx1, dx2, dx3;\n"
      "add.s64 dx1, %72, 2;\nadd.s64 dx2, %72, 4;\nadd.s64 dx3, %72, 6;\n"
      "wgmma.fence.sync.aligned;\n"
      "wgmma.mma_async.sync.aligned.m64n32k16.f32.bf16.bf16 {%0, %1, %2, %3, %4, %5, %6, %7, %8, %9, %10, %11, %12, %13, %14, %15}, {%68, %69, %70, %71}, %74, 0, 1, 1, 0;\n"
      "wgmma.mma_async.sync.aligned.m64n32k16.f32.bf16.bf16 {%0, %1, %2, %3, %4, %5, %6, %7, %8, %9, %10, %11, %12, %13, %14, %15}, {%48, %49, %50, %51}, %73, 1, 1, 1, 0;\n"
      "wgmma.mma_async.sync.aligned.m64n32k16.f32.bf16.bf16 {%0, %1, %2, %3, %4, %5, %6, %7, %8, %9, %10, %11, %12, %13, %14, %15}, {%32, %33, %34, %35}, %72, 1, 1, 1, 0;\n"
      "wgmma.mma_async.sync.aligned.m64n32k16.f32.bf16.bf16 {%0, %1, %2, %3, %4, %5, %6, %7, %8, %9, %10, %11, %12, %13, %14, %15}, {%36, %37, %38, %39}, dx1, 1, 1, 1, 0;\n"
      "wgmma.mma_async.sync.aligned.m64n32k16.f32.bf16.bf16 {%0, %1, %2, %3, %4, %5, %6, %7, %8, %9, %10, %11, %12, %13, %14, %15}, {%40, %41, %42, %43}, dx2, 1, 1, 1, 0;\n"
      "wgmma.mma_async.sync.aligned.m64n32k16.f32.bf16.bf16 {%0, %1, %2, %3, %4, %5, %6, %7, %8, %9, %10, %11, %12, %13, %14, %15}, {%44, %45, %46, %47}, dx3, 1, 1, 1, 0;\n"
      "wgmma.commit_group.sync.aligned;\n"
      "wgmma.mma_async.sync.aligned.m64n32k16.f32.bf16.bf16 {%16, %17, %18, %19, %20, %21, %22, %23, %24, %25, %26, %27, %28, %29, %30, %31}, {%52, %53, %54, %55}, %72, 0, 1, 1, 0;\n"
      "wgmma.mma_async.sync.aligned.m64n32k16.f32.bf16.bf16 {%16, %17, %18, %19, %20, %21, %22, %23, %24, %25, %26, %27, %28, %29, %30, %31}, {%56, %57, %58, %59}, dx1, 1, 1, 1, 0;\n"
      "wgmma.mma_async.sync.aligned.m64n32k16.f32.bf16.bf16 {%16, %17, %18, %19, %20, %21, %22, %23, %24, %25, %26, %27, %28, %29, %30, %31}, {%60, %61, %62, %63}, dx2, 1, 1, 1, 0;\n"
      "wgmma.mma_async.sync.aligned.m64n32k16.f32.bf16.bf16 {%16, %17, %18, %19, %20, %21, %22, %23, %24, %25, %26, %27, %28, %29, %30, %31}, {%64, %65, %66, %67}, dx3, 1, 1, 1, 0;\n"
      "wgmma.commit_group.sync.aligned;\n}\n"
      : "=f"(g[0]), "=f"(g[1]), "=f"(g[2]), "=f"(g[3]), "=f"(g[4]), "=f"(g[5]), "=f"(g[6]), "=f"(g[7]), "=f"(g[8]), "=f"(g[9]), "=f"(g[10]), "=f"(g[11]), "=f"(g[12]), "=f"(g[13]), "=f"(g[14]), "=f"(g[15]),
        "=f"(h[0]), "=f"(h[1]), "=f"(h[2]), "=f"(h[3]), "=f"(h[4]), "=f"(h[5]), "=f"(h[6]), "=f"(h[7]), "=f"(h[8]), "=f"(h[9]), "=f"(h[10]), "=f"(h[11]), "=f"(h[12]), "=f"(h[13]), "=f"(h[14]), "=f"(h[15])
      : "r"(w[0]), "r"(w[1]), "r"(w[2]), "r"(w[3]), "r"(w[4]), "r"(w[5]), "r"(w[6]), "r"(w[7]), "r"(w[8]), "r"(w[9]), "r"(w[10]), "r"(w[11]), "r"(w[12]), "r"(w[13]), "r"(w[14]), "r"(w[15]), "r"(w[16]), "r"(w[17]), "r"(w[18]), "r"(w[19]), "r"(w[20]), "r"(w[21]), "r"(w[22]), "r"(w[23]), "r"(w[24]), "r"(w[25]), "r"(w[26]), "r"(w[27]), "r"(w[28]), "r"(w[29]), "r"(w[30]), "r"(w[31]), "r"(w[32]), "r"(w[33]), "r"(w[34]), "r"(w[35]), "r"(w[36]), "r"(w[37]), "r"(w[38]), "r"(w[39]), "l"(dx), "l"(de), "l"(dh)
      : "memory");
  }
  static __device__ __forceinline__ void wait_g(float* g) {
    asm volatile("wgmma.wait_group.sync.aligned 1;\n"
      : "+f"(g[0]), "+f"(g[1]), "+f"(g[2]), "+f"(g[3]), "+f"(g[4]), "+f"(g[5]), "+f"(g[6]), "+f"(g[7]), "+f"(g[8]), "+f"(g[9]), "+f"(g[10]), "+f"(g[11]), "+f"(g[12]), "+f"(g[13]), "+f"(g[14]), "+f"(g[15])
      :: "memory");
  }
  static __device__ __forceinline__ void wait_h(float* h) {
    asm volatile("wgmma.wait_group.sync.aligned 0;\n"
      : "+f"(h[0]), "+f"(h[1]), "+f"(h[2]), "+f"(h[3]), "+f"(h[4]), "+f"(h[5]), "+f"(h[6]), "+f"(h[7]), "+f"(h[8]), "+f"(h[9]), "+f"(h[10]), "+f"(h[11]), "+f"(h[12]), "+f"(h[13]), "+f"(h[14]), "+f"(h[15])
      :: "memory");
  }
};
template<> struct TileMMA<5> {
  static __device__ __forceinline__ void issue(float* g, float* h, const uint32_t* w, uint64_t dx, uint64_t de, uint64_t dh, uint64_t dc) {
    asm volatile(
      "{\n.reg .b64 dx1, dx2, dx3;\n"
      "add.s64 dx1, %80, 2;\nadd.s64 dx2, %80, 4;\nadd.s64 dx3, %80, 6;\n"
      "wgmma.fence.sync.aligned;\n"
      "wgmma.mma_async.sync.aligned.m64n40k16.f32.bf16.bf16 {%0, %1, %2, %3, %4, %5, %6, %7, %8, %9, %10, %11, %12, %13, %14, %15, %16, %17, %18, %19}, {%76, %77, %78, %79}, %82, 0, 1, 1, 0;\n"
      "wgmma.mma_async.sync.aligned.m64n40k16.f32.bf16.bf16 {%0, %1, %2, %3, %4, %5, %6, %7, %8, %9, %10, %11, %12, %13, %14, %15, %16, %17, %18, %19}, {%56, %57, %58, %59}, %81, 1, 1, 1, 0;\n"
      "wgmma.mma_async.sync.aligned.m64n40k16.f32.bf16.bf16 {%0, %1, %2, %3, %4, %5, %6, %7, %8, %9, %10, %11, %12, %13, %14, %15, %16, %17, %18, %19}, {%40, %41, %42, %43}, %80, 1, 1, 1, 0;\n"
      "wgmma.mma_async.sync.aligned.m64n40k16.f32.bf16.bf16 {%0, %1, %2, %3, %4, %5, %6, %7, %8, %9, %10, %11, %12, %13, %14, %15, %16, %17, %18, %19}, {%44, %45, %46, %47}, dx1, 1, 1, 1, 0;\n"
      "wgmma.mma_async.sync.aligned.m64n40k16.f32.bf16.bf16 {%0, %1, %2, %3, %4, %5, %6, %7, %8, %9, %10, %11, %12, %13, %14, %15, %16, %17, %18, %19}, {%48, %49, %50, %51}, dx2, 1, 1, 1, 0;\n"
      "wgmma.mma_async.sync.aligned.m64n40k16.f32.bf16.bf16 {%0, %1, %2, %3, %4, %5, %6, %7, %8, %9, %10, %11, %12, %13, %14, %15, %16, %17, %18, %19}, {%52, %53, %54, %55}, dx3, 1, 1, 1, 0;\n"
      "wgmma.commit_group.sync.aligned;\n"
      "wgmma.mma_async.sync.aligned.m64n40k16.f32.bf16.bf16 {%20, %21, %22, %23, %24, %25, %26, %27, %28, %29, %30, %31, %32, %33, %34, %35, %36, %37, %38, %39}, {%60, %61, %62, %63}, %80, 0, 1, 1, 0;\n"
      "wgmma.mma_async.sync.aligned.m64n40k16.f32.bf16.bf16 {%20, %21, %22, %23, %24, %25, %26, %27, %28, %29, %30, %31, %32, %33, %34, %35, %36, %37, %38, %39}, {%64, %65, %66, %67}, dx1, 1, 1, 1, 0;\n"
      "wgmma.mma_async.sync.aligned.m64n40k16.f32.bf16.bf16 {%20, %21, %22, %23, %24, %25, %26, %27, %28, %29, %30, %31, %32, %33, %34, %35, %36, %37, %38, %39}, {%68, %69, %70, %71}, dx2, 1, 1, 1, 0;\n"
      "wgmma.mma_async.sync.aligned.m64n40k16.f32.bf16.bf16 {%20, %21, %22, %23, %24, %25, %26, %27, %28, %29, %30, %31, %32, %33, %34, %35, %36, %37, %38, %39}, {%72, %73, %74, %75}, dx3, 1, 1, 1, 0;\n"
      "wgmma.commit_group.sync.aligned;\n}\n"
      : "=f"(g[0]), "=f"(g[1]), "=f"(g[2]), "=f"(g[3]), "=f"(g[4]), "=f"(g[5]), "=f"(g[6]), "=f"(g[7]), "=f"(g[8]), "=f"(g[9]), "=f"(g[10]), "=f"(g[11]), "=f"(g[12]), "=f"(g[13]), "=f"(g[14]), "=f"(g[15]), "=f"(g[16]), "=f"(g[17]), "=f"(g[18]), "=f"(g[19]),
        "=f"(h[0]), "=f"(h[1]), "=f"(h[2]), "=f"(h[3]), "=f"(h[4]), "=f"(h[5]), "=f"(h[6]), "=f"(h[7]), "=f"(h[8]), "=f"(h[9]), "=f"(h[10]), "=f"(h[11]), "=f"(h[12]), "=f"(h[13]), "=f"(h[14]), "=f"(h[15]), "=f"(h[16]), "=f"(h[17]), "=f"(h[18]), "=f"(h[19])
      : "r"(w[0]), "r"(w[1]), "r"(w[2]), "r"(w[3]), "r"(w[4]), "r"(w[5]), "r"(w[6]), "r"(w[7]), "r"(w[8]), "r"(w[9]), "r"(w[10]), "r"(w[11]), "r"(w[12]), "r"(w[13]), "r"(w[14]), "r"(w[15]), "r"(w[16]), "r"(w[17]), "r"(w[18]), "r"(w[19]), "r"(w[20]), "r"(w[21]), "r"(w[22]), "r"(w[23]), "r"(w[24]), "r"(w[25]), "r"(w[26]), "r"(w[27]), "r"(w[28]), "r"(w[29]), "r"(w[30]), "r"(w[31]), "r"(w[32]), "r"(w[33]), "r"(w[34]), "r"(w[35]), "r"(w[36]), "r"(w[37]), "r"(w[38]), "r"(w[39]), "l"(dx), "l"(de), "l"(dh)
      : "memory");
  }
  static __device__ __forceinline__ void wait_g(float* g) {
    asm volatile("wgmma.wait_group.sync.aligned 1;\n"
      : "+f"(g[0]), "+f"(g[1]), "+f"(g[2]), "+f"(g[3]), "+f"(g[4]), "+f"(g[5]), "+f"(g[6]), "+f"(g[7]), "+f"(g[8]), "+f"(g[9]), "+f"(g[10]), "+f"(g[11]), "+f"(g[12]), "+f"(g[13]), "+f"(g[14]), "+f"(g[15]), "+f"(g[16]), "+f"(g[17]), "+f"(g[18]), "+f"(g[19])
      :: "memory");
  }
  static __device__ __forceinline__ void wait_h(float* h) {
    asm volatile("wgmma.wait_group.sync.aligned 0;\n"
      : "+f"(h[0]), "+f"(h[1]), "+f"(h[2]), "+f"(h[3]), "+f"(h[4]), "+f"(h[5]), "+f"(h[6]), "+f"(h[7]), "+f"(h[8]), "+f"(h[9]), "+f"(h[10]), "+f"(h[11]), "+f"(h[12]), "+f"(h[13]), "+f"(h[14]), "+f"(h[15]), "+f"(h[16]), "+f"(h[17]), "+f"(h[18]), "+f"(h[19])
      :: "memory");
  }
};
template<> struct TileMMA<6> {
  static __device__ __forceinline__ void issue(float* g, float* h, const uint32_t* w, uint64_t dx, uint64_t de, uint64_t dh, uint64_t dc) {
    asm volatile(
      "{\n.reg .b64 dx1, dx2, dx3;\n"
      "add.s64 dx1, %88, 2;\nadd.s64 dx2, %88, 4;\nadd.s64 dx3, %88, 6;\n"
      "wgmma.fence.sync.aligned;\n"
      "wgmma.mma_async.sync.aligned.m64n48k16.f32.bf16.bf16 {%0, %1, %2, %3, %4, %5, %6, %7, %8, %9, %10, %11, %12, %13, %14, %15, %16, %17, %18, %19, %20, %21, %22, %23}, {%84, %85, %86, %87}, %90, 0, 1, 1, 0;\n"
      "wgmma.mma_async.sync.aligned.m64n48k16.f32.bf16.bf16 {%0, %1, %2, %3, %4, %5, %6, %7, %8, %9, %10, %11, %12, %13, %14, %15, %16, %17, %18, %19, %20, %21, %22, %23}, {%64, %65, %66, %67}, %89, 1, 1, 1, 0;\n"
      "wgmma.mma_async.sync.aligned.m64n48k16.f32.bf16.bf16 {%0, %1, %2, %3, %4, %5, %6, %7, %8, %9, %10, %11, %12, %13, %14, %15, %16, %17, %18, %19, %20, %21, %22, %23}, {%48, %49, %50, %51}, %88, 1, 1, 1, 0;\n"
      "wgmma.mma_async.sync.aligned.m64n48k16.f32.bf16.bf16 {%0, %1, %2, %3, %4, %5, %6, %7, %8, %9, %10, %11, %12, %13, %14, %15, %16, %17, %18, %19, %20, %21, %22, %23}, {%52, %53, %54, %55}, dx1, 1, 1, 1, 0;\n"
      "wgmma.mma_async.sync.aligned.m64n48k16.f32.bf16.bf16 {%0, %1, %2, %3, %4, %5, %6, %7, %8, %9, %10, %11, %12, %13, %14, %15, %16, %17, %18, %19, %20, %21, %22, %23}, {%56, %57, %58, %59}, dx2, 1, 1, 1, 0;\n"
      "wgmma.mma_async.sync.aligned.m64n48k16.f32.bf16.bf16 {%0, %1, %2, %3, %4, %5, %6, %7, %8, %9, %10, %11, %12, %13, %14, %15, %16, %17, %18, %19, %20, %21, %22, %23}, {%60, %61, %62, %63}, dx3, 1, 1, 1, 0;\n"
      "wgmma.commit_group.sync.aligned;\n"
      "wgmma.mma_async.sync.aligned.m64n48k16.f32.bf16.bf16 {%24, %25, %26, %27, %28, %29, %30, %31, %32, %33, %34, %35, %36, %37, %38, %39, %40, %41, %42, %43, %44, %45, %46, %47}, {%68, %69, %70, %71}, %88, 0, 1, 1, 0;\n"
      "wgmma.mma_async.sync.aligned.m64n48k16.f32.bf16.bf16 {%24, %25, %26, %27, %28, %29, %30, %31, %32, %33, %34, %35, %36, %37, %38, %39, %40, %41, %42, %43, %44, %45, %46, %47}, {%72, %73, %74, %75}, dx1, 1, 1, 1, 0;\n"
      "wgmma.mma_async.sync.aligned.m64n48k16.f32.bf16.bf16 {%24, %25, %26, %27, %28, %29, %30, %31, %32, %33, %34, %35, %36, %37, %38, %39, %40, %41, %42, %43, %44, %45, %46, %47}, {%76, %77, %78, %79}, dx2, 1, 1, 1, 0;\n"
      "wgmma.mma_async.sync.aligned.m64n48k16.f32.bf16.bf16 {%24, %25, %26, %27, %28, %29, %30, %31, %32, %33, %34, %35, %36, %37, %38, %39, %40, %41, %42, %43, %44, %45, %46, %47}, {%80, %81, %82, %83}, dx3, 1, 1, 1, 0;\n"
      "wgmma.commit_group.sync.aligned;\n}\n"
      : "=f"(g[0]), "=f"(g[1]), "=f"(g[2]), "=f"(g[3]), "=f"(g[4]), "=f"(g[5]), "=f"(g[6]), "=f"(g[7]), "=f"(g[8]), "=f"(g[9]), "=f"(g[10]), "=f"(g[11]), "=f"(g[12]), "=f"(g[13]), "=f"(g[14]), "=f"(g[15]), "=f"(g[16]), "=f"(g[17]), "=f"(g[18]), "=f"(g[19]), "=f"(g[20]), "=f"(g[21]), "=f"(g[22]), "=f"(g[23]),
        "=f"(h[0]), "=f"(h[1]), "=f"(h[2]), "=f"(h[3]), "=f"(h[4]), "=f"(h[5]), "=f"(h[6]), "=f"(h[7]), "=f"(h[8]), "=f"(h[9]), "=f"(h[10]), "=f"(h[11]), "=f"(h[12]), "=f"(h[13]), "=f"(h[14]), "=f"(h[15]), "=f"(h[16]), "=f"(h[17]), "=f"(h[18]), "=f"(h[19]), "=f"(h[20]), "=f"(h[21]), "=f"(h[22]), "=f"(h[23])
      : "r"(w[0]), "r"(w[1]), "r"(w[2]), "r"(w[3]), "r"(w[4]), "r"(w[5]), "r"(w[6]), "r"(w[7]), "r"(w[8]), "r"(w[9]), "r"(w[10]), "r"(w[11]), "r"(w[12]), "r"(w[13]), "r"(w[14]), "r"(w[15]), "r"(w[16]), "r"(w[17]), "r"(w[18]), "r"(w[19]), "r"(w[20]), "r"(w[21]), "r"(w[22]), "r"(w[23]), "r"(w[24]), "r"(w[25]), "r"(w[26]), "r"(w[27]), "r"(w[28]), "r"(w[29]), "r"(w[30]), "r"(w[31]), "r"(w[32]), "r"(w[33]), "r"(w[34]), "r"(w[35]), "r"(w[36]), "r"(w[37]), "r"(w[38]), "r"(w[39]), "l"(dx), "l"(de), "l"(dh)
      : "memory");
  }
  static __device__ __forceinline__ void wait_g(float* g) {
    asm volatile("wgmma.wait_group.sync.aligned 1;\n"
      : "+f"(g[0]), "+f"(g[1]), "+f"(g[2]), "+f"(g[3]), "+f"(g[4]), "+f"(g[5]), "+f"(g[6]), "+f"(g[7]), "+f"(g[8]), "+f"(g[9]), "+f"(g[10]), "+f"(g[11]), "+f"(g[12]), "+f"(g[13]), "+f"(g[14]), "+f"(g[15]), "+f"(g[16]), "+f"(g[17]), "+f"(g[18]), "+f"(g[19]), "+f"(g[20]), "+f"(g[21]), "+f"(g[22]), "+f"(g[23])
      :: "memory");
  }
  static __device__ __forceinline__ void wait_h(float* h) {
    asm volatile("wgmma.wait_group.sync.aligned 0;\n"
      : "+f"(h[0]), "+f"(h[1]), "+f"(h[2]), "+f"(h[3]), "+f"(h[4]), "+f"(h[5]), "+f"(h[6]), "+f"(h[7]), "+f"(h[8]), "+f"(h[9]), "+f"(h[10]), "+f"(h[11]), "+f"(h[12]), "+f"(h[13]), "+f"(h[14]), "+f"(h[15]), "+f"(h[16]), "+f"(h[17]), "+f"(h[18]), "+f"(h[19]), "+f"(h[20]), "+f"(h[21]), "+f"(h[22]), "+f"(h[23])
      :: "memory");
  }
};
template<> struct TileMMA<7> {
  static __device__ __forceinline__ void issue(float* g, float* h, const uint32_t* w, uint64_t dx, uint64_t de, uint64_t dh, uint64_t dc) {
    asm volatile(
      "{\n.reg .b64 dx1, dx2, dx3;\n"
      "add.s64 dx1, %96, 2;\nadd.s64 dx2, %96, 4;\nadd.s64 dx3, %96, 6;\n"
      "wgmma.fence.sync.aligned;\n"
      "wgmma.mma_async.sync.aligned.m64n56k16.f32.bf16.bf16 {%0, %1, %2, %3, %4, %5, %6, %7, %8, %9, %10, %11, %12, %13, %14, %15, %16, %17, %18, %19, %20, %21, %22, %23, %24, %25, %26, %27}, {%92, %93, %94, %95}, %98, 0, 1, 1, 0;\n"
      "wgmma.mma_async.sync.aligned.m64n56k16.f32.bf16.bf16 {%0, %1, %2, %3, %4, %5, %6, %7, %8, %9, %10, %11, %12, %13, %14, %15, %16, %17, %18, %19, %20, %21, %22, %23, %24, %25, %26, %27}, {%72, %73, %74, %75}, %97, 1, 1, 1, 0;\n"
      "wgmma.mma_async.sync.aligned.m64n56k16.f32.bf16.bf16 {%0, %1, %2, %3, %4, %5, %6, %7, %8, %9, %10, %11, %12, %13, %14, %15, %16, %17, %18, %19, %20, %21, %22, %23, %24, %25, %26, %27}, {%56, %57, %58, %59}, %96, 1, 1, 1, 0;\n"
      "wgmma.mma_async.sync.aligned.m64n56k16.f32.bf16.bf16 {%0, %1, %2, %3, %4, %5, %6, %7, %8, %9, %10, %11, %12, %13, %14, %15, %16, %17, %18, %19, %20, %21, %22, %23, %24, %25, %26, %27}, {%60, %61, %62, %63}, dx1, 1, 1, 1, 0;\n"
      "wgmma.mma_async.sync.aligned.m64n56k16.f32.bf16.bf16 {%0, %1, %2, %3, %4, %5, %6, %7, %8, %9, %10, %11, %12, %13, %14, %15, %16, %17, %18, %19, %20, %21, %22, %23, %24, %25, %26, %27}, {%64, %65, %66, %67}, dx2, 1, 1, 1, 0;\n"
      "wgmma.mma_async.sync.aligned.m64n56k16.f32.bf16.bf16 {%0, %1, %2, %3, %4, %5, %6, %7, %8, %9, %10, %11, %12, %13, %14, %15, %16, %17, %18, %19, %20, %21, %22, %23, %24, %25, %26, %27}, {%68, %69, %70, %71}, dx3, 1, 1, 1, 0;\n"
      "wgmma.commit_group.sync.aligned;\n"
      "wgmma.mma_async.sync.aligned.m64n56k16.f32.bf16.bf16 {%28, %29, %30, %31, %32, %33, %34, %35, %36, %37, %38, %39, %40, %41, %42, %43, %44, %45, %46, %47, %48, %49, %50, %51, %52, %53, %54, %55}, {%76, %77, %78, %79}, %96, 0, 1, 1, 0;\n"
      "wgmma.mma_async.sync.aligned.m64n56k16.f32.bf16.bf16 {%28, %29, %30, %31, %32, %33, %34, %35, %36, %37, %38, %39, %40, %41, %42, %43, %44, %45, %46, %47, %48, %49, %50, %51, %52, %53, %54, %55}, {%80, %81, %82, %83}, dx1, 1, 1, 1, 0;\n"
      "wgmma.mma_async.sync.aligned.m64n56k16.f32.bf16.bf16 {%28, %29, %30, %31, %32, %33, %34, %35, %36, %37, %38, %39, %40, %41, %42, %43, %44, %45, %46, %47, %48, %49, %50, %51, %52, %53, %54, %55}, {%84, %85, %86, %87}, dx2, 1, 1, 1, 0;\n"
      "wgmma.mma_async.sync.aligned.m64n56k16.f32.bf16.bf16 {%28, %29, %30, %31, %32, %33, %34, %35, %36, %37, %38, %39, %40, %41, %42, %43, %44, %45, %46, %47, %48, %49, %50, %51, %52, %53, %54, %55}, {%88, %89, %90, %91}, dx3, 1, 1, 1, 0;\n"
      "wgmma.commit_group.sync.aligned;\n}\n"
      : "=f"(g[0]), "=f"(g[1]), "=f"(g[2]), "=f"(g[3]), "=f"(g[4]), "=f"(g[5]), "=f"(g[6]), "=f"(g[7]), "=f"(g[8]), "=f"(g[9]), "=f"(g[10]), "=f"(g[11]), "=f"(g[12]), "=f"(g[13]), "=f"(g[14]), "=f"(g[15]), "=f"(g[16]), "=f"(g[17]), "=f"(g[18]), "=f"(g[19]), "=f"(g[20]), "=f"(g[21]), "=f"(g[22]), "=f"(g[23]), "=f"(g[24]), "=f"(g[25]), "=f"(g[26]), "=f"(g[27]),
        "=f"(h[0]), "=f"(h[1]), "=f"(h[2]), "=f"(h[3]), "=f"(h[4]), "=f"(h[5]), "=f"(h[6]), "=f"(h[7]), "=f"(h[8]), "=f"(h[9]), "=f"(h[10]), "=f"(h[11]), "=f"(h[12]), "=f"(h[13]), "=f"(h[14]), "=f"(h[15]), "=f"(h[16]), "=f"(h[17]), "=f"(h[18]), "=f"(h[19]), "=f"(h[20]), "=f"(h[21]), "=f"(h[22]), "=f"(h[23]), "=f"(h[24]), "=f"(h[25]), "=f"(h[26]), "=f"(h[27])
      : "r"(w[0]), "r"(w[1]), "r"(w[2]), "r"(w[3]), "r"(w[4]), "r"(w[5]), "r"(w[6]), "r"(w[7]), "r"(w[8]), "r"(w[9]), "r"(w[10]), "r"(w[11]), "r"(w[12]), "r"(w[13]), "r"(w[14]), "r"(w[15]), "r"(w[16]), "r"(w[17]), "r"(w[18]), "r"(w[19]), "r"(w[20]), "r"(w[21]), "r"(w[22]), "r"(w[23]), "r"(w[24]), "r"(w[25]), "r"(w[26]), "r"(w[27]), "r"(w[28]), "r"(w[29]), "r"(w[30]), "r"(w[31]), "r"(w[32]), "r"(w[33]), "r"(w[34]), "r"(w[35]), "r"(w[36]), "r"(w[37]), "r"(w[38]), "r"(w[39]), "l"(dx), "l"(de), "l"(dh)
      : "memory");
  }
  static __device__ __forceinline__ void wait_g(float* g) {
    asm volatile("wgmma.wait_group.sync.aligned 1;\n"
      : "+f"(g[0]), "+f"(g[1]), "+f"(g[2]), "+f"(g[3]), "+f"(g[4]), "+f"(g[5]), "+f"(g[6]), "+f"(g[7]), "+f"(g[8]), "+f"(g[9]), "+f"(g[10]), "+f"(g[11]), "+f"(g[12]), "+f"(g[13]), "+f"(g[14]), "+f"(g[15]), "+f"(g[16]), "+f"(g[17]), "+f"(g[18]), "+f"(g[19]), "+f"(g[20]), "+f"(g[21]), "+f"(g[22]), "+f"(g[23]), "+f"(g[24]), "+f"(g[25]), "+f"(g[26]), "+f"(g[27])
      :: "memory");
  }
  static __device__ __forceinline__ void wait_h(float* h) {
    asm volatile("wgmma.wait_group.sync.aligned 0;\n"
      : "+f"(h[0]), "+f"(h[1]), "+f"(h[2]), "+f"(h[3]), "+f"(h[4]), "+f"(h[5]), "+f"(h[6]), "+f"(h[7]), "+f"(h[8]), "+f"(h[9]), "+f"(h[10]), "+f"(h[11]), "+f"(h[12]), "+f"(h[13]), "+f"(h[14]), "+f"(h[15]), "+f"(h[16]), "+f"(h[17]), "+f"(h[18]), "+f"(h[19]), "+f"(h[20]), "+f"(h[21]), "+f"(h[22]), "+f"(h[23]), "+f"(h[24]), "+f"(h[25]), "+f"(h[26]), "+f"(h[27])
      :: "memory");
  }
};
template<> struct TileMMA<8> {
  static __device__ __forceinline__ void issue(float* g, float* h, const uint32_t* w, uint64_t dx, uint64_t de, uint64_t dh, uint64_t dc) {
    asm volatile(
      "{\n.reg .b64 dx1, dx2, dx3;\n"
      "add.s64 dx1, %104, 2;\nadd.s64 dx2, %104, 4;\nadd.s64 dx3, %104, 6;\n"
      "wgmma.fence.sync.aligned;\n"
      "wgmma.mma_async.sync.aligned.m64n64k16.f32.bf16.bf16 {%0, %1, %2, %3, %4, %5, %6, %7, %8, %9, %10, %11, %12, %13, %14, %15, %16, %17, %18, %19, %20, %21, %22, %23, %24, %25, %26, %27, %28, %29, %30, %31}, {%100, %101, %102, %103}, %106, 0, 1, 1, 0;\n"
      "wgmma.mma_async.sync.aligned.m64n64k16.f32.bf16.bf16 {%0, %1, %2, %3, %4, %5, %6, %7, %8, %9, %10, %11, %12, %13, %14, %15, %16, %17, %18, %19, %20, %21, %22, %23, %24, %25, %26, %27, %28, %29, %30, %31}, {%80, %81, %82, %83}, %105, 1, 1, 1, 0;\n"
      "wgmma.mma_async.sync.aligned.m64n64k16.f32.bf16.bf16 {%0, %1, %2, %3, %4, %5, %6, %7, %8, %9, %10, %11, %12, %13, %14, %15, %16, %17, %18, %19, %20, %21, %22, %23, %24, %25, %26, %27, %28, %29, %30, %31}, {%64, %65, %66, %67}, %104, 1, 1, 1, 0;\n"
      "wgmma.mma_async.sync.aligned.m64n64k16.f32.bf16.bf16 {%0, %1, %2, %3, %4, %5, %6, %7, %8, %9, %10, %11, %12, %13, %14, %15, %16, %17, %18, %19, %20, %21, %22, %23, %24, %25, %26, %27, %28, %29, %30, %31}, {%68, %69, %70, %71}, dx1, 1, 1, 1, 0;\n"
      "wgmma.mma_async.sync.aligned.m64n64k16.f32.bf16.bf16 {%0, %1, %2, %3, %4, %5, %6, %7, %8, %9, %10, %11, %12, %13, %14, %15, %16, %17, %18, %19, %20, %21, %22, %23, %24, %25, %26, %27, %28, %29, %30, %31}, {%72, %73, %74, %75}, dx2, 1, 1, 1, 0;\n"
      "wgmma.mma_async.sync.aligned.m64n64k16.f32.bf16.bf16 {%0, %1, %2, %3, %4, %5, %6, %7, %8, %9, %10, %11, %12, %13, %14, %15, %16, %17, %18, %19, %20, %21, %22, %23, %24, %25, %26, %27, %28, %29, %30, %31}, {%76, %77, %78, %79}, dx3, 1, 1, 1, 0;\n"
      "wgmma.commit_group.sync.aligned;\n"
      "wgmma.mma_async.sync.aligned.m64n64k16.f32.bf16.bf16 {%32, %33, %34, %35, %36, %37, %38, %39, %40, %41, %42, %43, %44, %45, %46, %47, %48, %49, %50, %51, %52, %53, %54, %55, %56, %57, %58, %59, %60, %61, %62, %63}, {%84, %85, %86, %87}, %104, 0, 1, 1, 0;\n"
      "wgmma.mma_async.sync.aligned.m64n64k16.f32.bf16.bf16 {%32, %33, %34, %35, %36, %37, %38, %39, %40, %41, %42, %43, %44, %45, %46, %47, %48, %49, %50, %51, %52, %53, %54, %55, %56, %57, %58, %59, %60, %61, %62, %63}, {%88, %89, %90, %91}, dx1, 1, 1, 1, 0;\n"
      "wgmma.mma_async.sync.aligned.m64n64k16.f32.bf16.bf16 {%32, %33, %34, %35, %36, %37, %38, %39, %40, %41, %42, %43, %44, %45, %46, %47, %48, %49, %50, %51, %52, %53, %54, %55, %56, %57, %58, %59, %60, %61, %62, %63}, {%92, %93, %94, %95}, dx2, 1, 1, 1, 0;\n"
      "wgmma.mma_async.sync.aligned.m64n64k16.f32.bf16.bf16 {%32, %33, %34, %35, %36, %37, %38, %39, %40, %41, %42, %43, %44, %45, %46, %47, %48, %49, %50, %51, %52, %53, %54, %55, %56, %57, %58, %59, %60, %61, %62, %63}, {%96, %97, %98, %99}, dx3, 1, 1, 1, 0;\n"
      "wgmma.commit_group.sync.aligned;\n}\n"
      : "=f"(g[0]), "=f"(g[1]), "=f"(g[2]), "=f"(g[3]), "=f"(g[4]), "=f"(g[5]), "=f"(g[6]), "=f"(g[7]), "=f"(g[8]), "=f"(g[9]), "=f"(g[10]), "=f"(g[11]), "=f"(g[12]), "=f"(g[13]), "=f"(g[14]), "=f"(g[15]), "=f"(g[16]), "=f"(g[17]), "=f"(g[18]), "=f"(g[19]), "=f"(g[20]), "=f"(g[21]), "=f"(g[22]), "=f"(g[23]), "=f"(g[24]), "=f"(g[25]), "=f"(g[26]), "=f"(g[27]), "=f"(g[28]), "=f"(g[29]), "=f"(g[30]), "=f"(g[31]),
        "=f"(h[0]), "=f"(h[1]), "=f"(h[2]), "=f"(h[3]), "=f"(h[4]), "=f"(h[5]), "=f"(h[6]), "=f"(h[7]), "=f"(h[8]), "=f"(h[9]), "=f"(h[10]), "=f"(h[11]), "=f"(h[12]), "=f"(h[13]), "=f"(h[14]), "=f"(h[15]), "=f"(h[16]), "=f"(h[17]), "=f"(h[18]), "=f"(h[19]), "=f"(h[20]), "=f"(h[21]), "=f"(h[22]), "=f"(h[23]), "=f"(h[24]), "=f"(h[25]), "=f"(h[26]), "=f"(h[27]), "=f"(h[28]), "=f"(h[29]), "=f"(h[30]), "=f"(h[31])
      : "r"(w[0]), "r"(w[1]), "r"(w[2]), "r"(w[3]), "r"(w[4]), "r"(w[5]), "r"(w[6]), "r"(w[7]), "r"(w[8]), "r"(w[9]), "r"(w[10]), "r"(w[11]), "r"(w[12]), "r"(w[13]), "r"(w[14]), "r"(w[15]), "r"(w[16]), "r"(w[17]), "r"(w[18]), "r"(w[19]), "r"(w[20]), "r"(w[21]), "r"(w[22]), "r"(w[23]), "r"(w[24]), "r"(w[25]), "r"(w[26]), "r"(w[27]), "r"(w[28]), "r"(w[29]), "r"(w[30]), "r"(w[31]), "r"(w[32]), "r"(w[33]), "r"(w[34]), "r"(w[35]), "r"(w[36]), "r"(w[37]), "r"(w[38]), "r"(w[39]), "l"(dx), "l"(de), "l"(dh)
      : "memory");
  }
  static __device__ __forceinline__ void wait_g(float* g) {
    asm volatile("wgmma.wait_group.sync.aligned 1;\n"
      : "+f"(g[0]), "+f"(g[1]), "+f"(g[2]), "+f"(g[3]), "+f"(g[4]), "+f"(g[5]), "+f"(g[6]), "+f"(g[7]), "+f"(g[8]), "+f"(g[9]), "+f"(g[10]), "+f"(g[11]), "+f"(g[12]), "+f"(g[13]), "+f"(g[14]), "+f"(g[15]), "+f"(g[16]), "+f"(g[17]), "+f"(g[18]), "+f"(g[19]), "+f"(g[20]), "+f"(g[21]), "+f"(g[22]), "+f"(g[23]), "+f"(g[24]), "+f"(g[25]), "+f"(g[26]), "+f"(g[27]), "+f"(g[28]), "+f"(g[29]), "+f"(g[30]), "+f"(g[31])
      :: "memory");
  }
  static __device__ __forceinline__ void wait_h(float* h) {
    asm volatile("wgmma.wait_group.sync.aligned 0;\n"
      : "+f"(h[0]), "+f"(h[1]), "+f"(h[2]), "+f"(h[3]), "+f"(h[4]), "+f"(h[5]), "+f"(h[6]), "+f"(h[7]), "+f"(h[8]), "+f"(h[9]), "+f"(h[10]), "+f"(h[11]), "+f"(h[12]), "+f"(h[13]), "+f"(h[14]), "+f"(h[15]), "+f"(h[16]), "+f"(h[17]), "+f"(h[18]), "+f"(h[19]), "+f"(h[20]), "+f"(h[21]), "+f"(h[22]), "+f"(h[23]), "+f"(h[24]), "+f"(h[25]), "+f"(h[26]), "+f"(h[27]), "+f"(h[28]), "+f"(h[29]), "+f"(h[30]), "+f"(h[31])
      :: "memory");
  }
};
template<> struct TileMMA<9> {
  static __device__ __forceinline__ void issue(float* g, float* h, const uint32_t* w, uint64_t dx, uint64_t de, uint64_t dh, uint64_t dc) {
    asm volatile(
      "{\n.reg .b64 dx1, dx2, dx3;\n"
      "add.s64 dx1, %112, 2;\nadd.s64 dx2, %112, 4;\nadd.s64 dx3, %112, 6;\n"
      "wgmma.fence.sync.aligned;\n"
      "wgmma.mma_async.sync.aligned.m64n72k16.f32.bf16.bf16 {%0, %1, %2, %3, %4, %5, %6, %7, %8, %9, %10, %11, %12, %13, %14, %15, %16, %17, %18, %19, %20, %21, %22, %23, %24, %25, %26, %27, %28, %29, %30, %31, %32, %33, %34, %35}, {%108, %109, %110, %111}, %114, 0, 1, 1, 0;\n"
      "wgmma.mma_async.sync.aligned.m64n72k16.f32.bf16.bf16 {%0, %1, %2, %3, %4, %5, %6, %7, %8, %9, %10, %11, %12, %13, %14, %15, %16, %17, %18, %19, %20, %21, %22, %23, %24, %25, %26, %27, %28, %29, %30, %31, %32, %33, %34, %35}, {%88, %89, %90, %91}, %113, 1, 1, 1, 0;\n"
      "wgmma.mma_async.sync.aligned.m64n72k16.f32.bf16.bf16 {%0, %1, %2, %3, %4, %5, %6, %7, %8, %9, %10, %11, %12, %13, %14, %15, %16, %17, %18, %19, %20, %21, %22, %23, %24, %25, %26, %27, %28, %29, %30, %31, %32, %33, %34, %35}, {%72, %73, %74, %75}, %112, 1, 1, 1, 0;\n"
      "wgmma.mma_async.sync.aligned.m64n72k16.f32.bf16.bf16 {%0, %1, %2, %3, %4, %5, %6, %7, %8, %9, %10, %11, %12, %13, %14, %15, %16, %17, %18, %19, %20, %21, %22, %23, %24, %25, %26, %27, %28, %29, %30, %31, %32, %33, %34, %35}, {%76, %77, %78, %79}, dx1, 1, 1, 1, 0;\n"
      "wgmma.mma_async.sync.aligned.m64n72k16.f32.bf16.bf16 {%0, %1, %2, %3, %4, %5, %6, %7, %8, %9, %10, %11, %12, %13, %14, %15, %16, %17, %18, %19, %20, %21, %22, %23, %24, %25, %26, %27, %28, %29, %30, %31, %32, %33, %34, %35}, {%80, %81, %82, %83}, dx2, 1, 1, 1, 0;\n"
      "wgmma.mma_async.sync.aligned.m64n72k16.f32.bf16.bf16 {%0, %1, %2, %3, %4, %5, %6, %7, %8, %9, %10, %11, %12, %13, %14, %15, %16, %17, %18, %19, %20, %21, %22, %23, %24, %25, %26, %27, %28, %29, %30, %31, %32, %33, %34, %35}, {%84, %85, %86, %87}, dx3, 1, 1, 1, 0;\n"
      "wgmma.commit_group.sync.aligned;\n"
      "wgmma.mma_async.sync.aligned.m64n72k16.f32.bf16.bf16 {%36, %37, %38, %39, %40, %41, %42, %43, %44, %45, %46, %47, %48, %49, %50, %51, %52, %53, %54, %55, %56, %57, %58, %59, %60, %61, %62, %63, %64, %65, %66, %67, %68, %69, %70, %71}, {%92, %93, %94, %95}, %112, 0, 1, 1, 0;\n"
      "wgmma.mma_async.sync.aligned.m64n72k16.f32.bf16.bf16 {%36, %37, %38, %39, %40, %41, %42, %43, %44, %45, %46, %47, %48, %49, %50, %51, %52, %53, %54, %55, %56, %57, %58, %59, %60, %61, %62, %63, %64, %65, %66, %67, %68, %69, %70, %71}, {%96, %97, %98, %99}, dx1, 1, 1, 1, 0;\n"
      "wgmma.mma_async.sync.aligned.m64n72k16.f32.bf16.bf16 {%36, %37, %38, %39, %40, %41, %42, %43, %44, %45, %46, %47, %48, %49, %50, %51, %52, %53, %54, %55, %56, %57, %58, %59, %60, %61, %62, %63, %64, %65, %66, %67, %68, %69, %70, %71}, {%100, %101, %102, %103}, dx2, 1, 1, 1, 0;\n"
      "wgmma.mma_async.sync.aligned.m64n72k16.f32.bf16.bf16 {%36, %37, %38, %39, %40, %41, %42, %43, %44, %45, %46, %47, %48, %49, %50, %51, %52, %53, %54, %55, %56, %57, %58, %59, %60, %61, %62, %63, %64, %65, %66, %67, %68, %69, %70, %71}, {%104, %105, %106, %107}, dx3, 1, 1, 1, 0;\n"
      "wgmma.commit_group.sync.aligned;\n}\n"
      : "=f"(g[0]), "=f"(g[1]), "=f"(g[2]), "=f"(g[3]), "=f"(g[4]), "=f"(g[5]), "=f"(g[6]), "=f"(g[7]), "=f"(g[8]), "=f"(g[9]), "=f"(g[10]), "=f"(g[11]), "=f"(g[12]), "=f"(g[13]), "=f"(g[14]), "=f"(g[15]), "=f"(g[16]), "=f"(g[17]), "=f"(g[18]), "=f"(g[19]), "=f"(g[20]), "=f"(g[21]), "=f"(g[22]), "=f"(g[23]), "=f"(g[24]), "=f"(g[25]), "=f"(g[26]), "=f"(g[27]), "=f"(g[28]), "=f"(g[29]), "=f"(g[30]), "=f"(g[31]), "=f"(g[32]), "=f"(g[33]), "=f"(g[34]), "=f"(g[35]),
        "=f"(h[0]), "=f"(h[1]), "=f"(h[2]), "=f"(h[3]), "=f"(h[4]), "=f"(h[5]), "=f"(h[6]), "=f"(h[7]), "=f"(h[8]), "=f"(h[9]), "=f"(h[10]), "=f"(h[11]), "=f"(h[12]), "=f"(h[13]), "=f"(h[14]), "=f"(h[15]), "=f"(h[16]), "=f"(h[17]), "=f"(h[18]), "=f"(h[19]), "=f"(h[20]), "=f"(h[21]), "=f"(h[22]), "=f"(h[23]), "=f"(h[24]), "=f"(h[25]), "=f"(h[26]), "=f"(h[27]), "=f"(h[28]), "=f"(h[29]), "=f"(h[30]), "=f"(h[31]), "=f"(h[32]), "=f"(h[33]), "=f"(h[34]), "=f"(h[35])
      : "r"(w[0]), "r"(w[1]), "r"(w[2]), "r"(w[3]), "r"(w[4]), "r"(w[5]), "r"(w[6]), "r"(w[7]), "r"(w[8]), "r"(w[9]), "r"(w[10]), "r"(w[11]), "r"(w[12]), "r"(w[13]), "r"(w[14]), "r"(w[15]), "r"(w[16]), "r"(w[17]), "r"(w[18]), "r"(w[19]), "r"(w[20]), "r"(w[21]), "r"(w[22]), "r"(w[23]), "r"(w[24]), "r"(w[25]), "r"(w[26]), "r"(w[27]), "r"(w[28]), "r"(w[29]), "r"(w[30]), "r"(w[31]), "r"(w[32]), "r"(w[33]), "r"(w[34]), "r"(w[35]), "r"(w[36]), "r"(w[37]), "r"(w[38]), "r"(w[39]), "l"(dx), "l"(de), "l"(dh)
      : "memory");
  }
  static __device__ __forceinline__ void wait_g(float* g) {
    asm volatile("wgmma.wait_group.sync.aligned 1;\n"
      : "+f"(g[0]), "+f"(g[1]), "+f"(g[2]), "+f"(g[3]), "+f"(g[4]), "+f"(g[5]), "+f"(g[6]), "+f"(g[7]), "+f"(g[8]), "+f"(g[9]), "+f"(g[10]), "+f"(g[11]), "+f"(g[12]), "+f"(g[13]), "+f"(g[14]), "+f"(g[15]), "+f"(g[16]), "+f"(g[17]), "+f"(g[18]), "+f"(g[19]), "+f"(g[20]), "+f"(g[21]), "+f"(g[22]), "+f"(g[23]), "+f"(g[24]), "+f"(g[25]), "+f"(g[26]), "+f"(g[27]), "+f"(g[28]), "+f"(g[29]), "+f"(g[30]), "+f"(g[31]), "+f"(g[32]), "+f"(g[33]), "+f"(g[34]), "+f"(g[35])
      :: "memory");
  }
  static __device__ __forceinline__ void wait_h(float* h) {
    asm volatile("wgmma.wait_group.sync.aligned 0;\n"
      : "+f"(h[0]), "+f"(h[1]), "+f"(h[2]), "+f"(h[3]), "+f"(h[4]), "+f"(h[5]), "+f"(h[6]), "+f"(h[7]), "+f"(h[8]), "+f"(h[9]), "+f"(h[10]), "+f"(h[11]), "+f"(h[12]), "+f"(h[13]), "+f"(h[14]), "+f"(h[15]), "+f"(h[16]), "+f"(h[17]), "+f"(h[18]), "+f"(h[19]), "+f"(h[20]), "+f"(h[21]), "+f"(h[22]), "+f"(h[23]), "+f"(h[24]), "+f"(h[25]), "+f"(h[26]), "+f"(h[27]), "+f"(h[28]), "+f"(h[29]), "+f"(h[30]), "+f"(h[31]), "+f"(h[32]), "+f"(h[33]), "+f"(h[34]), "+f"(h[35])
      :: "memory");
  }
};
template<> struct TileMMA<10> {
  static __device__ __forceinline__ void issue(float* g, float* h, const uint32_t* w, uint64_t dx, uint64_t de, uint64_t dh, uint64_t dc) {
    asm volatile(
      "{\n.reg .b64 dx1, dx2, dx3;\n"
      "add.s64 dx1, %120, 2;\nadd.s64 dx2, %120, 4;\nadd.s64 dx3, %120, 6;\n"
      "wgmma.fence.sync.aligned;\n"
      "wgmma.mma_async.sync.aligned.m64n80k16.f32.bf16.bf16 {%0, %1, %2, %3, %4, %5, %6, %7, %8, %9, %10, %11, %12, %13, %14, %15, %16, %17, %18, %19, %20, %21, %22, %23, %24, %25, %26, %27, %28, %29, %30, %31, %32, %33, %34, %35, %36, %37, %38, %39}, {%116, %117, %118, %119}, %122, 0, 1, 1, 0;\n"
      "wgmma.mma_async.sync.aligned.m64n80k16.f32.bf16.bf16 {%0, %1, %2, %3, %4, %5, %6, %7, %8, %9, %10, %11, %12, %13, %14, %15, %16, %17, %18, %19, %20, %21, %22, %23, %24, %25, %26, %27, %28, %29, %30, %31, %32, %33, %34, %35, %36, %37, %38, %39}, {%96, %97, %98, %99}, %121, 1, 1, 1, 0;\n"
      "wgmma.mma_async.sync.aligned.m64n80k16.f32.bf16.bf16 {%0, %1, %2, %3, %4, %5, %6, %7, %8, %9, %10, %11, %12, %13, %14, %15, %16, %17, %18, %19, %20, %21, %22, %23, %24, %25, %26, %27, %28, %29, %30, %31, %32, %33, %34, %35, %36, %37, %38, %39}, {%80, %81, %82, %83}, %120, 1, 1, 1, 0;\n"
      "wgmma.mma_async.sync.aligned.m64n80k16.f32.bf16.bf16 {%0, %1, %2, %3, %4, %5, %6, %7, %8, %9, %10, %11, %12, %13, %14, %15, %16, %17, %18, %19, %20, %21, %22, %23, %24, %25, %26, %27, %28, %29, %30, %31, %32, %33, %34, %35, %36, %37, %38, %39}, {%84, %85, %86, %87}, dx1, 1, 1, 1, 0;\n"
      "wgmma.mma_async.sync.aligned.m64n80k16.f32.bf16.bf16 {%0, %1, %2, %3, %4, %5, %6, %7, %8, %9, %10, %11, %12, %13, %14, %15, %16, %17, %18, %19, %20, %21, %22, %23, %24, %25, %26, %27, %28, %29, %30, %31, %32, %33, %34, %35, %36, %37, %38, %39}, {%88, %89, %90, %91}, dx2, 1, 1, 1, 0;\n"
      "wgmma.mma_async.sync.aligned.m64n80k16.f32.bf16.bf16 {%0, %1, %2, %3, %4, %5, %6, %7, %8, %9, %10, %11, %12, %13, %14, %15, %16, %17, %18, %19, %20, %21, %22, %23, %24, %25, %26, %27, %28, %29, %30, %31, %32, %33, %34, %35, %36, %37, %38, %39}, {%92, %93, %94, %95}, dx3, 1, 1, 1, 0;\n"
      "wgmma.commit_group.sync.aligned;\n"
      "wgmma.mma_async.sync.aligned.m64n80k16.f32.bf16.bf16 {%40, %41, %42, %43, %44, %45, %46, %47, %48, %49, %50, %51, %52, %53, %54, %55, %56, %57, %58, %59, %60, %61, %62, %63, %64, %65, %66, %67, %68, %69, %70, %71, %72, %73, %74, %75, %76, %77, %78, %79}, {%100, %101, %102, %103}, %120, 0, 1, 1, 0;\n"
      "wgmma.mma_async.sync.aligned.m64n80k16.f32.bf16.bf16 {%40, %41, %42, %43, %44, %45, %46, %47, %48, %49, %50, %51, %52, %53, %54, %55, %56, %57, %58, %59, %60, %61, %62, %63, %64, %65, %66, %67, %68, %69, %70, %71, %72, %73, %74, %75, %76, %77, %78, %79}, {%104, %105, %106, %107}, dx1, 1, 1, 1, 0;\n"
      "wgmma.mma_async.sync.aligned.m64n80k16.f32.bf16.bf16 {%40, %41, %42, %43, %44, %45, %46, %47, %48, %49, %50, %51, %52, %53, %54, %55, %56, %57, %58, %59, %60, %61, %62, %63, %64, %65, %66, %67, %68, %69, %70, %71, %72, %73, %74, %75, %76, %77, %78, %79}, {%108, %109, %110, %111}, dx2, 1, 1, 1, 0;\n"
      "wgmma.mma_async.sync.aligned.m64n80k16.f32.bf16.bf16 {%40, %41, %42, %43, %44, %45, %46, %47, %48, %49, %50, %51, %52, %53, %54, %55, %56, %57, %58, %59, %60, %61, %62, %63, %64, %65, %66, %67, %68, %69, %70, %71, %72, %73, %74, %75, %76, %77, %78, %79}, {%112, %113, %114, %115}, dx3, 1, 1, 1, 0;\n"
      "wgmma.commit_group.sync.aligned;\n}\n"
      : "=f"(g[0]), "=f"(g[1]), "=f"(g[2]), "=f"(g[3]), "=f"(g[4]), "=f"(g[5]), "=f"(g[6]), "=f"(g[7]), "=f"(g[8]), "=f"(g[9]), "=f"(g[10]), "=f"(g[11]), "=f"(g[12]), "=f"(g[13]), "=f"(g[14]), "=f"(g[15]), "=f"(g[16]), "=f"(g[17]), "=f"(g[18]), "=f"(g[19]), "=f"(g[20]), "=f"(g[21]), "=f"(g[22]), "=f"(g[23]), "=f"(g[24]), "=f"(g[25]), "=f"(g[26]), "=f"(g[27]), "=f"(g[28]), "=f"(g[29]), "=f"(g[30]), "=f"(g[31]), "=f"(g[32]), "=f"(g[33]), "=f"(g[34]), "=f"(g[35]), "=f"(g[36]), "=f"(g[37]), "=f"(g[38]), "=f"(g[39]),
        "=f"(h[0]), "=f"(h[1]), "=f"(h[2]), "=f"(h[3]), "=f"(h[4]), "=f"(h[5]), "=f"(h[6]), "=f"(h[7]), "=f"(h[8]), "=f"(h[9]), "=f"(h[10]), "=f"(h[11]), "=f"(h[12]), "=f"(h[13]), "=f"(h[14]), "=f"(h[15]), "=f"(h[16]), "=f"(h[17]), "=f"(h[18]), "=f"(h[19]), "=f"(h[20]), "=f"(h[21]), "=f"(h[22]), "=f"(h[23]), "=f"(h[24]), "=f"(h[25]), "=f"(h[26]), "=f"(h[27]), "=f"(h[28]), "=f"(h[29]), "=f"(h[30]), "=f"(h[31]), "=f"(h[32]), "=f"(h[33]), "=f"(h[34]), "=f"(h[35]), "=f"(h[36]), "=f"(h[37]), "=f"(h[38]), "=f"(h[39])
      : "r"(w[0]), "r"(w[1]), "r"(w[2]), "r"(w[3]), "r"(w[4]), "r"(w[5]), "r"(w[6]), "r"(w[7]), "r"(w[8]), "r"(w[9]), "r"(w[10]), "r"(w[11]), "r"(w[12]), "r"(w[13]), "r"(w[14]), "r"(w[15]), "r"(w[16]), "r"(w[17]), "r"(w[18]), "r"(w[19]), "r"(w[20]), "r"(w[21]), "r"(w[22]), "r"(w[23]), "r"(w[24]), "r"(w[25]), "r"(w[26]), "r"(w[27]), "r"(w[28]), "r"(w[29]), "r"(w[30]), "r"(w[31]), "r"(w[32]), "r"(w[33]), "r"(w[34]), "r"(w[35]), "r"(w[36]), "r"(w[37]), "r"(w[38]), "r"(w[39]), "l"(dx), "l"(de), "l"(dh)
      : "memory");
  }
  static __device__ __forceinline__ void wait_g(float* g) {
    asm volatile("wgmma.wait_group.sync.aligned 1;\n"
      : "+f"(g[0]), "+f"(g[1]), "+f"(g[2]), "+f"(g[3]), "+f"(g[4]), "+f"(g[5]), "+f"(g[6]), "+f"(g[7]), "+f"(g[8]), "+f"(g[9]), "+f"(g[10]), "+f"(g[11]), "+f"(g[12]), "+f"(g[13]), "+f"(g[14]), "+f"(g[15]), "+f"(g[16]), "+f"(g[17]), "+f"(g[18]), "+f"(g[19]), "+f"(g[20]), "+f"(g[21]), "+f"(g[22]), "+f"(g[23]), "+f"(g[24]), "+f"(g[25]), "+f"(g[26]), "+f"(g[27]), "+f"(g[28]), "+f"(g[29]), "+f"(g[30]), "+f"(g[31]), "+f"(g[32]), "+f"(g[33]), "+f"(g[34]), "+f"(g[35]), "+f"(g[36]), "+f"(g[37]), "+f"(g[38]), "+f"(g[39])
      :: "memory");
  }
  static __device__ __forceinline__ void wait_h(float* h) {
    asm volatile("wgmma.wait_group.sync.aligned 0;\n"
      : "+f"(h[0]), "+f"(h[1]), "+f"(h[2]), "+f"(h[3]), "+f"(h[4]), "+f"(h[5]), "+f"(h[6]), "+f"(h[7]), "+f"(h[8]), "+f"(h[9]), "+f"(h[10]), "+f"(h[11]), "+f"(h[12]), "+f"(h[13]), "+f"(h[14]), "+f"(h[15]), "+f"(h[16]), "+f"(h[17]), "+f"(h[18]), "+f"(h[19]), "+f"(h[20]), "+f"(h[21]), "+f"(h[22]), "+f"(h[23]), "+f"(h[24]), "+f"(h[25]), "+f"(h[26]), "+f"(h[27]), "+f"(h[28]), "+f"(h[29]), "+f"(h[30]), "+f"(h[31]), "+f"(h[32]), "+f"(h[33]), "+f"(h[34]), "+f"(h[35]), "+f"(h[36]), "+f"(h[37]), "+f"(h[38]), "+f"(h[39])
      :: "memory");
  }
};
template<> struct TileMMA<11> {
  static __device__ __forceinline__ void issue(float* g, float* h, const uint32_t* w, uint64_t dx, uint64_t de, uint64_t dh, uint64_t dc) {
    asm volatile(
      "{\n.reg .b64 dx1, dx2, dx3;\n"
      "add.s64 dx1, %124, 2;\nadd.s64 dx2, %124, 4;\nadd.s64 dx3, %124, 6;\n"
      "wgmma.fence.sync.aligned;\n"
      "wgmma.mma_async.sync.aligned.m64n88k16.f32.bf16.bf16 {%0, %1, %2, %3, %4, %5, %6, %7, %8, %9, %10, %11, %12, %13, %14, %15, %16, %17, %18, %19, %20, %21, %22, %23, %24, %25, %26, %27, %28, %29, %30, %31, %32, %33, %34, %35, %36, %37, %38, %39, %40, %41, %42, %43}, {%120, %121, %122, %123}, %126, 0, 1, 1, 0;\n"
      "wgmma.mma_async.sync.aligned.m64n88k16.f32.bf16.bf16 {%0, %1, %2, %3, %4, %5, %6, %7, %8, %9, %10, %11, %12, %13, %14, %15, %16, %17, %18, %19, %20, %21, %22, %23, %24, %25, %26, %27, %28, %29, %30, %31, %32, %33, %34, %35, %36, %37, %38, %39, %40, %41, %42, %43}, %127, %125, 1, 1, 1, 0, 0;\n"
      "wgmma.mma_async.sync.aligned.m64n88k16.f32.bf16.bf16 {%0, %1, %2, %3, %4, %5, %6, %7, %8, %9, %10, %11, %12, %13, %14, %15, %16, %17, %18, %19, %20, %21, %22, %23, %24, %25, %26, %27, %28, %29, %30, %31, %32, %33, %34, %35, %36, %37, %38, %39, %40, %41, %42, %43}, {%88, %89, %90, %91}, %124, 1, 1, 1, 0;\n"
      "wgmma.mma_async.sync.aligned.m64n88k16.f32.bf16.bf16 {%0, %1, %2, %3, %4, %5, %6, %7, %8, %9, %10, %11, %12, %13, %14, %15, %16, %17, %18, %19, %20, %21, %22, %23, %24, %25, %26, %27, %28, %29, %30, %31, %32, %33, %34, %35, %36, %37, %38, %39, %40, %41, %42, %43}, {%92, %93, %94, %95}, dx1, 1, 1, 1, 0;\n"
      "wgmma.mma_async.sync.aligned.m64n88k16.f32.bf16.bf16 {%0, %1, %2, %3, %4, %5, %6, %7, %8, %9, %10, %11, %12, %13, %14, %15, %16, %17, %18, %19, %20, %21, %22, %23, %24, %25, %26, %27, %28, %29, %30, %31, %32, %33, %34, %35, %36, %37, %38, %39, %40, %41, %42, %43}, {%96, %97, %98, %99}, dx2, 1, 1, 1, 0;\n"
      "wgmma.mma_async.sync.aligned.m64n88k16.f32.bf16.bf16 {%0, %1, %2, %3, %4, %5, %6, %7, %8, %9, %10, %11, %12, %13, %14, %15, %16, %17, %18, %19, %20, %21, %22, %23, %24, %25, %26, %27, %28, %29, %30, %31, %32, %33, %34, %35, %36, %37, %38, %39, %40, %41, %42, %43}, {%100, %101, %102, %103}, dx3, 1, 1, 1, 0;\n"
      "wgmma.commit_group.sync.aligned;\n"
      "wgmma.mma_async.sync.aligned.m64n88k16.f32.bf16.bf16 {%44, %45, %46, %47, %48, %49, %50, %51, %52, %53, %54, %55, %56, %57, %58, %59, %60, %61, %62, %63, %64, %65, %66, %67, %68, %69, %70, %71, %72, %73, %74, %75, %76, %77, %78, %79, %80, %81, %82, %83, %84, %85, %86, %87}, {%104, %105, %106, %107}, %124, 0, 1, 1, 0;\n"
      "wgmma.mma_async.sync.aligned.m64n88k16.f32.bf16.bf16 {%44, %45, %46, %47, %48, %49, %50, %51, %52, %53, %54, %55, %56, %57, %58, %59, %60, %61, %62, %63, %64, %65, %66, %67, %68, %69, %70, %71, %72, %73, %74, %75, %76, %77, %78, %79, %80, %81, %82, %83, %84, %85, %86, %87}, {%108, %109, %110, %111}, dx1, 1, 1, 1, 0;\n"
      "wgmma.mma_async.sync.aligned.m64n88k16.f32.bf16.bf16 {%44, %45, %46, %47, %48, %49, %50, %51, %52, %53, %54, %55, %56, %57, %58, %59, %60, %61, %62, %63, %64, %65, %66, %67, %68, %69, %70, %71, %72, %73, %74, %75, %76, %77, %78, %79, %80, %81, %82, %83, %84, %85, %86, %87}, {%112, %113, %114, %115}, dx2, 1, 1, 1, 0;\n"
      "wgmma.mma_async.sync.aligned.m64n88k16.f32.bf16.bf16 {%44, %45, %46, %47, %48, %49, %50, %51, %52, %53, %54, %55, %56, %57, %58, %59, %60, %61, %62, %63, %64, %65, %66, %67, %68, %69, %70, %71, %72, %73, %74, %75, %76, %77, %78, %79, %80, %81, %82, %83, %84, %85, %86, %87}, {%116, %117, %118, %119}, dx3, 1, 1, 1, 0;\n"
      "wgmma.commit_group.sync.aligned;\n}\n"
      : "=f"(g[0]), "=f"(g[1]), "=f"(g[2]), "=f"(g[3]), "=f"(g[4]), "=f"(g[5]), "=f"(g[6]), "=f"(g[7]), "=f"(g[8]), "=f"(g[9]), "=f"(g[10]), "=f"(g[11]), "=f"(g[12]), "=f"(g[13]), "=f"(g[14]), "=f"(g[15]), "=f"(g[16]), "=f"(g[17]), "=f"(g[18]), "=f"(g[19]), "=f"(g[20]), "=f"(g[21]), "=f"(g[22]), "=f"(g[23]), "=f"(g[24]), "=f"(g[25]), "=f"(g[26]), "=f"(g[27]), "=f"(g[28]), "=f"(g[29]), "=f"(g[30]), "=f"(g[31]), "=f"(g[32]), "=f"(g[33]), "=f"(g[34]), "=f"(g[35]), "=f"(g[36]), "=f"(g[37]), "=f"(g[38]), "=f"(g[39]), "=f"(g[40]), "=f"(g[41]), "=f"(g[42]), "=f"(g[43]),
        "=f"(h[0]), "=f"(h[1]), "=f"(h[2]), "=f"(h[3]), "=f"(h[4]), "=f"(h[5]), "=f"(h[6]), "=f"(h[7]), "=f"(h[8]), "=f"(h[9]), "=f"(h[10]), "=f"(h[11]), "=f"(h[12]), "=f"(h[13]), "=f"(h[14]), "=f"(h[15]), "=f"(h[16]), "=f"(h[17]), "=f"(h[18]), "=f"(h[19]), "=f"(h[20]), "=f"(h[21]), "=f"(h[22]), "=f"(h[23]), "=f"(h[24]), "=f"(h[25]), "=f"(h[26]), "=f"(h[27]), "=f"(h[28]), "=f"(h[29]), "=f"(h[30]), "=f"(h[31]), "=f"(h[32]), "=f"(h[33]), "=f"(h[34]), "=f"(h[35]), "=f"(h[36]), "=f"(h[37]), "=f"(h[38]), "=f"(h[39]), "=f"(h[40]), "=f"(h[41]), "=f"(h[42]), "=f"(h[43])
      : "r"(w[0]), "r"(w[1]), "r"(w[2]), "r"(w[3]), "r"(w[4]), "r"(w[5]), "r"(w[6]), "r"(w[7]), "r"(w[8]), "r"(w[9]), "r"(w[10]), "r"(w[11]), "r"(w[12]), "r"(w[13]), "r"(w[14]), "r"(w[15]), "r"(w[20]), "r"(w[21]), "r"(w[22]), "r"(w[23]), "r"(w[24]), "r"(w[25]), "r"(w[26]), "r"(w[27]), "r"(w[28]), "r"(w[29]), "r"(w[30]), "r"(w[31]), "r"(w[32]), "r"(w[33]), "r"(w[34]), "r"(w[35]), "r"(w[36]), "r"(w[37]), "r"(w[38]), "r"(w[39]), "l"(dx), "l"(de), "l"(dh), "l"(dc)
      : "memory");
  }
  static __device__ __forceinline__ void wait_g(float* g) {
    asm volatile("wgmma.wait_group.sync.aligned 1;\n"
      : "+f"(g[0]), "+f"(g[1]), "+f"(g[2]), "+f"(g[3]), "+f"(g[4]), "+f"(g[5]), "+f"(g[6]), "+f"(g[7]), "+f"(g[8]), "+f"(g[9]), "+f"(g[10]), "+f"(g[11]), "+f"(g[12]), "+f"(g[13]), "+f"(g[14]), "+f"(g[15]), "+f"(g[16]), "+f"(g[17]), "+f"(g[18]), "+f"(g[19]), "+f"(g[20]), "+f"(g[21]), "+f"(g[22]), "+f"(g[23]), "+f"(g[24]), "+f"(g[25]), "+f"(g[26]), "+f"(g[27]), "+f"(g[28]), "+f"(g[29]), "+f"(g[30]), "+f"(g[31]), "+f"(g[32]), "+f"(g[33]), "+f"(g[34]), "+f"(g[35]), "+f"(g[36]), "+f"(g[37]), "+f"(g[38]), "+f"(g[39]), "+f"(g[40]), "+f"(g[41]), "+f"(g[42]), "+f"(g[43])
      :: "memory");
  }
  static __device__ __forceinline__ void wait_h(float* h) {
    asm volatile("wgmma.wait_group.sync.aligned 0;\n"
      : "+f"(h[0]), "+f"(h[1]), "+f"(h[2]), "+f"(h[3]), "+f"(h[4]), "+f"(h[5]), "+f"(h[6]), "+f"(h[7]), "+f"(h[8]), "+f"(h[9]), "+f"(h[10]), "+f"(h[11]), "+f"(h[12]), "+f"(h[13]), "+f"(h[14]), "+f"(h[15]), "+f"(h[16]), "+f"(h[17]), "+f"(h[18]), "+f"(h[19]), "+f"(h[20]), "+f"(h[21]), "+f"(h[22]), "+f"(h[23]), "+f"(h[24]), "+f"(h[25]), "+f"(h[26]), "+f"(h[27]), "+f"(h[28]), "+f"(h[29]), "+f"(h[30]), "+f"(h[31]), "+f"(h[32]), "+f"(h[33]), "+f"(h[34]), "+f"(h[35]), "+f"(h[36]), "+f"(h[37]), "+f"(h[38]), "+f"(h[39]), "+f"(h[40]), "+f"(h[41]), "+f"(h[42]), "+f"(h[43])
      :: "memory");
  }
};
__device__ __forceinline__ void node_mma2(float* u, float* a, const uint32_t* w, uint64_t dx) {
    asm volatile(
      "{\n.reg .b64 dx1, dx2, dx3, dy0, dy1, dy2, dy3;\n"
      "add.s64 dx1, %80, 2;\nadd.s64 dx2, %80, 4;\nadd.s64 dx3, %80, 6;\n"
      "add.s64 dy0, %80, 512;\nadd.s64 dy1, %80, 514;\nadd.s64 dy2, %80, 516;\nadd.s64 dy3, %80, 518;\n"
      "wgmma.fence.sync.aligned;\n"
      "wgmma.mma_async.sync.aligned.m64n64k16.f32.bf16.bf16 {%0, %1, %2, %3, %4, %5, %6, %7, %8, %9, %10, %11, %12, %13, %14, %15, %16, %17, %18, %19, %20, %21, %22, %23, %24, %25, %26, %27, %28, %29, %30, %31}, {%64, %65, %66, %67}, %80, 0, 1, 1, 0;\n"
      "wgmma.mma_async.sync.aligned.m64n64k16.f32.bf16.bf16 {%0, %1, %2, %3, %4, %5, %6, %7, %8, %9, %10, %11, %12, %13, %14, %15, %16, %17, %18, %19, %20, %21, %22, %23, %24, %25, %26, %27, %28, %29, %30, %31}, {%68, %69, %70, %71}, dx1, 1, 1, 1, 0;\n"
      "wgmma.mma_async.sync.aligned.m64n64k16.f32.bf16.bf16 {%0, %1, %2, %3, %4, %5, %6, %7, %8, %9, %10, %11, %12, %13, %14, %15, %16, %17, %18, %19, %20, %21, %22, %23, %24, %25, %26, %27, %28, %29, %30, %31}, {%72, %73, %74, %75}, dx2, 1, 1, 1, 0;\n"
      "wgmma.mma_async.sync.aligned.m64n64k16.f32.bf16.bf16 {%0, %1, %2, %3, %4, %5, %6, %7, %8, %9, %10, %11, %12, %13, %14, %15, %16, %17, %18, %19, %20, %21, %22, %23, %24, %25, %26, %27, %28, %29, %30, %31}, {%76, %77, %78, %79}, dx3, 1, 1, 1, 0;\n"
      "wgmma.commit_group.sync.aligned;\n"
      "wgmma.mma_async.sync.aligned.m64n64k16.f32.bf16.bf16 {%32, %33, %34, %35, %36, %37, %38, %39, %40, %41, %42, %43, %44, %45, %46, %47, %48, %49, %50, %51, %52, %53, %54, %55, %56, %57, %58, %59, %60, %61, %62, %63}, {%64, %65, %66, %67}, dy0, 0, 1, 1, 0;\n"
      "wgmma.mma_async.sync.aligned.m64n64k16.f32.bf16.bf16 {%32, %33, %34, %35, %36, %37, %38, %39, %40, %41, %42, %43, %44, %45, %46, %47, %48, %49, %50, %51, %52, %53, %54, %55, %56, %57, %58, %59, %60, %61, %62, %63}, {%68, %69, %70, %71}, dy1, 1, 1, 1, 0;\n"
      "wgmma.mma_async.sync.aligned.m64n64k16.f32.bf16.bf16 {%32, %33, %34, %35, %36, %37, %38, %39, %40, %41, %42, %43, %44, %45, %46, %47, %48, %49, %50, %51, %52, %53, %54, %55, %56, %57, %58, %59, %60, %61, %62, %63}, {%72, %73, %74, %75}, dy2, 1, 1, 1, 0;\n"
      "wgmma.mma_async.sync.aligned.m64n64k16.f32.bf16.bf16 {%32, %33, %34, %35, %36, %37, %38, %39, %40, %41, %42, %43, %44, %45, %46, %47, %48, %49, %50, %51, %52, %53, %54, %55, %56, %57, %58, %59, %60, %61, %62, %63}, {%76, %77, %78, %79}, dy3, 1, 1, 1, 0;\n"
      "wgmma.commit_group.sync.aligned;\n}\n"
      : "=f"(u[0]), "=f"(u[1]), "=f"(u[2]), "=f"(u[3]), "=f"(u[4]), "=f"(u[5]), "=f"(u[6]), "=f"(u[7]), "=f"(u[8]), "=f"(u[9]), "=f"(u[10]), "=f"(u[11]), "=f"(u[12]), "=f"(u[13]), "=f"(u[14]), "=f"(u[15]), "=f"(u[16]), "=f"(u[17]), "=f"(u[18]), "=f"(u[19]), "=f"(u[20]), "=f"(u[21]), "=f"(u[22]), "=f"(u[23]), "=f"(u[24]), "=f"(u[25]), "=f"(u[26]), "=f"(u[27]), "=f"(u[28]), "=f"(u[29]), "=f"(u[30]), "=f"(u[31]),
        "=f"(a[0]), "=f"(a[1]), "=f"(a[2]), "=f"(a[3]), "=f"(a[4]), "=f"(a[5]), "=f"(a[6]), "=f"(a[7]), "=f"(a[8]), "=f"(a[9]), "=f"(a[10]), "=f"(a[11]), "=f"(a[12]), "=f"(a[13]), "=f"(a[14]), "=f"(a[15]), "=f"(a[16]), "=f"(a[17]), "=f"(a[18]), "=f"(a[19]), "=f"(a[20]), "=f"(a[21]), "=f"(a[22]), "=f"(a[23]), "=f"(a[24]), "=f"(a[25]), "=f"(a[26]), "=f"(a[27]), "=f"(a[28]), "=f"(a[29]), "=f"(a[30]), "=f"(a[31])
      : "r"(w[0]), "r"(w[1]), "r"(w[2]), "r"(w[3]), "r"(w[4]), "r"(w[5]), "r"(w[6]), "r"(w[7]), "r"(w[8]), "r"(w[9]), "r"(w[10]), "r"(w[11]), "r"(w[12]), "r"(w[13]), "r"(w[14]), "r"(w[15]), "l"(dx)
      : "memory");
}

__device__ __forceinline__ uint32_t smem_u32(const void* p) { return (uint32_t)__cvta_generic_to_shared(p); }
__device__ __forceinline__ float ex2f(float x) { float y; asm("ex2.approx.ftz.f32 %0, %1;" : "=f"(y) : "f"(x)); return y; }
__device__ __forceinline__ float rcpf(float x) { float y; asm("rcp.approx.ftz.f32 %0, %1;" : "=f"(y) : "f"(x)); return y; }
__device__ __forceinline__ uint32_t pack_bf16(float lo, float hi) {
    uint32_t r; asm("cvt.rn.bf16x2.f32 %0, %1, %2;" : "=r"(r) : "f"(hi), "f"(lo)); return r;
}
__device__ __forceinline__ float bf_lo(uint32_t v) { return __uint_as_float(v << 16); }
__device__ __forceinline__ float bf_hi(uint32_t v) { return __uint_as_float(v & 0xFFFF0000u); }
template<int STRIDE>
__device__ __forceinline__ void cp16i(uint32_t dst, const char* base, uint32_t idx) {
    asm volatile("{\n.reg .b64 a;\nmad.wide.u32 a, %2, %3, %1;\ncp.async.cg.shared.global [%0], [a], 16;\n}\n" :: "r"(dst), "l"(base), "r"(idx), "n"(STRIDE) : "memory");
}
__device__ __forceinline__ void cp16e(uint32_t dst, const char* base, uint32_t idx, uint64_t pol) {
    asm volatile("{\n.reg .b64 a;\nmad.wide.u32 a, %2, 32, %1;\ncp.async.cg.shared.global.L2::cache_hint [%0], [a], 16, %3;\n}\n" :: "r"(dst), "l"(base), "r"(idx), "l"(pol) : "memory");
}
template<int STRIDE>
__device__ __forceinline__ void cp16z(uint32_t dst, const char* base, uint32_t idx, int k, int n, uint64_t pol) {
    if (STRIDE == 32)
        asm volatile("{\n.reg .b64 a;\n.reg .pred p;\nsetp.ge.s32 p, %3, %4;\nmad.wide.u32 a, %2, 32, %1;\ncp.async.cg.shared.global.L2::cache_hint [%0], [a], 16, p, %5;\n}\n"
                     :: "r"(dst), "l"(base), "r"(idx), "r"(k), "r"(n), "l"(pol) : "memory");
    else
        asm volatile("{\n.reg .b64 a;\n.reg .pred p;\nsetp.ge.s32 p, %3, %4;\nmad.wide.u32 a, %2, 128, %1;\ncp.async.cg.shared.global [%0], [a], 16, p;\n}\n"
                     :: "r"(dst), "l"(base), "r"(idx), "r"(k), "r"(n) : "memory");
}
template<int HI, bool Z>
__device__ __forceinline__ void cpx(uint32_t hi, uint32_t dst, uint32_t p, uint32_t lo, int k, int n) {
    if (Z) asm volatile("{\n.reg .b32 l;\n.reg .b64 a;\n.reg .pred q;\nsetp.ge.s32 q, %5, %6;\ndp2a.lo.u32.u32 l, %1, %2, %3;\nmov.b64 a, {l, %0};\ncp.async.cg.shared.global [%4], [a], 16, q;\n}\n"
                        :: "r"(hi), "r"(p), "r"(HI ? 0x8000u : 0x80u), "r"(lo), "r"(dst), "r"(k), "r"(n) : "memory");
    else asm volatile("{\n.reg .b32 l;\n.reg .b64 a;\ndp2a.lo.u32.u32 l, %1, %2, %3;\nmov.b64 a, {l, %0};\ncp.async.cg.shared.global [%4], [a], 16;\n}\n"
                      :: "r"(hi), "r"(p), "r"(HI ? 0x8000u : 0x80u), "r"(lo), "r"(dst) : "memory");
}
template<bool Z>
__device__ __forceinline__ void cpe(uint32_t hi, uint32_t dst, uint32_t idx, uint32_t lo, int k, int n, uint64_t pol) {
    if (Z) asm volatile("{\n.reg .b32 l;\n.reg .b64 a;\n.reg .pred q;\nsetp.ge.s32 q, %5, %6;\nmad.lo.u32 l, %1, 32, %2;\nmov.b64 a, {l, %0};\ncp.async.cg.shared.global.L2::cache_hint [%3], [a], 16, q, %4;\n}\n"
                        :: "r"(hi), "r"(idx), "r"(lo), "r"(dst), "l"(pol), "r"(k), "r"(n) : "memory");
    else asm volatile("{\n.reg .b32 l;\n.reg .b64 a;\nmad.lo.u32 l, %1, 32, %2;\nmov.b64 a, {l, %0};\ncp.async.cg.shared.global.L2::cache_hint [%3], [a], 16, %4;\n}\n"
                      :: "r"(hi), "r"(idx), "r"(lo), "r"(dst), "l"(pol) : "memory");
}
template<int N> __device__ __forceinline__ void cp_wait() { asm volatile("cp.async.wait_group %0;" :: "n"(N) : "memory"); }
__device__ __forceinline__ void mbar_init(uint32_t bar, int cnt) { asm volatile("mbarrier.init.shared.b64 [%0], %1;" :: "r"(bar), "r"(cnt) : "memory"); }
__device__ __forceinline__ void mbar_arrive(uint32_t bar) { asm volatile("mbarrier.arrive.shared.b64 _, [%0];" :: "r"(bar) : "memory"); }
__device__ __forceinline__ void mbar_expect(uint32_t bar, uint32_t bytes) { asm volatile("mbarrier.arrive.expect_tx.shared.b64 _, [%0], %1;" :: "r"(bar), "r"(bytes) : "memory"); }
__device__ __forceinline__ void mbar_cp_arrive(uint32_t bar) { asm volatile("cp.async.mbarrier.arrive.noinc.shared.b64 [%0];" :: "r"(bar) : "memory"); }
__device__ __forceinline__ void mbar_wait(uint32_t bar, uint32_t parity) {
    asm volatile("{\n.reg .pred p;\n.reg .u32 n;\nmbarrier.try_wait.parity.shared.b64 p, [%0], %1;\n@p bra DONE_%=;\nmov.u32 n, 0;\n"
                 "WAIT_%=:\nmbarrier.try_wait.parity.shared.b64 p, [%0], %1, 0x100000;\n@p bra DONE_%=;\n"
                 "add.u32 n, n, 1;\nsetp.lt.u32 p, n, 0x400000;\n@p bra WAIT_%=;\ntrap;\nDONE_%=:\n}\n"
                 :: "r"(bar), "r"(parity) : "memory");
}
__device__ __forceinline__ void mbar_wait_c(uint32_t bar, uint32_t parity) {
    asm volatile("{\n.reg .pred p;\nWAIT_%=:\nmbarrier.try_wait.parity.shared.b64 p, [%0], %1;\n@p bra DONE_%=;\nbra WAIT_%=;\nDONE_%=:\n}\n"
                 :: "r"(bar), "r"(parity) : "memory");
}
__device__ __forceinline__ void mbar_wait_h(uint32_t bar, uint32_t parity) {
    asm volatile("{\n.reg .pred p;\nWAIT_%=:\nmbarrier.try_wait.parity.shared.b64 p, [%0], %1, 0x100000;\n@p bra DONE_%=;\nbra WAIT_%=;\nDONE_%=:\n}\n"
                 :: "r"(bar), "r"(parity) : "memory");
}
__device__ __forceinline__ uint32_t lds32(uint32_t a) { uint32_t v; asm volatile("ld.shared.u32 %0, [%1];" : "=r"(v) : "r"(a) : "memory"); return v; }
__device__ __forceinline__ void sts32(uint32_t a, uint32_t v) { asm volatile("st.shared.u32 [%0], %1;" :: "r"(a), "r"(v) : "memory"); }
__device__ __forceinline__ uint2 lds64(uint32_t a) { uint2 v; asm volatile("ld.shared.v2.u32 {%0,%1}, [%2];" : "=r"(v.x), "=r"(v.y) : "r"(a) : "memory"); return v; }
__device__ __forceinline__ uint4 lds128(uint32_t a) { uint4 v; asm volatile("ld.shared.v4.u32 {%0,%1,%2,%3}, [%4];" : "=r"(v.x), "=r"(v.y), "=r"(v.z), "=r"(v.w) : "r"(a) : "memory"); return v; }
__device__ __forceinline__ void sts128(uint32_t a, uint4 v) { asm volatile("st.shared.v4.u32 [%0], {%1,%2,%3,%4};" :: "r"(a), "r"(v.x), "r"(v.y), "r"(v.z), "r"(v.w) : "memory"); }
__device__ __forceinline__ void ldsm4t(uint32_t* v, uint32_t a) {
    asm volatile("ldmatrix.sync.aligned.m8n8.x4.trans.shared.b16 {%0,%1,%2,%3}, [%4];" : "=r"(v[0]), "=r"(v[1]), "=r"(v[2]), "=r"(v[3]) : "r"(a) : "memory");
}
__device__ __forceinline__ void stsm4t(uint32_t a, const uint32_t* v) {
    asm volatile("stmatrix.sync.aligned.m8n8.x4.trans.shared.b16 [%0], {%1,%2,%3,%4};" :: "r"(a), "r"(v[0]), "r"(v[1]), "r"(v[2]), "r"(v[3]) : "memory");
}
__device__ __forceinline__ int atoms_inc(uint32_t a) { int v; asm volatile("atom.shared.add.u32 %0, [%1], 1;" : "=r"(v) : "r"(a) : "memory"); return v; }
__device__ __forceinline__ bool elect_one() {
    uint32_t el;
    asm volatile("{\n.reg .pred p;\nelect.sync _|p, 0xffffffff;\nselp.u32 %0, 1, 0, p;\n}" : "=r"(el));
    return el != 0;
}
__device__ __forceinline__ float tanhf_a(float x) { float y; asm("tanh.approx.f32 %0, %1;" : "=f"(y) : "f"(x)); return y; }
__device__ __forceinline__ const char* as_pair(const void* p, uint32_t scratch) {
    const char* r;
    asm volatile("st.shared.u64 [%1], %2;\nld.volatile.shared.u64 %0, [%1];" : "=l"(r) : "r"(scratch), "l"(p) : "memory");
    return r;
}
__device__ __forceinline__ void ld_unit(uint4& v, const char* p, bool ok) {
    asm volatile("{\n.reg .pred q;\nsetp.ne.u32 q, %5, 0;\n@q ld.relaxed.gpu.global.v4.u32 {%0,%1,%2,%3}, [%4];\n}"
                 : "+r"(v.x), "+r"(v.y), "+r"(v.z), "+r"(v.w) : "l"(p), "r"((uint32_t)ok) : "memory");
}
__device__ __forceinline__ void ld_unit(uint2& v, const char* p, bool ok) {
    asm volatile("{\n.reg .pred q;\nsetp.ne.u32 q, %3, 0;\n@q ld.relaxed.gpu.global.v2.u32 {%0,%1}, [%2];\n}"
                 : "+r"(v.x), "+r"(v.y) : "l"(p), "r"((uint32_t)ok) : "memory");
}
__device__ __forceinline__ void bulk_ld(uint32_t dst, const void* src, int bytes, uint32_t bar) {
    mbar_expect(bar, bytes);
    if (bytes > 0) asm volatile("cp.async.bulk.shared::cluster.global.mbarrier::complete_tx::bytes [%0], [%1], %2, [%3];" :: "r"(dst), "l"(src), "r"(bytes), "r"(bar) : "memory");
}
__device__ __forceinline__ void bulk_st(void* dst, uint32_t src, int bytes) {
    asm volatile("cp.async.bulk.global.shared::cta.bulk_group [%0], [%1], %2;" :: "l"(dst), "r"(src), "r"(bytes) : "memory");
}

__device__ __forceinline__ void finish(uint4& a, const uint4& xu, const uint4& xv) {
    asm("{\n.reg .b32 z;\nfma.rn.relu.bf16x2 z, %0, %3, %1;\nadd.rn.bf16x2 %0, z, %2;\n}" : "+r"(a.x) : "r"(xu.x), "r"(xv.x), "r"(0x3F803F80u));
    asm("{\n.reg .b32 z;\nfma.rn.relu.bf16x2 z, %0, %3, %1;\nadd.rn.bf16x2 %0, z, %2;\n}" : "+r"(a.y) : "r"(xu.y), "r"(xv.y), "r"(0x3F803F80u));
    asm("{\n.reg .b32 z;\nfma.rn.relu.bf16x2 z, %0, %3, %1;\nadd.rn.bf16x2 %0, z, %2;\n}" : "+r"(a.z) : "r"(xu.z), "r"(xv.z), "r"(0x3F803F80u));
    asm("{\n.reg .b32 z;\nfma.rn.relu.bf16x2 z, %0, %3, %1;\nadd.rn.bf16x2 %0, z, %2;\n}" : "+r"(a.w) : "r"(xu.w), "r"(xv.w), "r"(0x3F803F80u));
}

__device__ __forceinline__ void node_rows(uint32_t p, const float* a) {
    #pragma unroll
    for (int i = 0; i < 4; i++) {
        const float* u = a + 8 * i;
        const uint32_t v[4] = {pack_bf16(u[0], u[1]), pack_bf16(u[2], u[3]), pack_bf16(u[4], u[5]), pack_bf16(u[6], u[7])};
        stsm4t(p + i * 2048, v);
    }
}

constexpr float EPS2 = 2e-6f;
constexpr float TAU = 2.5e-5f;

template<bool HALF>
__device__ __forceinline__ void make_wfrag(uint32_t* f, const uint32_t* v) {
    const uint32_t v0 = v[0], v1 = v[1], v2 = v[2], v3 = v[3];
    f[0] = __byte_perm(v0, v1, 0x5410); f[1] = __byte_perm(v0, v1, 0x7632);
    f[2] = __byte_perm(v2, v3, 0x5410); f[3] = __byte_perm(v2, v3, 0x7632);
    if (HALF) {
        #pragma unroll
        for (int i = 0; i < 4; i++) asm("mul.rn.bf16x2 %0, %0, %1;" : "+r"(f[i]) : "r"(0x3F003F00u));
    }
}

template<int NP>
__device__ __forceinline__ void epi_fast(const float* g, const float* h, float m1, float m2,
                                         float& n0, float& d0, float& n1, float& d1, float& dmin)
{
    constexpr int JC = NP >= 6 ? NP - 1 - 2 : NP >= 4 ? NP - 2 : NP - 1;
    constexpr int JT = NP < 3 ? -1 : JC < NP - 1 ? JC : NP - 2;
    #pragma unroll
    for (int j = 0; j < NP; j++) {
        float t0 = tanhf_a(g[4*j+0]), t1 = tanhf_a(g[4*j+1]), t2 = tanhf_a(g[4*j+2]), t3 = tanhf_a(g[4*j+3]);
        auto add_d = [&]() {
            if (j == 0) { d0 = t0 + (2.f * (JT + 1) + EPS2); d1 = t2 + (2.f * (JT + 1) + EPS2); } else { d0 += t0; d1 += t2; }
            d0 += t1; d1 += t3;
        };
        if (j <= JT) add_d();
        if (j == NP - 1) { t0 = fmaf(t0, m1, m1); t1 = fmaf(t1, m2, m2); t2 = fmaf(t2, m1, m1); t3 = fmaf(t3, m2, m2); }
        else { t0 += 1.f; t1 += 1.f; t2 += 1.f; t3 += 1.f; }
        if (j > JT) add_d();
        if (j == 0) { n0 = t0 * h[0]; n1 = t2 * h[2]; } else { n0 = fmaf(t0, h[4*j], n0); n1 = fmaf(t2, h[4*j+2], n1); }
        n0 = fmaf(t1, h[4*j+1], n0); n1 = fmaf(t3, h[4*j+3], n1);
        if (j == JC) dmin = fminf(d0, d1);
    }
}

__device__ __noinline__ float4 epi_exact(const float4* gh, int np, int dv)
{
    float n0 = 0.f, d0 = EPS2, n1 = 0.f, d1 = EPS2;
    #pragma unroll 2
    for (int j = 0; j < np; j++) {
        const float4 g = gh[j], h = gh[NPMAX + j];
        const float ma = (2 * j < dv) ? 2.f : 0.f, mb = (2 * j + 1 < dv) ? 2.f : 0.f;
        const float e0 = ma * rcpf(1.f + ex2f(-2.f * LOG2E * g.x)), e1 = mb * rcpf(1.f + ex2f(-2.f * LOG2E * g.y));
        const float e2 = ma * rcpf(1.f + ex2f(-2.f * LOG2E * g.z)), e3 = mb * rcpf(1.f + ex2f(-2.f * LOG2E * g.w));
        d0 += e0 + e1; n0 = fmaf(e0, h.x, fmaf(e1, h.y, n0));
        d1 += e2 + e3; n1 = fmaf(e2, h.z, fmaf(e3, h.w, n1));
    }
    return make_float4(n0, d0, n1, d1);
}
template<int NP>
__device__ __forceinline__ void epi_dump(const float* g, const float* h, float4* gh) {
    #pragma unroll
    for (int i = 0; i < NP; i++) {
        gh[i] = make_float4(g[4*i], g[4*i+1], g[4*i+2], g[4*i+3]);
        gh[NPMAX + i] = make_float4(h[4*i], h[4*i+1], h[4*i+2], h[4*i+3]);
    }
}

__device__ __noinline__ void slow_bin(const __nv_bfloat16* x, const __nv_bfloat16* ea, const int* src, const int* dst,
                                      const __nv_bfloat16* wa, const __nv_bfloat16* wb, const __nv_bfloat16* wc,
                                      const __nv_bfloat16* wu, const __nv_bfloat16* wv, __nv_bfloat16* out,
                                      int E, int node0, int nn, int nthr)
{
    const int tid = threadIdx.x, lane = tid & 31;
    for (int i = tid; i < nn * 128; i += nthr) g_slow[(size_t)node0 * 128 + i] = 0.f;
    asm volatile("bar.sync 1, %0;" :: "r"(nthr) : "memory");
    for (int e0 = (tid >> 5) * 32; e0 < E; e0 += nthr) {
        int d = (e0 + lane < E) ? dst[e0 + lane] - node0 : -1;
        unsigned m = __ballot_sync(~0u, d >= 0 && d < nn);
        while (m) {
            int l = __ffs(m) - 1; m &= m - 1;
            int e = e0 + l, n = node0 + __shfl_sync(~0u, d, l), s = src[e];
            float g0 = 0, g1 = 0, h0 = 0, h1 = 0;
            for (int k = 0; k < 64; k++) {
                float xs = __bfloat162float(x[(size_t)s * 64 + k]), xd = __bfloat162float(x[(size_t)n * 64 + k]);
                uint32_t b2 = *(const uint32_t*)(wb + k * 64 + 2 * lane), v2 = *(const uint32_t*)(wv + k * 64 + 2 * lane);
                uint32_t a2 = *(const uint32_t*)(wa + k * 64 + 2 * lane);
                g0 = fmaf(xs, bf_lo(b2), fmaf(xd, bf_lo(a2), g0)); g1 = fmaf(xs, bf_hi(b2), fmaf(xd, bf_hi(a2), g1));
                h0 = fmaf(xs, bf_lo(v2), h0); h1 = fmaf(xs, bf_hi(v2), h1);
            }
            for (int k = 0; k < 16; k++) {
                float ev = __bfloat162float(ea[(size_t)e * 16 + k]);
                uint32_t c2 = *(const uint32_t*)(wc + k * 64 + 2 * lane);
                g0 = fmaf(ev, bf_lo(c2), g0); g1 = fmaf(ev, bf_hi(c2), g1);
            }
            float s0 = rcpf(1.f + ex2f(-LOG2E * g0)), s1 = rcpf(1.f + ex2f(-LOG2E * g1));
            float* acc = g_slow + (size_t)n * 128 + 4 * lane;
            atomicAdd(acc + 0, s0 * h0); atomicAdd(acc + 1, s0);
            atomicAdd(acc + 2, s1 * h1); atomicAdd(acc + 3, s1);
        }
    }
    __threadfence();
    asm volatile("bar.sync 1, %0;" :: "r"(nthr) : "memory");
    for (int i = tid; i < nn * 32; i += nthr) {
        int n = node0 + (i >> 5), cp = i & 31;
        float4 a = __ldcg((const float4*)(g_slow + (size_t)n * 128 + 4 * cp));
        float u0 = 0, u1 = 0;
        for (int k = 0; k < 64; k++) {
            float xd = __bfloat162float(x[(size_t)n * 64 + k]);
            uint32_t w2 = *(const uint32_t*)(wu + k * 64 + 2 * cp);
            u0 = fmaf(xd, bf_lo(w2), u0); u1 = fmaf(xd, bf_hi(w2), u1);
        }
        uint32_t xv = *(const uint32_t*)(x + (size_t)n * 64 + 2 * cp);
        float z0 = u0 + a.x / (a.y + 1e-6f), z1 = u1 + a.z / (a.w + 1e-6f);
        *(uint32_t*)(out + (size_t)n * 64 + 2 * cp) = pack_bf16(bf_lo(xv) + fmaxf(z0, 0.f), bf_hi(xv) + fmaxf(z1, 0.f));
    }
}

__global__ void __launch_bounds__(256) slow_kernel(const __nv_bfloat16* x, const __nv_bfloat16* ea, const int* src, const int* dst,
        const __nv_bfloat16* wa, const __nv_bfloat16* wb, const __nv_bfloat16* wc, const __nv_bfloat16* wu, const __nv_bfloat16* wv,
        __nv_bfloat16* out, int N, int E, int npb)
{
    int node0 = blockIdx.x * npb;
    slow_bin(x, ea, src, dst, wa, wb, wc, wu, wv, out, E, node0, max(0, min(npb, N - node0)), 256);
}

constexpr int XS_BYTES = NPMAX * 1024;
constexpr int ES_BYTES = NPMAX * 256;
constexpr int SM_XS = 0;
constexpr int SM_XU = SM_XS + 3 * NSTAGE * XS_BYTES;
constexpr int SM_TAB = SM_XU + NPB_MAX * 128;
constexpr int SM_ES = SM_TAB + (NPB_MAX + 2) * 128;
constexpr int SM_WC = SM_ES + 3 * NSTAGE * ES_BYTES;
constexpr int SM_OH = SM_WC + 2048;
constexpr int SM_EID = SM_OH + 256;
constexpr int SM_SRC = SM_EID + (SLOT_CAP + 32) * 4;
constexpr int SM_TINFO = SM_SRC + (SLOT_CAP + 32) * 2;
constexpr int SM_MISC = SM_TINFO + TILE_CAP * 32;
constexpr int SM_CLAIM = SM_TAB + (NPB_MAX + 1) * 128;
constexpr int SM_BARS = SM_MISC + 32 * 4;
constexpr int SM_ABAR = SM_BARS + 6 * 48;
constexpr int SM_XBAR = SM_ABAR + 10 * 8;
constexpr int SM_SBAR = SM_XBAR + 4 * 8;
constexpr int SM_GBAR = SM_SBAR + 3 * 8;
constexpr int SM_WL = SM_GBAR + 97 * 8;
constexpr int WST = 9;
constexpr int SMEM_BYTES = SM_WL + (96 + WST) * 8;
constexpr int SM_P2 = 0, SM_P1 = 6 * 384 * 16;
constexpr int SM_DEG = SM_P1 + P1B;
constexpr int SM_CNT = SM_DEG + 512 * 4;
constexpr int SM_CLS = SM_CNT + 512 * 4;
constexpr int SM_HIST = SM_CLS + NCLS * 4;
constexpr int SM_XLIST = SM_HIST + 136 * 4;
constexpr int SM_SORT = SM_XLIST + XCAP * 8;
constexpr int SM_BASE = SM_SORT + NPB_MAX * 4;
constexpr int SM_PAIR = SM_BASE + (NPB_MAX + 4) * 2;
constexpr int SM_IDX = SM_EID;
constexpr int SM_WR = SM_TAB;
static_assert(TILE_CAP <= 128 && TR >= 2 && SM_ES % 256 == 0 && NSTAGE == 2 && SM_BARS % 16 == 0 && SM_TINFO % 16 == 0 && SM_EID % 128 == 0 && SM_TAB % 1024 == 0 && SM_XU % 1024 == 0 && SM_TINFO % 8 == 0 && SM_OH % 16 == 0 && SM_SORT % 16 == 0 && SM_PAIR % 8 == 0, "align");
static_assert(P1B % 16 == 0 && P2B <= SM_P1 && NB_MAX <= 6 * 24 && SM_PAIR + 128 * 8 <= SM_XU && CH_MAX * 4 <= SM_SRC - SM_EID && SM_DEG >= 3 << 14, "alias");
static_assert(SMEM_BYTES <= 232448, "smem");
constexpr uint32_t C_BRK = 16  , C_CONT = 32, C_MORE = 64;
constexpr uint32_t ONE_F = 0x3F800000u;
constexpr int NONE = NPB_MAX;

__device__ __forceinline__ uint2 tile_info(uint32_t e) {
    const uint32_t y = (uint32_t)((int)e >> 16) & (ONE_F | 0x1FFFu);
    return make_uint2(e, (e & 0x1F000000u) ? y | 0x80000000u : y);
}
__device__ __forceinline__ bool unpad(uint32_t w1, int np, float ga, float gb, float& d0, float& d1, int& dv) {
    const int pad = (int)w1 < 0 ? (w1 >> 8) & 31 : 0;
    dv = 2 * np - 2 - pad + ((int)w1 > 127) + ((int)w1 >= (int)ONE_F);
    float t0 = TAU * 2 * np, t1 = t0;
    if (pad) {
        t0 = fmaxf(t0, d0 * (1.f / 1024)); t1 = fmaxf(t1, d1 * (1.f / 1024));
        asm volatile("tanh.approx.f32 %0, %0;\ntanh.approx.f32 %1, %1;" : "+f"(ga), "+f"(gb));
        d0 -= pad * (1.f + ga); d1 -= pad * (1.f + gb);
    }
    if (dv == 0) { d0 = d1 = EPS2; t0 = t1 = 0.f; }
    return __any_sync(~0u, d0 < t0 || d1 < t1);
}
__device__ __forceinline__ uint64_t desc_sw128(uint32_t a) {
    return (uint64_t)((a & 0x3FFFF) >> 4) | ((uint64_t)1 << 16) | ((uint64_t)64 << 32) | ((uint64_t)1 << 62);
}

__device__ __forceinline__ uint32_t sel(bool c, uint32_t a, uint32_t b) {
    uint32_t r; asm("{\n.reg .pred p;\nsetp.ne.u32 p, %1, 0;\nselp.b32 %0, %2, %3, p;\n}" : "=r"(r) : "r"((uint32_t)c), "r"(a), "r"(b)); return r;
}
__device__ __forceinline__ void tile_entry(uint8_t* smem, uint32_t sv, int dg, int mn, int t, int tl, int np, int done, uint32_t flags, int next) {
    const uint32_t nd = sv & 0xFFFF, w0 = nd * 128 + ((nd & 7) << 4);
    const int dv = min(max(dg - done, 0), 2 * np), r = 2 * np - dv;
    const bool gen = mn - done < 2 * np - 2;
    const uint32_t w1 = (uint32_t)np | flags | sel(gen || flags, C_BRK, 0u) | sel(r < 2, 0x8000u >> (8 * r), (r - 2) << 8);
    *(uint2*)(smem + SM_TINFO + tl * 32 + t * 8) = make_uint2(sel(dv, (sv >> 16) + done, 0) | (sel(gen, 13 + (np > 5) + (np > 8), np) << 16) | (next << 20) | ((uint32_t)dv << 27), w0 | sel(np, w1 << 16, 0u));
}
__device__ __noinline__ void tiles_many(uint8_t* smem, uint32_t sv, int dg, int mn, int id, int left, unsigned sm) {
    int* misc = (int*)(smem + SM_MISC);
    int nt = (left + NPMAX - 1) / NPMAX, tl = id >> 2, done = 0, nx = 0;
    if ((id & 3) == 0) { nx = atomicAdd(&misc[5], nt - 1); if (nx + nt - 1 > TILE_CAP) misc[1] = 1; }
    nx = __shfl_sync(sm, nx, id & 28);
    if (nx + nt - 1 > TILE_CAP) left = 0;
    uint32_t cont = 0;
    #pragma unroll 1
    while (left > 0) {
        const int np = (left + nt - 1) / nt;
        left -= np; nt--;
        tile_entry(smem, sv, dg, mn, id & 3, tl, np, done, cont | (left > 0 ? C_MORE : 0u), left > 0 ? nx : 0);
        tl = nx++; cont = C_CONT; done += 2 * np;
    }
}
__device__ __forceinline__ void tables(uint8_t* smem, uint32_t sbase, int id0, int ngroups) {
    const int t = id0 & 3;
    uint4 s4[3];
    uint32_t me[3], sv[3];
    #pragma unroll
    for (int k = 0; k < 3; k++) { s4[k] = lds128(sbase + SM_SORT + (id0 & ~3) * 4 + k * 512); me[k] = lds32(sbase + SM_SORT + id0 * 4 + k * 512); }
    #pragma unroll
    for (int k = 0; k < 3; k++) asm volatile("ld.shared.u16 %0, [%1];" : "=r"(sv[k]) : "r"(sbase + SM_BASE + (me[k] & 0xFFFF) * 2) : "memory");
    int mn[3], left[3];
    uint32_t more = 0;
    #pragma unroll
    for (int k = 0; k < 3; k++) {
        const int g = (id0 >> 2) + 32 * k, nx = ngroups + 4 + g;
        sv[k] = sv[k] << 16 | (me[k] & 0xFFFF);
        mn[k] = min(min(s4[k].x, s4[k].y), min(s4[k].z, s4[k].w)) >> 16;
        left[k] = ((max(max(s4[k].x, s4[k].y), max(s4[k].z, s4[k].w)) >> 16) + 1) >> 1;
        const bool two = left[k] > NPMAX;
        more |= two << k;
        tile_entry(smem, sv[k], me[k] >> 16, mn[k], t, sel(g >= ngroups + 4, ngroups, g), sel(two, min((left[k] + 1) >> 1, NPMAX), sel(left[k], max(left[k], NPMIN), 0)), 0, sel(two, C_MORE, 0u), sel(two, nx & 127, 0));
    }
    #pragma unroll 1
    for (int id = id0; __any_sync(~0u, more); id += 128) {
        const int nx = ngroups + 4 + (id >> 2);
        const bool odd = left[0] > 2 * NPMAX || ((more & 1) && nx >= TILE_CAP - TILE_X);
        const unsigned sm = __ballot_sync(~0u, odd);
        if (__builtin_expect(odd, 0)) tiles_many(smem, sv[0], me[0] >> 16, mn[0], id, left[0], sm);
        else if (more & 1) tile_entry(smem, sv[0], me[0] >> 16, mn[0], t, nx, left[0] >> 1, (left[0] + 1) & ~1, C_CONT, 0);
        __syncwarp();
        more >>= 1;
        sv[0] = sv[1]; sv[1] = sv[2]; me[0] = me[1]; me[1] = me[2]; mn[0] = mn[1]; mn[1] = mn[2]; left[0] = left[1]; left[1] = left[2];
    }
}
__device__ __forceinline__ uint32_t to_list(uint32_t sbase, uint32_t e, uint32_t bin) {
    uint32_t j; asm volatile("atom.shared.inc.u32 %0, [%1], 0x7fffffff;" : "=r"(j) : "r"(sbase + SM_MISC + 8) : "memory");
    j = min(j, 63u);
    sts32(sbase + SM_P1 + j * 4, e | ((j < 63 ? bin : 255u) << 16));
    return j;
}

template<bool LO32>
__global__ void __launch_bounds__(THREADS, 1)
gcn_kernel(const int* __restrict__ dst, unsigned* gbar, char* gs, const int* __restrict__ src, int E, int ch, int N, int npb, uint32_t magic,
           const __nv_bfloat16* __restrict__ x, const __nv_bfloat16* __restrict__ ea,
           const __nv_bfloat16* __restrict__ wa, const __nv_bfloat16* __restrict__ wb, const __nv_bfloat16* __restrict__ wc,
           const __nv_bfloat16* __restrict__ wu, const __nv_bfloat16* __restrict__ wv,
           __nv_bfloat16* out, int4 wrow, const __grid_constant__ CUtensorMap tm2, const __grid_constant__ CUtensorMap tmw,
           const __grid_constant__ CUtensorMap tmc, const __grid_constant__ CUtensorMap tmx)
{
    extern __shared__ __align__(1024) uint8_t smem[];
    int* cls = (int*)(smem + SM_CLS);
    int* misc = (int*)(smem + SM_MISC);
    uint32_t* xlist = (uint32_t*)(smem + SM_XLIST);
    WG0(); WS(0);
    const uint32_t sbase = smem_u32(smem);
    const int tid = threadIdx.x, lane = tid & 31;
    const int b = blockIdx.x, nb = gridDim.x;
    const int cnt = max(0, min(ch, E - b * ch));
    const int node0 = b * npb;
    auto src_ld = [&](int v) { bulk_ld(sbase + SM_XU + v * 8192, src + b * ch + v * 2048, min(max(cnt * 4 - v * 8192, 0), 8192), sbase + SM_SBAR + v * 8); };
    auto dst_ld = [&](int v) { bulk_ld(sbase + SM_IDX + v * 8192, dst + b * ch + v * 2048, min(max(cnt * 4 - v * 8192, 0), 8192), sbase + SM_ABAR + v * 8); };
    auto box_ld = [&](uint32_t dst, const CUtensorMap* tm, int col, int row, uint32_t bar) {
        asm volatile("cp.async.bulk.tensor.2d.shared::cluster.global.mbarrier::complete_tx::bytes [%0], [%1, {%3, %4}], [%2];"
            :: "r"(dst), "l"((uint64_t)tm), "r"(bar), "r"(col), "r"(row) : "memory");
    };
    auto w_ld = [&]() {
        mbar_expect(sbase + SM_ABAR + 24, 272 * 128);
        box_ld(sbase + SM_WR, &tmw, 0, wrow.y, sbase + SM_ABAR + 24); box_ld(sbase + SM_WR + 64 * 128, &tmc, 0, 0, sbase + SM_ABAR + 24);
        box_ld(sbase + SM_WR + 80 * 128, &tmw, 0, wrow.w, sbase + SM_ABAR + 24); box_ld(sbase + SM_WR + 144 * 128, &tmw, 0, wrow.x, sbase + SM_ABAR + 24);
        box_ld(sbase + SM_WR + 208 * 128, &tmw, 0, wrow.z, sbase + SM_ABAR + 24);
    };
    auto x_ld = [&](int k) {
        mbar_expect(sbase + SM_XBAR + k * 8, 16384);
        box_ld(sbase + SM_XU + k * 16384, &tmx, 0, node0 + 128 * k, sbase + SM_XBAR + k * 8);
    };
    uint32_t tag = 0;
    if (tid < 32) asm volatile("ld.relaxed.gpu.global.u32 %0, [%1];" : "=r"(tag) : "l"(gbar));
    if (tid >> 5 == 11) {
        if (elect_one()) {
            mbar_init(sbase + SM_ABAR, 1);
            asm volatile("fence.mbarrier_init.release.cluster;" ::: "memory");
            dst_ld(0);
        }
    }
    if (tid >= 384) {
        if (elect_one()) {
            const int v = (tid >> 5) & 3;
            if (v) mbar_init(sbase + SM_ABAR + v * 8, 1);
            asm volatile("fence.mbarrier_init.release.cluster;" ::: "memory");
            if (v == 1) dst_ld(v);
            if (v == 3) {
                mbar_init(sbase + SM_ABAR + 40, 1); mbar_init(sbase + SM_GBAR + 96 * 8, 32); mbar_init(sbase + SM_ABAR + 72, 384); mbar_init(sbase + SM_XBAR + 24, 512);
            }
            #pragma unroll 1
            for (int j = 0; j < 3; j++) {
                #pragma unroll
                for (int i = 0; i < 8; i++) mbar_init(sbase + SM_GBAR + (v * 24 + j * 8 + i) * 8, 32);
                if (j == 1 && v == 2) dst_ld(v);
            }
            if (tid < 480) {
                #pragma unroll
                for (int i = 0; i < 2; i++) { mbar_init(sbase + SM_BARS + (v * 2 + i) * 48, 64); mbar_init(sbase + SM_BARS + (v * 2 + i) * 48 + 8, 128); }
                mbar_init(sbase + SM_ABAR + 48 + v * 8, 128); mbar_init(sbase + SM_XBAR + v * 8, 1); mbar_init(sbase + SM_SBAR + v * 8, 1);
            }
            asm volatile("fence.mbarrier_init.release.cluster;" ::: "memory");
        }
    }
    if (tid >= 128 && tid < 132) asm volatile("prefetch.tensormap [%0];" :: "l"((uint64_t)(tid == 128 ? &tmw : tid == 129 ? &tmc : tid == 130 ? &tm2 : &tmx)) : "memory");
    const int warp = (int)__reduce_max_sync(~0u, (unsigned)tid >> 5);
    const int wg = warp >> 2, w = warp & 3;
    const int q = lane >> 2, t = lane & 3;
    const int ch0 = 16 * w + 2 * q;
    const int nn = max(0, min(npb, N - node0));
    if (sbase & 1023) __trap();

    sts32(sbase + (tid < NPB_MAX ? SM_DEG : SM_CNT) + tid * 4, tid < NPB_MAX ? 0 : 0xC0000000u);
    if (tid < NCLS + NB_MAX) cls[tid] = tid < NCLS ? 0 : (tid - NCLS) * CE + 64;
    else if (wg == 2) {
        if (w < 2) {
            *(uint32_t*)(smem + SM_OH + (tid & 63) * 4) = t != (q >> 1) ? 0u : (w == 0 ? 0x00003F00u : 0x3F000000u);
        } else if (w == 2) *(uint32_t*)(smem + SM_TAB + NPB_MAX * 128 + lane * 4) = 0u;
        else misc[lane] = lane == 5 ? TILE_CAP - TILE_X : 0;
    }
    if (warp == 13 && lane < WST * 2) sts32(sbase + SM_WL + 768 + lane * 4, NONE * 0x10001u);
    if (warp == 14) sts32(sbase + SM_TINFO + 96 * 32 + lane * 4, 0);
    if (warp == 15) sts32(sbase + SM_CLAIM + lane * 4, lane == 0 ? 3 : 0x40000000);
    if (wg < 3) {
        #pragma unroll 1
        for (int i = tid; i < P2B / 32; i += 384) { sts128(sbase + SM_P2 + i * 16, make_uint4(0, 0, 0, 0)); sts128(sbase + SM_P2 + P2B / 2 + i * 16, make_uint4(0, 0, 0, 0)); }
    }
    if (tid == 0) sts32(sbase + SM_PAIR, tag);
    if (wg < 3) { asm volatile("bar.sync 1, 384;" ::: "memory"); tag = lds32(sbase + SM_PAIR); }
    tag = (tag & 1) | 2;
    if (wg < 3) {
        const uint32_t d0 = ((NPB_MAX + ((2 * lane) & 15) + 16 * (b & 1)) * 4 | (tag << 14)) * 0x10001u, d1 = d0 + 0x40004u;
        #pragma unroll
        for (int i = 0; i < 3; i++) if (i < 2 || tid + 768 < P1B / 16) sts128(sbase + SM_P1 + (tid + 384 * i) * 16, make_uint4(d0, d0, d1, d1));
    }
    if (warp == 15 && elect_one()) w_ld();
    WS(1);
    __syncthreads();
    if (wg == 3) tag = (lds32(sbase + SM_PAIR) & 1) | 2;

    uint32_t ent[EPT];
    #pragma unroll
    for (int v = 0; v < EPT / 4; v++) {
        mbar_wait_c(sbase + SM_ABAR + v * 8, 0);
        if (((v == 0 && (warp == 13 || warp == 14)) || (v == 1 && warp == 15)) && elect_one()) src_ld(warp - 13);
        const uint32_t off = v * (THREADS * 4) + tid * 4;
        if (off < (uint32_t)cnt) {
            const uint32_t ia = sbase + SM_IDX + off * 4;
            const uint4 u = lds128(ia);
            uint32_t dv[4] = {u.x, u.y, u.z, u.w}, ps[4], ck[4];
            uint32_t* en = ent + 4 * v;
            #pragma unroll
            for (int k = 0; k < 4; k++) {
                dv[k] = min(dv[k], (uint32_t)(nb * npb - 1));
                ps[k] = __umulhi(dv[k], magic); en[k] = atoms_inc(sbase + SM_HIST + ps[k] * 4);
            }
            #pragma unroll
            for (int k = 0; k < 4; k++) {
                dv[k] = (dv[k] - ps[k] * npb) * 4 + (tag << 14);
                ck[k] = en[k] - ps[k] * CE;
                en[k] ^= ps[k] * 4 & 60;
            }
            if (__builtin_expect(max(max(ck[0], ck[1]), max(ck[2], ck[3])) >= 64 + CE, 0)) {
                #pragma unroll
                for (int k = 0; k < 4; k++) if (ck[k] >= 64 + CE) en[k] = to_list(sbase, dv[k], ps[k]);
            }
            #pragma unroll
            for (int k = 0; k < 4; k++)
                asm volatile("{\n.reg .pred p;\nsetp.ge.u32 p, %2, 64;\n@p st.shared.u16 [%0], %1;\n}" :: "r"(sbase + SM_P1 + 128 + en[k] * 2), "r"(dv[k]), "r"(en[k]) : "memory");
        }
    }
    WS(5);
    __syncthreads();
    auto send = [&](int o, uint32_t a, int bytes) {
        if (warp == 14 && elect_one()) {
            asm volatile("fence.proxy.async.shared::cta;" ::: "memory");
            bulk_st(gs + b * (P1B + P2B) + o, a, bytes);
            asm volatile("cp.async.bulk.commit_group;" ::: "memory");
        }
    };
    send(0, sbase + SM_P1, 256 + nb * (CE * 2));
    #pragma unroll
    for (int v = 0; v < EPT / 4; v++) {
        mbar_wait_c(sbase + SM_SBAR + v * 8, 0);
        const uint32_t off = v * (THREADS * 4) + tid * 4;
        if (off < (uint32_t)cnt) {
            const uint4 sv = lds128(sbase + SM_XU + off * 4);
            const uint32_t ss[4] = {sv.x, sv.y, sv.z, sv.w};
            #pragma unroll
            for (int k = 0; k < 4; k++) sts32(sbase + SM_P2 + ent[4*v+k] * 4, (ss[k] & 0xFFFF) | (((off + k) << 19) + (tag << 16)));
        }
    }
    WS(7);
    __syncthreads();
    send(P1B, sbase + SM_P2, 256 + nb * (CE * 4));
    WSL(8);

    const int ngroups = (nn + 3) >> 2;
    if (wg == 3) {
        asm volatile("setmaxnreg.dec.sync.aligned.u32 56;");
        WS(2);
        const char* const ga = as_pair((const char*)x + (w < 3 ? 0 : (size_t)node0 * 128) + (lane & 7) * 16, sbase + SM_PAIR + (tid & 127) * 8);
        const char* const gb = as_pair(w < 3 ? (const char*)ea + (lane & 1) * 16 : (const char*)out + (size_t)node0 * 128 + (lane & 7) * 16, sbase + SM_PAIR + (tid & 127) * 8);
        WS(3);
        const uint32_t dm = ((NPB_MAX + lane) * 4 | (tag << 14)) * 0x10001u;
        const uint32_t db = sbase + SM_DEG - (tag << 14);
        const char* gl = gs + ((tid & 127) >> 2) * (P1B + P2B) + t * 16;
        uint4 rl[5];
        #pragma unroll
        for (int i = 0; i < 5; i++) rl[i].w = ((tid & 127) >> 2) + 32 * i < nb ? 0 : dm;
        auto p2_ld = [&]() {
            mbar_expect(sbase + SM_ABAR + 40, nb * (CE * 4));
            box_ld(sbase + SM_P2, &tm2, P1B / 4 + 64 + b * CE, 0, sbase + SM_ABAR + 40);
        };
        asm volatile("cp.async.bulk.wait_group.read 0;" ::: "memory");
        asm volatile("bar.sync 6, 128;" ::: "memory");
        WSL(12);
        uint32_t spins = 0;
        #pragma unroll 1
        for (int r = 0;; r++) {
            #pragma unroll
            for (int i = 0; i < 5; i++) rl[i].x = rl[i].y = rl[i].z = dm;
            while (true) {
                #pragma unroll
                for (int i = 0; i < 5; i++) ld_unit(rl[i], gl + i * (32 * (P1B + P2B)), (rl[i].w ^ dm) & 0xC000);
                if (spins == 0) asm volatile("bar.sync 5, 512;" ::: "memory");
                if (++spins > (1u << 22)) __trap();
                if (!__any_sync(~0u, ((rl[0].w ^ dm) | (rl[1].w ^ dm) | (rl[2].w ^ dm) | (rl[3].w ^ dm) | (rl[4].w ^ dm)) & 0xC000)) break;
            }
            WS(4);
            uint32_t own = 0;
            #pragma unroll
            for (int i = 0; i < 5; i++) {
                const uint32_t bb = b << 16;
                own |= (min(min(rl[i].x ^ bb, rl[i].y ^ bb), min(rl[i].z ^ bb, rl[i].w ^ bb)) < 0x10000u) << i;
            }
            while (own != 0) {
                const int i = __ffs(own) - 1; own &= own - 1;
                const uint4 u = i == 0 ? rl[0] : i == 1 ? rl[1] : i == 2 ? rl[2] : i == 3 ? rl[3] : rl[4];
                const uint32_t e[4] = {u.x ^ (b << 16), u.y ^ (b << 16), u.z ^ (b << 16), u.w ^ (b << 16)};
                const uint32_t s = (((tid & 127) >> 2) + 32 * i << 16) + (4 * r + t << 26);
                int n;
                asm volatile("atom.shared.add.u32 %0, [%1], %2;" : "=r"(n) : "r"(sbase + SM_MISC), "r"((e[0] < 0x10000u) + (e[1] < 0x10000u) + (e[2] < 0x10000u) + (e[3] < 0x10000u)) : "memory");
                #pragma unroll
                for (int k = 0; k < 4; k++) asm volatile("red.shared.add.u32 [%0], 1;" :: "r"(db + min(e[k], dm & 0xFFFF)) : "memory");
                if (n + 4 > XCAP) { misc[1] = 1; n = 0; }
                #pragma unroll
                for (int k = 0; k < 4; k++) if (e[k] < 0x10000u) xlist[n++] = e[k] | (s + (k << 24));
            }
            __syncwarp();
            if (__builtin_expect(!__any_sync(~0u, t == 3 && min(min(min(rl[0].w, rl[1].w), min(rl[2].w, rl[3].w)), rl[4].w) < 0x1000000u), 1)) break;
            if (r == 3) { misc[1] = 1; break; }
            #pragma unroll
            for (int i = 0; i < 5; i++) rl[i].w = __shfl_sync(~0u, rl[i].w, lane | 3) < 0x1000000u ? 0 : dm;
            gl += 64;
        }
        WS(11);
        asm volatile("bar.sync 7, 512;" ::: "memory");
        auto rest_ld = [&]() {
            if (w == 2 && elect_one()) {
                p2_ld(); x_ld(2);
            }
            __syncwarp();
        };
        WS(9);
        {
            int dg[3], cl[3], cr[3];
            #pragma unroll
            for (int k = 0; k < 3; k++) dg[k] = lds32(sbase + SM_DEG + ((tid & 127) + 128 * k) * 4);
            const uint2 m01 = lds64(sbase + SM_MISC);
            const int xi = (tid + 96) & 127, nx = m01.y ? 0 : m01.x;
            const uint32_t xe = xlist[xi];
            #pragma unroll
            for (int k = 0; k < 3; k++) {
                cl[k] = NCLS - 1 - (dg[k] <= 40 ? dg[k] : min(41 + ((dg[k] - 41) >> 3), NCLS - 1));
                cr[k] = atoms_inc(sbase + ((tid & 127) + 128 * k < nn ? SM_CLS + cl[k] * 4 : SM_DEG + NPB_MAX * 4));
            }
            rest_ld();
            asm volatile("bar.sync 6, 128;" ::: "memory");
            WS(13);
            const uint2 c = lds64(sbase + SM_CLS + lane * 8);
            uint32_t inc = c.x + c.y;
            #pragma unroll
            for (int o = 1; o < 32; o <<= 1) { const uint32_t y = __shfl_up_sync(~0u, inc, o); if (lane >= o) inc += y; }
            inc = (inc - c.x - c.y) | (inc - c.y) << 16;
            #pragma unroll
            for (int k = 0; k < 3; k++) {
                const int id = (tid & 127) + 128 * k;
                const uint32_t e = __shfl_sync(~0u, inc, cl[k] >> 1);
                const uint32_t pos = id < nn ? (cl[k] & 1 ? e >> 16 : e & 0xFFFF) + cr[k] : id, nd = id < nn ? id : NONE;
                sts32(sbase + SM_SORT + pos * 4, nd | min(dg[k], 65535) << 16);
                asm volatile("st.shared.u16 [%0], %1;" :: "r"(sbase + SM_WL + pos * 2), "r"(nd) : "memory");
            }
            if (tid == 511) misc[4] = (nn - c.y + 3) >> 2;
            asm volatile("bar.sync 4, 512;" ::: "memory");
            WS(14);
            uint32_t xs = 0x80000000u, xv = tag << 16;
            auto x_get = [&]() { asm volatile("ld.relaxed.gpu.global.u32 %0, [%1];" : "=r"(xv) : "l"(gs + ((xe >> 16) & 0xFF) * (P1B + P2B) + P1B + (xe >> 24) * 4) : "memory"); };
            if (xi < nx) {
                asm volatile("atom.shared.add.u32 %0, [%1], 4;" : "=r"(xs) : "r"(db + (SM_CNT - SM_DEG) + (xe & 0xFFFF)) : "memory");
                x_get();
            }
            tables(smem, sbase, (tid + 32) & 127, ngroups);
            __syncwarp();
            while (__any_sync(~0u, ((xv >> 16) & 3) != tag)) { if (((xv >> 16) & 3) != tag) x_get(); if (++spins > (1u << 22)) __trap(); }
            if (xs < 4 * SLOT_CAP) {
                sts32(sbase + SM_EID + xs, ((xe >> 16) & 0xFF) * ch + (xv >> 19));
                asm volatile("st.shared.u16 [%0], %1;" :: "r"(sbase + SM_SRC + (xs >> 1)), "r"(xv) : "memory");
            }
            mbar_arrive(sbase + SM_XBAR + 24);
            asm volatile("bar.sync 6, 128;" ::: "memory");
        }
        WS(10);
        WGD();
        const int r4 = lane >> 3, c8 = lane & 7;
        const uint32_t sb = __reduce_or_sync(~0u, sbase);
        if (w < 3) {
            const char* gx = ga; const char* ge = gb;
            const uint32_t gx0 = (uint32_t)(uint64_t)gx, ge0 = (uint32_t)(uint64_t)ge, hi = (uint64_t)gx >> 32, he = (uint64_t)ge >> 32;
            const int s = (lane >> 1) & 3;
            const uint32_t xs0 = sb + SM_XS + w * NSTAGE * XS_BYTES;
            const uint32_t es0 = sb + SM_ES + w * NSTAGE * ES_BYTES + r4 * 64 + (((lane ^ (r4 >> 1)) & 1) << 4) + (s >> 1) * 256 + (s & 1) * 32;
            const uint32_t bars = sb + SM_BARS + w * 96;
            const uint32_t xoffA = (2 * r4) * 128 + ((c8 ^ (2 * r4)) << 4), xoffB = (2 * r4 + 1) * 128 + ((c8 ^ (2 * r4 + 1)) << 4);
            uint64_t pol;
            asm volatile("createpolicy.fractional.L2::evict_first.b64 %0, 1.0;" : "=l"(pol));
            uint32_t first = 1;
            WS(15);
            uint32_t ph = 1, cur = w;
            uint32_t hist = 96 * 0x010101u;
            auto done3 = [&]() { mbar_arrive(sb + SM_GBAR + ((hist >> 16) & 0xFF) * 8); };
            const uint32_t ca = sb + SM_CLAIM + lane * 4, pa = sb + SM_TINFO + r4 * 8;
            const uint2 p0 = lds64(pa + w * 32);
            const bool go = lds32(sb + SM_MISC + 4) == 0 && nn > 0;
            uint32_t pw = go ? p0.x : 0, brk = (p0.y >> 16) & C_BRK;
            const uint32_t se0 = sb + SM_EID + s * 4, xab = xoffB - xoffA, das = 2 * (xs0 + xoffA) + XS_BYTES, des = 2 * es0 + ES_BYTES, brs = 2 * bars + 48;
            uint32_t da = xs0 + xoffA, de = es0, br = bars;
            #pragma unroll 1
            while (true) {
                const uint32_t pt = __reduce_or_sync(~0u, pw);
                uint32_t se, sx;
                asm("dp2a.lo.u32.u32 %0, %1, 4, %2;" : "=r"(se) : "r"(pw), "r"(se0));
                asm("dp2a.lo.u32.u32 %0, %1, 2, %2;" : "=r"(sx) : "r"(pw), "r"(sb + SM_SRC));
                const int dv = pw >> 27;
                const uint32_t db = da + xab;
                const uint32_t sel = (pt >> 16) & 15, nx = (pt >> 20) & 127;
                uint32_t g;
                auto claim = [&]() { asm volatile("atom.shared.add.u32 %0, [%1], %2;" : "=r"(g) : "r"(ca), "r"(nx == 0 ? 1u : 0u) : "memory"); };
                if (sel == 0) break;
                if (first) { asm volatile("bar.sync 3, 480;" ::: "memory"); first = 0; WSL(6); }
                switch (sel) {
#define CASE(L, P, GEN) case L: { \
                        uint32_t oe[(P + 1) / 2], o[P]; \
                        _Pragma("unroll") for (int j = 0; j < (P + 1) / 2; j++) oe[j] = lds32(se + j * 16); \
                        _Pragma("unroll") for (int j = 0; j < P; j++) o[j] = lds32(sx + j * 4); \
                        mbar_wait_h(br + 8, ph); \
                        _Pragma("unroll") for (int j = 0; j < (P + 1) / 2; j++) \
                            if (LO32) { if (!GEN && 2 * j + 2 < P) cpe<false>(he, de + j * 512, oe[j], ge0, 0, 0, pol); \
                                else if (2 * j + 1 < NPMAX || s < 2) cpe<true>(he, de + j * 512, oe[j], ge0, 4 * j + s, dv, pol); } \
                            else if (!GEN && 2 * j + 2 < P) cp16e(de + j * 512, ge, oe[j], pol); else if (2 * j + 1 < NPMAX || s < 2) cp16z<32>(de + j * 512, ge, oe[j], 4 * j + s, dv, pol); \
                        _Pragma("unroll") for (int j = 0; j < P - 1; j++) { \
                            if (LO32) { cpx<0, GEN>(hi, da + j * 1024, o[j], gx0, 2 * j, dv); cpx<1, GEN>(hi, db + j * 1024, o[j], gx0, 2 * j + 1, dv); } \
                            else if (GEN) { cp16z<128>(da + j * 1024, gx, o[j] & 0xFFFFu, 2 * j, dv, 0); cp16z<128>(db + j * 1024, gx, o[j] >> 16, 2 * j + 1, dv, 0); } \
                            else { cp16i<128>(da + j * 1024, gx, o[j] & 0xFFFFu); cp16i<128>(db + j * 1024, gx, o[j] >> 16); } } \
                        if (LO32) { cpx<0, true>(hi, da + (P - 1) * 1024, o[P - 1], gx0, 2 * P - 2, dv); cpx<1, true>(hi, db + (P - 1) * 1024, o[P - 1], gx0, 2 * P - 1, dv); } \
                        else { cp16z<128>(da + (P - 1) * 1024, gx, o[P - 1] & 0xFFFFu, 2 * P - 2, dv, 0); cp16z<128>(db + (P - 1) * 1024, gx, o[P - 1] >> 16, 2 * P - 1, dv, 0); } \
                    } break;
                    CASE(6, 6, false) CASE(7, 7, false) CASE(8, 8, false) CASE(9, 9, false) CASE(10, 10, false) CASE(11, 11, false)
                    CASE(15, NPMAX, true) CASE(14, 8, true) default: CASE(13, 5, true)
#undef CASE
                }
                claim();
                mbar_cp_arrive(br);
                done3();
                g = __reduce_min_sync(~0u, g);
                {
                    const uint2 e = lds64(pa + (nx == 0 ? g : nx) * 32);
                    const uint2 v = tile_info(e.y);
                    pw = e.x;
                    asm volatile("st.shared.v2.u32 [%0], {%1, %2};" :: "r"(br + 16 + r4 * 8), "r"(v.x), "r"((v.y & ~C_BRK) | brk) : "memory");
                    brk = v.y & C_BRK;
                }
                mbar_arrive(br);
                hist = (hist << 8) | (nx == 0 ? cur : 96u);
                cur = nx == 0 ? g : cur;
                ph ^= br != bars; br = brs - br; da = das - da; de = des - de;
            }
            if (first) asm volatile("bar.sync 3, 480;" ::: "memory");
            if (go) {
                mbar_wait(sb + SM_ABAR + 72, 0);
                const int g0 = 3 * max((ngroups + 2) / 3 - TR, 0) + w;
                uint32_t ra[TR], gb[TR]; uint4 xv[TR], xu[TR]; char* po[TR];
                const int gz = misc[4];
                #pragma unroll
                for (int k = 0; k < TR; k++) {
                    uint32_t nd;
                    asm volatile("ld.shared.u16 %0, [%1];" : "=r"(nd) : "r"(sb + SM_WL + (g0 + 3 * k) * 8 + r4 * 2) : "memory");
                    xv[k] = __ldg((const uint4*)(gx + (size_t)(node0 + (nd == NONE ? 0u : nd)) * 128));
                    const uint32_t ro = sb + nd * 128 + ((c8 ^ (nd & 7)) << 4);
                    xu[k] = lds128(ro + SM_XU);
                    const bool some = g0 + 3 * k < gz;
                    ra[k] = some ? ro + SM_TAB : sb + SM_MISC + 64;
                    gb[k] = some ? sb + SM_GBAR + (g0 + 3 * k) * 8 : sb + SM_ABAR + 72;
                    po[k] = nd != NONE ? (char*)out + (size_t)(node0 + nd) * 128 + c8 * 16 : nullptr;
                    asm volatile("" : "+r"(ra[k]), "+r"(gb[k]), "+l"(po[k]));
                }
                #pragma unroll 1
                for (int k = 0; k < 3; k++) {
                    mbar_wait(k < 2 ? br + 8 : sb + SM_ABAR + 48 + w * 8, k < 2 ? ph : 0);
                    done3(); hist <<= 8;
                    ph ^= br != bars; br = brs - br;
                }
                #pragma unroll
                for (int k = 0; k < TR; k++) {
                    mbar_wait_c(gb[k], 0);
                    uint4 a = lds128(ra[k]);
                    finish(a, xu[k], xv[k]);
                    if (po[k]) *(uint4*)po[k] = a;
                }
            }
            cp_wait<0>();
        } else {
            const char* gx = ga; const char* ob = gb;
            mbar_wait(sb + SM_ABAR + 72, 0);
            WS(15);
            if (b == 0 && lane == 0) asm volatile("red.relaxed.gpu.global.add.u32 [%0], 1;" :: "l"(gbar) : "memory");
            const int rounds = misc[1] ? 0 : max((ngroups + 2) / 3 - TR, 0);
            const int gz = misc[4], fast = __reduce_min_sync(~0u, min(rounds, gz / 3));
            uint32_t wl = sb + SM_WL + r4 * 2, gbar = sb + SM_GBAR;
            auto row_at = [&](uint32_t a) { uint32_t n; asm volatile("ld.shared.u16 %0, [%1];" : "=r"(n) : "r"(a) : "memory"); return n; };
            auto fetch = [&](uint32_t n, uint4& v) {
                asm volatile("{\n.reg .b64 p;\nmad.wide.u32 p, %5, 128, %4;\nld.global.nc.L1::no_allocate.v4.u32 {%0,%1,%2,%3}, [p];\n}"
                             : "=r"(v.x), "=r"(v.y), "=r"(v.z), "=r"(v.w) : "l"(gx), "r"(n));
            };
            auto store = [&](uint32_t n, const uint4& a) {
                asm volatile("{\n.reg .b64 p;\nmad.wide.u32 p, %1, 128, %0;\nst.global.v4.u32 [p], {%2,%3,%4,%5};\n}" :: "l"(ob), "r"(n), "r"(a.x), "r"(a.y), "r"(a.z), "r"(a.w) : "memory");
            };
            uint32_t n0[3]; uint4 x0[3];
            if (fast) {
                #pragma unroll
                for (int r = 0; r < 3; r++) { n0[r] = row_at(wl + r * 8); fetch(n0[r], x0[r]); }
            }
            #pragma unroll 1
            for (int k = 0; k < fast; k++) {
                wl += 24;
                #pragma unroll
                for (int r = 0; r < 3; r++) {
                    const uint32_t nd = n0[r], ro = sb + nd * 128 + ((c8 ^ (nd & 7)) << 4);
                    const uint4 xu = lds128(ro + SM_XU);
                    n0[r] = row_at(wl + r * 8);
                    mbar_wait(gbar + r * 8, 0);
                    uint4 a = lds128(ro + SM_TAB);
                    finish(a, xu, x0[r]);
                    fetch(n0[r], x0[r]);
                    store(nd, a);
                }
                gbar += 24;
            }
            #pragma unroll 1
            for (int g = 3 * fast; g < 3 * rounds; g++) {
                const uint32_t nd = row_at(sb + SM_WL + r4 * 2 + g * 8), ro = sb + nd * 128 + ((c8 ^ (nd & 7)) << 4);
                uint4 xv, a = make_uint4(0, 0, 0, 0);
                fetch(nd, xv);
                if (g < gz) { mbar_wait(sb + SM_GBAR + g * 8, 0); a = lds128(ro + SM_TAB); }
                finish(a, lds128(ro + SM_XU), xv);
                store(nd, a);
            }
        }
    } else {
        asm volatile("setmaxnreg.inc.sync.aligned.u32 152;");
        float4 lgh[2 * NPMAX];
        uint32_t wf[40], wn[16], wt[16];
        const uint32_t mo0 = sbase + SM_TAB + (8 * (lane >> 4) + (lane & 7)) * 128 + (((2 * w + ((lane >> 3) & 1)) ^ (lane & 7)) << 4);
        mbar_wait_c(sbase + SM_ABAR + 24, 0);
        {
            const uint32_t wo = sbase + SM_WR + (2 * t) * 128 + ((ch0 * 2) ^ (t * 32));
            #pragma unroll
            for (int ks = 0; ks < 9; ks++) {
                uint32_t wr[4];
                #pragma unroll
                for (int i = 0; i < 4; i++) wr[i] = lds32((wo ^ ((i & 1) * 16)) + (16 * ks + (i & 1) + 4 * (i & 2)) * 128);
                if (ks < 5) make_wfrag<true>(wf + 4 * ks, wr); else make_wfrag<false>(wf + 4 * ks, wr);
            }
            #pragma unroll
            for (int ks = 0; ks < 4; ks++) { ldsm4t(wn + 4 * ks, mo0 + (144 + 16 * ks) * 128); ldsm4t(wt + 4 * ks, mo0 + (208 + 16 * ks) * 128); }
            if (wg == 2) {
                const uint32_t a = sbase + SM_WC + (16 * w + q) * 32 + t * 4, sw = (q >> 2) << 4;
                sts32(a + sw, wf[16]); sts32(a + 256 + sw, wf[17]); sts32(a + (sw ^ 16), wf[18]); sts32(a + 256 + (sw ^ 16), wf[19]);
                asm volatile("fence.proxy.async.shared::cta;" ::: "memory");
            }
            #pragma unroll
            for (int i = 0; i < 36; i++) asm volatile("" : "+r"(wf[i]));
        }
        WS(9);
        constexpr int NU = 6;
        const uint32_t dm = ((NPB_MAX + lane) * 4 | (tag << 14)) * 0x10001u;
        const char* const g1 = gs + (tid >> 4) * (P1B + P2B) + 256 + b * (CE * 2) + (lane & 15) * 8;
        const bool last = 2 * warp + 24 * (NU - 1) < nb;
        uint2 r1[NU];
        #pragma unroll
        for (int i = 0; i < NU; i++) r1[i] = make_uint2(dm, (tid >> 4) + 24 * i < nb ? 0 : dm);
        uint32_t spins = 0;
        asm volatile("bar.sync 5, 512;" ::: "memory");
        while (true) {
            #pragma unroll
            for (int i = 0; i < NU; i++) ld_unit(r1[i], g1 + i * (24 * (P1B + P2B)), (r1[i].y ^ dm) & 0xC000);
            #pragma unroll
            for (int i = 0; i < 4; i++) sts128(mo0 + wg * 16384 + 8192 + i * 2048, make_uint4(wt[4*i], wt[4*i+1], wt[4*i+2], wt[4*i+3]));
            uint32_t bad = 0;
            #pragma unroll
            for (int i = 0; i < NU; i++) bad |= r1[i].y ^ dm;
            const bool more = __any_sync(~0u, bad & 0xC000);
            if (spins == 0) WS(2);
            if (!more) break;
            if (++spins > (1u << 22)) __trap();
        }
        WS(3);
        const uint32_t db = sbase + SM_DEG - (tag << 14);
        uint32_t rk[NU][4];
        #pragma unroll
        for (int i = 0; i < NU; i++) {
            #pragma unroll
            for (int k = 0; k < 4; k++) {
                asm("dp2a.lo.u32.u32 %0, %1, %2, %3;" : "=r"(rk[i][k]) : "r"(k < 2 ? r1[i].x : r1[i].y), "r"(k & 1 ? 0x100u : 1u), "r"(db));
                if (i < NU - 1 || last) asm volatile("red.shared.add.u32 [%0], 1;" :: "r"(rk[i][k]) : "memory");
            }
        }
        WS(10);
        asm volatile("bar.sync 7, 512;" ::: "memory");
        WS(11);
        {
            const uint32_t ev = (lds32(sbase + SM_DEG + tid * 4) + 1) & ~1u;
            uint32_t inc = ev, base = 0;
            #pragma unroll
            for (int o = 1; o < 32; o <<= 1) { const uint32_t y = __shfl_up_sync(~0u, inc, o); if (lane >= o) inc += y; }
            if (lane == 31) {
                asm volatile("atom.shared.add.u32 %0, [%1], %2;" : "=r"(base) : "r"(sbase + SM_MISC + 24), "r"(inc) : "memory");
                if (base + inc > SLOT_CAP) misc[1] = 1;
            }
            const uint32_t s0 = min(__shfl_sync(~0u, base, 31) + inc - ev, SLOT_CAP);
            sts32(sbase + SM_CNT + tid * 4, 4 * s0);
            asm volatile("st.shared.u16 [%0], %1;" :: "r"(sbase + SM_BASE + tid * 2), "r"(s0) : "memory");
        }
        asm volatile("bar.arrive 4, 512;" ::: "memory");
        asm volatile("bar.sync 1, 384;" ::: "memory");
        WS(13);
        #pragma unroll
        for (int i = 0; i < NU; i++) {
            if (i < NU - 1 || last) {
                #pragma unroll
                for (int k = 0; k < 4; k++) asm volatile("atom.shared.add.u32 %0, [%0+%1], 4;" : "+r"(rk[i][k]) : "n"(SM_CNT - SM_DEG) : "memory");
            }
        }
        WS(14);
        uint4 r2[NU];
        mbar_wait_c(sbase + SM_ABAR + 40, 0);
        if (warp == 11 && elect_one()) { x_ld(1); x_ld(0); }
        WS(4);
        #pragma unroll
        for (int i = 0; i < NU; i++) r2[i] = lds128(sbase + SM_P2 + (i < NU - 1 ? tid + 384 * i : min(tid + 384 * i, P2B / 16 - 1)) * 16);
        while (true) {
            uint32_t bad = 0;
            #pragma unroll
            for (int i = 0; i < NU; i++) if (i < NU - 1 || last) bad |= (r2[i].x ^ (tag << 16)) & ~(rk[i][0] >> 14);
            if (__builtin_expect(!__any_sync(~0u, bad & 0x30000), 1)) break;
            #pragma unroll
            for (int i = 0; i < NU; i++)
                ld_unit(r2[i], g1 + (P1B + b * (CE * 2) + (lane & 15) * 8 + i * (24 * (P1B + P2B))), (i < NU - 1 || last) && ((r2[i].x ^ (tag << 16)) & ~(rk[i][0] >> 14) & 0x30000));
            if (++spins > (1u << 22)) __trap();
        }
        WS(16);
        const uint32_t sbu = __reduce_or_sync(~0u, sbase);
        auto place = [&](uint32_t s4, uint32_t v, uint32_t eb) {
            asm volatile("{\n.reg .pred p;\nsetp.lt.u32 p, %0, %5;\n@p st.shared.u32 [%1], %2;\n@p st.shared.u16 [%3], %4;\n}"
                         :: "r"(s4), "r"(sbu + SM_EID + s4), "r"(eb + (v >> 19)), "r"(sbu + SM_SRC + (s4 >> 1)), "r"(v), "n"(4 * SLOT_CAP) : "memory");
        };
        #pragma unroll
        for (int i = 0; i < NU; i++) {
            const uint32_t eb = ((tid >> 4) + 24 * i) * ch;
            if (i < NU - 1 || last) { place(rk[i][0], r2[i].x, eb); place(rk[i][1], r2[i].y, eb); place(rk[i][2], r2[i].z, eb); place(rk[i][3], r2[i].w, eb); }
        }
        WS(1);
        WGD();
        asm volatile("bar.arrive 3, 480;" ::: "memory");
        {
        int lane;
        asm volatile("mov.u32 %0, %%laneid;" : "=r"(lane));
        const int q = lane >> 2, t = lane & 3, ch0 = 16 * w + 2 * q;
        const uint32_t sbase = sbu;
        { const uint2 z = lds64(sbase + SM_OH + 8); wf[37] = z.x; wf[38] = z.y; }
        const uint32_t c2 = __shfl_sync(~0u, ch0 * 2, lane), t8 = __shfl_sync(~0u, t * 8, lane);
        float g[4 * NPMAX], h[4 * NPMAX];
        float4 cyr = make_float4(0.f, 0.f, 0.f, 0.f);
        {
            const uint32_t mo = sbase + (8 * (lane >> 4) + (lane & 7)) * 128 + (((2 * w + ((lane >> 3) & 1)) ^ (lane & 7)) << 4);
            mbar_wait_c(sbase + SM_XBAR + wg * 8, 0);
            WSP(4);
            node_mma2(g, h, wn, desc_sw128(sbase + SM_XU + wg * 16384));
            TileMMA<8>::wait_g(g);
            node_rows(mo + SM_TAB + wg * 16384, g);
            TileMMA<8>::wait_h(h);
            WSP(5);
            #pragma unroll
            for (int i = 0; i < 4; i++) {
                const uint4 f = lds128(mo + SM_TAB + wg * 16384 + 8192 + i * 2048);
                wn[4*i] = f.x; wn[4*i+1] = f.y; wn[4*i+2] = f.z; wn[4*i+3] = f.w;
            }
            __syncwarp();
            node_rows(mo + SM_TAB + wg * 16384 + 8192, h);
            mbar_arrive(sbase + SM_XBAR + 24);
            WSP(2);
            node_mma2(g, h, wn, desc_sw128(sbase + SM_XU + wg * 16384));
            TileMMA<8>::wait_g(g);
            asm volatile("bar.sync %0, 128;" :: "r"(8 + wg) : "memory");
            node_rows(mo + SM_XU + wg * 16384, g);
            TileMMA<8>::wait_h(h);
            WSP(3);
            asm volatile("bar.sync %0, 128;" :: "r"(8 + wg) : "memory");
            node_rows(mo + SM_XU + wg * 16384 + 8192, h);
            mbar_arrive(sbase + SM_ABAR + 72);
            mbar_wait_c(sbase + SM_XBAR + 24, 0);
            if (__builtin_expect(lds32(sbase + SM_MISC + 4) != 0, 0)) { slow_bin(x, ea, src, dst, wa, wb, wc, wu, wv, out, E, node0, nn, 384); return; }
            WS(6);
        }
        const uint64_t wcd = __reduce_or_sync(~0u, (((sbase + SM_WC) & 0x3FFFF) >> 4) | (8u << 16)) | EDHI;
        const uint32_t bar0 = __reduce_or_sync(~0u, sbase + SM_BARS + wg * 96);
        const uint32_t xd0 = __reduce_or_sync(~0u, (((sbase + SM_XS + wg * NSTAGE * XS_BYTES) & 0x3FFFF) >> 4) | (1u << 16));
        const uint32_t ed0 = __reduce_or_sync(~0u, (((sbase + SM_ES + wg * NSTAGE * ES_BYTES) & 0x3FFFF) >> 4) | (8u << 16));
        const uint64_t ohd = __reduce_or_sync(~0u, (((sbase + SM_OH) & 0x3FFFF) >> 4) | (8u << 16));
        const uint32_t tabx = __reduce_or_sync(~0u, sbase + SM_TAB);
        const uint32_t bars = __reduce_or_sync(~0u, 2 * bar0 + 48), xds = __reduce_or_sync(~0u, 2 * xd0 + XS_BYTES / 16), eds = __reduce_or_sync(~0u, 2 * ed0 + ES_BYTES / 16);
        uint32_t bar = bar0, xd = xd0, ed = ed0, ph = 0, code, w1, ta, pta = NONE * 128 + c2;
        float pn0 = 0.f, pd0 = 1.f, pn1 = 0.f, pd1 = 1.f;
        uint2 ni = tile_info(lds32(sbase + SM_TINFO + wg * 32 + t * 8 + 4));
        auto fetch_a = [&]() {
            ta = (ni.x & 0xFFFFu) ^ c2;
            wf[36] = lds32(tabx + ta); wf[39] = lds32(tabx + ta);
            code = __reduce_or_sync(~0u, ni.y);
        };
        auto emit = [&]() { sts32(tabx + pta, pack_bf16(pn0 * rcpf(pd0), pn1 * rcpf(pd1))); };
        auto carry = [&]() {
            if (w1 & C_CONT) { pn0 += cyr.x; pd0 += cyr.y; pn1 += cyr.z; pd1 += cyr.w; }
            if (w1 & C_MORE) { cyr = make_float4(pn0, pd0 - EPS2, pn1, pd1 - EPS2); pn0 = pn1 = 0.f; pta = NONE * 128 + c2; }
        };
        auto next = [&](uint32_t fb) {
            pta = ta;
            w1 = ni.y;
            ni = lds64(fb + 16 + t8);
        };
        fetch_a();
        while (true) {
            switch (code & 15) {
                default: goto finished;
#define TILE(P) { \
                    float dmin; \
                    do { \
                        mbar_wait_c(bar, ph); \
                        TileMMA<P>::issue(g, h, wf, xd | (0x40000040ull << 32), ed | EDHI, ohd, wcd); \
                        const uint32_t eb = bar + 8; \
                        ph ^= bar != bar0; bar = bars - bar; xd = xds - xd; ed = eds - ed; \
                          \
                        asm volatile("{\n.reg .pred p;\nsetp.eq.u32 p, %0, 77;\n@p trap;\n}" :: "r"(xds) : "memory"); \
                        emit(); next(eb - 8); \
                        TileMMA<P>::wait_g(g); fetch_a(); TileMMA<P>::wait_h(h); \
                        mbar_arrive(eb); \
                        float m1; \
                        asm("set.gt.f32.f32 %0, %1, 0f0000007F;" : "=f"(m1) : "f"(__uint_as_float(w1))); \
                        epi_fast<P>(g, h, m1, __uint_as_float(w1), pn0, pd0, pn1, pd1, dmin); \
                    } while (!(__any_sync(~0u, dmin < TAU * 2 * P) | ((code & 31) != P))); \
                    if (__builtin_expect(__any_sync(~0u, (int)w1 < 0 || dmin < TAU * 2 * P), 0)) { \
                        int dv; \
                        if (unpad(w1, P, g[P > 1 ? 4 * P - 7 : 0], g[P > 1 ? 4 * P - 5 : 0], pd0, pd1, dv)) { \
                            FBT(2); \
                            epi_dump<P>(g, h, lgh); \
                            FBT(3); \
                            const float4 r = epi_exact(lgh, P, dv); \
                            pn0 = r.x; pd0 = r.y; pn1 = r.z; pd1 = r.w; \
                            if (pd0 != 77.f) FBT(4); \
                        } \
                    } \
                    if (code & C_BRK) { carry(); if (P != 11 && (code & 15) == P) goto L##P; } \
                    if (P == 11) {         \
                        const uint32_t a = tabx + (SM_WC - SM_TAB) + (c2 & 0x60) * 16 + (c2 & 0x1C) * 8 + (t8 >> 1), sw = c2 & 16; \
                        wf[16] = lds32(a + sw); wf[17] = lds32(a + 256 + sw); wf[18] = lds32(a + (sw ^ 16)); wf[19] = lds32(a + 256 + (sw ^ 16)); \
                    } }
#define CASE(P, UP, DN) case P: L##P: TILE(P) \
                    if (P > NPMIN && (code & 15) == P - 1) goto L##DN; \
                    if (P <= 6 && (code & 15) == 0) goto finished; \
                    if ((code & 15) == UP) goto L##UP; \
                    break;
                CASE(11, 11, 10) CASE(10, 11, 9) CASE(9, 10, 8) CASE(8, 9, 7) CASE(7, 8, 6) CASE(6, 7, 5) CASE(5, 6, 4) CASE(4, 5, 4)
#undef CASE
#undef TILE
            }
        }
finished:
        emit();
        mbar_arrive(sbase + SM_ABAR + 48 + wg * 8);
        }
    }
    WS(17); WG1();
}

}

extern "C" void kernel_launch(void* const* d_in, const int* in_sizes, int n_in, void* d_out, int out_size) {
    const __nv_bfloat16* x = (const __nv_bfloat16*)d_in[0];
    const __nv_bfloat16* ea = (const __nv_bfloat16*)d_in[1];
    const int* src = (const int*)d_in[2];
    const int* dst = (const int*)d_in[3];
    const __nv_bfloat16* wa = (const __nv_bfloat16*)d_in[4];
    const __nv_bfloat16* wb = (const __nv_bfloat16*)d_in[5];
    const __nv_bfloat16* wc = (const __nv_bfloat16*)d_in[6];
    const __nv_bfloat16* wu = (const __nv_bfloat16*)d_in[7];
    const __nv_bfloat16* wv = (const __nv_bfloat16*)d_in[8];
    __nv_bfloat16* out = (__nv_bfloat16*)d_out;
    int N = in_sizes[0] / 64, E = in_sizes[2];
    static int sms = 0;
    static CUtensorMap tm2;
    static bool tm_ok = false;
    typedef CUresult (*EncFn)(CUtensorMap*, CUtensorMapDataType, cuuint32_t, void*, const cuuint64_t*, const cuuint64_t*, const cuuint32_t*,
                              const cuuint32_t*, CUtensorMapInterleave, CUtensorMapSwizzle, CUtensorMapL2promotion, CUtensorMapFloatOOBfill);
    static void* fn = nullptr;
    static void* gp = nullptr; static void* gb = nullptr;
    if (!sms) {
        cudaDeviceGetAttribute(&sms, cudaDevAttrMultiProcessorCount, 0);
        cudaDriverEntryPointQueryResult qr;
        cudaGetDriverEntryPoint("cuTensorMapEncodeTiled", &fn, cudaEnableDefault, &qr);
        cudaGetSymbolAddress(&gp, g_str); cudaGetSymbolAddress(&gb, g_bar);
        if (fn && gp && gb) {
            const cuuint32_t rows = sms < NB_MAX ? sms : NB_MAX;
            cuuint64_t g2[2] = {(P1B + P2B) / 4, NB_MAX}, gs[1] = {P1B + P2B};
            cuuint32_t b2[2] = {CE, rows}, es[2] = {1, 1};
            tm_ok = ((EncFn)fn)(&tm2, CU_TENSOR_MAP_DATA_TYPE_UINT32, 2, gp, g2, gs, b2, es, CU_TENSOR_MAP_INTERLEAVE_NONE, CU_TENSOR_MAP_SWIZZLE_NONE,
                                CU_TENSOR_MAP_L2_PROMOTION_NONE, CU_TENSOR_MAP_FLOAT_OOB_FILL_NONE) == CUDA_SUCCESS;
        }
        cudaFuncSetAttribute(gcn_kernel<true>, cudaFuncAttributeMaxDynamicSharedMemorySize, SMEM_LAUNCH);
        cudaFuncSetAttribute(gcn_kernel<false>, cudaFuncAttributeMaxDynamicSharedMemorySize, SMEM_LAUNCH);
    }
    auto rows = [&](CUtensorMap* tm, const void* base, uint64_t n, uint32_t box) {
        cuuint64_t gd[2] = {64, n}, gs[1] = {128};
        cuuint32_t bx[2] = {64, box}, es[2] = {1, 1};
        return ((EncFn)fn)(tm, CU_TENSOR_MAP_DATA_TYPE_BFLOAT16, 2, (void*)base, gd, gs, bx, es, CU_TENSOR_MAP_INTERLEAVE_NONE, CU_TENSOR_MAP_SWIZZLE_128B,
                           CU_TENSOR_MAP_L2_PROMOTION_NONE, CU_TENSOR_MAP_FLOAT_OOB_FILL_NONE) == CUDA_SUCCESS;
    };
    const uintptr_t wp[4] = {(uintptr_t)wa, (uintptr_t)wb, (uintptr_t)wu, (uintptr_t)wv};
    uintptr_t w0 = wp[0], w1 = wp[0], wal = 0;
    for (int i = 1; i < 4; i++) { w0 = wp[i] < w0 ? wp[i] : w0; w1 = wp[i] > w1 ? wp[i] : w1; wal |= wp[i] - wp[0]; }
    int4 wrow = make_int4((int)((wp[0] - w0) >> 7), (int)((wp[1] - w0) >> 7), (int)((wp[2] - w0) >> 7), (int)((wp[3] - w0) >> 7));
    CUtensorMap tmw, tmc, tmx;
    const bool maps = tm_ok && N > 0 && !(wal & 127) && ((w1 - w0) >> 7) < (1u << 30) && rows(&tmw, (void*)w0, ((w1 - w0) >> 7) + 64, 64) && rows(&tmc, wc, 16, 16) && rows(&tmx, x, N, 128);
    int nb = sms < NB_MAX ? sms : NB_MAX;
    int npb = (N + nb - 1) / nb;
    int ch = (((E + nb - 1) / nb) + 3) & ~3;
    if (!maps || npb > NPB_MAX || ch > CH_MAX || (E & 3) || N > 65535 || npb < 2 || (((uintptr_t)src | (uintptr_t)dst | (uintptr_t)wa | (uintptr_t)wb | (uintptr_t)wc | (uintptr_t)wu | (uintptr_t)wv) & 15)) {
        int g = 1024, p = (N + g - 1) / g;
        slow_kernel<<<g, 256>>>(x, ea, src, dst, wa, wb, wc, wu, wv, out, N, E, p < 1 ? 1 : p);
        return;
    }
    uint32_t magic = (uint32_t)((1ull << 32) / (uint32_t)npb) + 1u;
    void* args[] = {&dst, &gb, &gp, &src, &E, &ch, &N, &npb, &magic, &x, &ea, &wa, &wb, &wc, &wu, &wv, &out, &wrow, &tm2, &tmw, &tmc, &tmx};
    const bool lo32 = ((uintptr_t)x >> 32) == (((uintptr_t)x + (size_t)N * 128 - 1) >> 32) && ((uintptr_t)ea >> 32) == (((uintptr_t)ea + (size_t)E * 32 - 1) >> 32);
    cudaLaunchCooperativeKernel(lo32 && !FORCE64 ? (const void*)gcn_kernel<true> : (const void*)gcn_kernel<false>, dim3(nb), dim3(THREADS), args, SMEM_LAUNCH, cudaStreamPerThread);
}
```

```cpp
#include <cuda_runtime.h>
#include <cuda.h>
#include <cuda_bf16.h>
#include <stdint.h>

namespace {

constexpr int N_MAX = 65536;
constexpr int NPMIN = 4;
constexpr int NPMAX = 11;
constexpr int THREADS = 512;
constexpr int EPT = 12;
constexpr int CH_MAX = THREADS * EPT;
constexpr int NB_MAX = 134;
constexpr int GAL = 128;
constexpr int CE = 64;
constexpr int P1B = (256 + NB_MAX * CE * 2 + GAL - 1) / GAL * GAL;
constexpr int P2B = (256 + NB_MAX * CE * 4 + GAL - 1) / GAL * GAL;
constexpr int NPB_MAX = 384;
constexpr int SLOT_CAP = 6784;
constexpr int TILE_CAP = 124;
constexpr int TILE_X = 8;
constexpr int NCLS = 64;
constexpr int XCAP = 128;
constexpr int NSTAGE = 2;
constexpr int TR = 2;
constexpr float LOG2E = 1.4426950408889634f;

__device__ __align__(128) uint4 g_str[NB_MAX * (P1B + P2B) / 16];
__device__ __align__(128) unsigned g_bar[32];
__device__ float g_slow[N_MAX * 128];

#define WS(k)
#define WGD()
#define FBT(k)
#define WSP(k)
#define WSL(k)
#define WSG(k)
#define WG0()
#define WG1()
#define SMEM_LAUNCH SMEM_BYTES
#define FORCE64 0
#define EDHI ((16ull << 32) | (3ull << 62))
template<int NP> struct TileMMA;
template<> struct TileMMA<4> {
  static __device__ __forceinline__ void issue(float* g, float* h, const uint32_t* w, uint64_t dx, uint64_t de, uint64_t dh, uint64_t dc) {
    asm volatile(
      "{\n.reg .b64 dx1, dx2, dx3;\n"
      "add.s64 dx1, %72, 2;\nadd.s64 dx2, %72, 4;\nadd.s64 dx3, %72, 6;\n"
      "wgmma.fence.sync.aligned;\n"
      "wgmma.mma_async.sync.aligned.m64n32k16.f32.bf16.bf16 {%0, %1, %2, %3, %4, %5, %6, %7, %8, %9, %10, %11, %12, %13, %14, %15}, {%68, %69, %70, %71}, %74, 0, 1, 1, 0;\n"
      "wgmma.mma_async.sync.aligned.m64n32k16.f32.bf16.bf16 {%0, %1, %2, %3, %4, %5, %6, %7, %8, %9, %10, %11, %12, %13, %14, %15}, {%48, %49, %50, %51}, %73, 1, 1, 1, 0;\n"
      "wgmma.mma_async.sync.aligned.m64n32k16.f32.bf16.bf16 {%0, %1, %2, %3, %4, %5, %6, %7, %8, %9, %10, %11, %12, %13, %14, %15}, {%32, %33, %34, %35}, %72, 1, 1, 1, 0;\n"
      "wgmma.mma_async.sync.aligned.m64n32k16.f32.bf16.bf16 {%0, %1, %2, %3, %4, %5, %6, %7, %8, %9, %10, %11, %12, %13, %14, %15}, {%36, %37, %38, %39}, dx1, 1, 1, 1, 0;\n"
      "wgmma.mma_async.sync.aligned.m64n32k16.f32.bf16.bf16 {%0, %1, %2, %3, %4, %5, %6, %7, %8, %9, %10, %11, %12, %13, %14, %15}, {%40, %41, %42, %43}, dx2, 1, 1, 1, 0;\n"
      "wgmma.mma_async.sync.aligned.m64n32k16.f32.bf16.bf16 {%0, %1, %2, %3, %4, %5, %6, %7, %8, %9, %10, %11, %12, %13, %14, %15}, {%44, %45, %46, %47}, dx3, 1, 1, 1, 0;\n"
      "wgmma.commit_group.sync.aligned;\n"
      "wgmma.mma_async.sync.aligned.m64n32k16.f32.bf16.bf16 {%16, %17, %18, %19, %20, %21, %22, %23, %24, %25, %26, %27, %28, %29, %30, %31}, {%52, %53, %54, %55}, %72, 0, 1, 1, 0;\n"
      "wgmma.mma_async.sync.aligned.m64n32k16.f32.bf16.bf16 {%16, %17, %18, %19, %20, %21, %22, %23, %24, %25, %26, %27, %28, %29, %30, %31}, {%56, %57, %58, %59}, dx1, 1, 1, 1, 0;\n"
      "wgmma.mma_async.sync.aligned.m64n32k16.f32.bf16.bf16 {%16, %17, %18, %19, %20, %21, %22, %23, %24, %25, %26, %27, %28, %29, %30, %31}, {%60, %61, %62, %63}, dx2, 1, 1, 1, 0;\n"
      "wgmma.mma_async.sync.aligned.m64n32k16.f32.bf16.bf16 {%16, %17, %18, %19, %20, %21, %22, %23, %24, %25, %26, %27, %28, %29, %30, %31}, {%64, %65, %66, %67}, dx3, 1, 1, 1, 0;\n"
      "wgmma.commit_group.sync.aligned;\n}\n"
      : "=f"(g[0]), "=f"(g[1]), "=f"(g[2]), "=f"(g[3]), "=f"(g[4]), "=f"(g[5]), "=f"(g[6]), "=f"(g[7]), "=f"(g[8]), "=f"(g[9]), "=f"(g[10]), "=f"(g[11]), "=f"(g[12]), "=f"(g[13]), "=f"(g[14]), "=f"(g[15]),
        "=f"(h[0]), "=f"(h[1]), "=f"(h[2]), "=f"(h[3]), "=f"(h[4]), "=f"(h[5]), "=f"(h[6]), "=f"(h[7]), "=f"(h[8]), "=f"(h[9]), "=f"(h[10]), "=f"(h[11]), "=f"(h[12]), "=f"(h[13]), "=f"(h[14]), "=f"(h[15])
      : "r"(w[0]), "r"(w[1]), "r"(w[2]), "r"(w[3]), "r"(w[4]), "r"(w[5]), "r"(w[6]), "r"(w[7]), "r"(w[8]), "r"(w[9]), "r"(w[10]), "r"(w[11]), "r"(w[12]), "r"(w[13]), "r"(w[14]), "r"(w[15]), "r"(w[16]), "r"(w[17]), "r"(w[18]), "r"(w[19]), "r"(w[20]), "r"(w[21]), "r"(w[22]), "r"(w[23]), "r"(w[24]), "r"(w[25]), "r"(w[26]), "r"(w[27]), "r"(w[28]), "r"(w[29]), "r"(w[30]), "r"(w[31]), "r"(w[32]), "r"(w[33]), "r"(w[34]), "r"(w[35]), "r"(w[36]), "r"(w[37]), "r"(w[38]), "r"(w[39]), "l"(dx), "l"(de), "l"(dh)
      : "memory");
  }
  static __device__ __forceinline__ void wait_g(float* g) {
    asm volatile("wgmma.wait_group.sync.aligned 1;\n"
      : "+f"(g[0]), "+f"(g[1]), "+f"(g[2]), "+f"(g[3]), "+f"(g[4]), "+f"(g[5]), "+f"(g[6]), "+f"(g[7]), "+f"(g[8]), "+f"(g[9]), "+f"(g[10]), "+f"(g[11]), "+f"(g[12]), "+f"(g[13]), "+f"(g[14]), "+f"(g[15])
      :: "memory");
  }
  static __device__ __forceinline__ void wait_h(float* h) {
    asm volatile("wgmma.wait_group.sync.aligned 0;\n"
      : "+f"(h[0]), "+f"(h[1]), "+f"(h[2]), "+f"(h[3]), "+f"(h[4]), "+f"(h[5]), "+f"(h[6]), "+f"(h[7]), "+f"(h[8]), "+f"(h[9]), "+f"(h[10]), "+f"(h[11]), "+f"(h[12]), "+f"(h[13]), "+f"(h[14]), "+f"(h[15])
      :: "memory");
  }
};
template<> struct TileMMA<5> {
  static __device__ __forceinline__ void issue(float* g, float* h, const uint32_t* w, uint64_t dx, uint64_t de, uint64_t dh, uint64_t dc) {
    asm volatile(
      "{\n.reg .b64 dx1, dx2, dx3;\n"
      "add.s64 dx1, %80, 2;\nadd.s64 dx2, %80, 4;\nadd.s64 dx3, %80, 6;\n"
      "wgmma.fence.sync.aligned;\n"
      "wgmma.mma_async.sync.aligned.m64n40k16.f32.bf16.bf16 {%0, %1, %2, %3, %4, %5, %6, %7, %8, %9, %10, %11, %12, %13, %14, %15, %16, %17, %18, %19}, {%76, %77, %78, %79}, %82, 0, 1, 1, 0;\n"
      "wgmma.mma_async.sync.aligned.m64n40k16.f32.bf16.bf16 {%0, %1, %2, %3, %4, %5, %6, %7, %8, %9, %10, %11, %12, %13, %14, %15, %16, %17, %18, %19}, {%56, %57, %58, %59}, %81, 1, 1, 1, 0;\n"
      "wgmma.mma_async.sync.aligned.m64n40k16.f32.bf16.bf16 {%0, %1, %2, %3, %4, %5, %6, %7, %8, %9, %10, %11, %12, %13, %14, %15, %16, %17, %18, %19}, {%40, %41, %42, %43}, %80, 1, 1, 1, 0;\n"
      "wgmma.mma_async.sync.aligned.m64n40k16.f32.bf16.bf16 {%0, %1, %2, %3, %4, %5, %6, %7, %8, %9, %10, %11, %12, %13, %14, %15, %16, %17, %18, %19}, {%44, %45, %46, %47}, dx1, 1, 1, 1, 0;\n"
      "wgmma.mma_async.sync.aligned.m64n40k16.f32.bf16.bf16 {%0, %1, %2, %3, %4, %5, %6, %7, %8, %9, %10, %11, %12, %13, %14, %15, %16, %17, %18, %19}, {%48, %49, %50, %51}, dx2, 1, 1, 1, 0;\n"
      "wgmma.mma_async.sync.aligned.m64n40k16.f32.bf16.bf16 {%0, %1, %2, %3, %4, %5, %6, %7, %8, %9, %10, %11, %12, %13, %14, %15, %16, %17, %18, %19}, {%52, %53, %54, %55}, dx3, 1, 1, 1, 0;\n"
      "wgmma.commit_group.sync.aligned;\n"
      "wgmma.mma_async.sync.aligned.m64n40k16.f32.bf16.bf16 {%20, %21, %22, %23, %24, %25, %26, %27, %28, %29, %30, %31, %32, %33, %34, %35, %36, %37, %38, %39}, {%60, %61, %62, %63}, %80, 0, 1, 1, 0;\n"
      "wgmma.mma_async.sync.aligned.m64n40k16.f32.bf16.bf16 {%20, %21, %22, %23, %24, %25, %26, %27, %28, %29, %30, %31, %32, %33, %34, %35, %36, %37, %38, %39}, {%64, %65, %66, %67}, dx1, 1, 1, 1, 0;\n"
      "wgmma.mma_async.sync.aligned.m64n40k16.f32.bf16.bf16 {%20, %21, %22, %23, %24, %25, %26, %27, %28, %29, %30, %31, %32, %33, %34, %35, %36, %37, %38, %39}, {%68, %69, %70, %71}, dx2, 1, 1, 1, 0;\n"
      "wgmma.mma_async.sync.aligned.m64n40k16.f32.bf16.bf16 {%20, %21, %22, %23, %24, %25, %26, %27, %28, %29, %30, %31, %32, %33, %34, %35, %36, %37, %38, %39}, {%72, %73, %74, %75}, dx3, 1, 1, 1, 0;\n"
      "wgmma.commit_group.sync.aligned;\n}\n"
      : "=f"(g[0]), "=f"(g[1]), "=f"(g[2]), "=f"(g[3]), "=f"(g[4]), "=f"(g[5]), "=f"(g[6]), "=f"(g[7]), "=f"(g[8]), "=f"(g[9]), "=f"(g[10]), "=f"(g[11]), "=f"(g[12]), "=f"(g[13]), "=f"(g[14]), "=f"(g[15]), "=f"(g[16]), "=f"(g[17]), "=f"(g[18]), "=f"(g[19]),
        "=f"(h[0]), "=f"(h[1]), "=f"(h[2]), "=f"(h[3]), "=f"(h[4]), "=f"(h[5]), "=f"(h[6]), "=f"(h[7]), "=f"(h[8]), "=f"(h[9]), "=f"(h[10]), "=f"(h[11]), "=f"(h[12]), "=f"(h[13]), "=f"(h[14]), "=f"(h[15]), "=f"(h[16]), "=f"(h[17]), "=f"(h[18]), "=f"(h[19])
      : "r"(w[0]), "r"(w[1]), "r"(w[2]), "r"(w[3]), "r"(w[4]), "r"(w[5]), "r"(w[6]), "r"(w[7]), "r"(w[8]), "r"(w[9]), "r"(w[10]), "r"(w[11]), "r"(w[12]), "r"(w[13]), "r"(w[14]), "r"(w[15]), "r"(w[16]), "r"(w[17]), "r"(w[18]), "r"(w[19]), "r"(w[20]), "r"(w[21]), "r"(w[22]), "r"(w[23]), "r"(w[24]), "r"(w[25]), "r"(w[26]), "r"(w[27]), "r"(w[28]), "r"(w[29]), "r"(w[30]), "r"(w[31]), "r"(w[32]), "r"(w[33]), "r"(w[34]), "r"(w[35]), "r"(w[36]), "r"(w[37]), "r"(w[38]), "r"(w[39]), "l"(dx), "l"(de), "l"(dh)
      : "memory");
  }
  static __device__ __forceinline__ void wait_g(float* g) {
    asm volatile("wgmma.wait_group.sync.aligned 1;\n"
      : "+f"(g[0]), "+f"(g[1]), "+f"(g[2]), "+f"(g[3]), "+f"(g[4]), "+f"(g[5]), "+f"(g[6]), "+f"(g[7]), "+f"(g[8]), "+f"(g[9]), "+f"(g[10]), "+f"(g[11]), "+f"(g[12]), "+f"(g[13]), "+f"(g[14]), "+f"(g[15]), "+f"(g[16]), "+f"(g[17]), "+f"(g[18]), "+f"(g[19])
      :: "memory");
  }
  static __device__ __forceinline__ void wait_h(float* h) {
    asm volatile("wgmma.wait_group.sync.aligned 0;\n"
      : "+f"(h[0]), "+f"(h[1]), "+f"(h[2]), "+f"(h[3]), "+f"(h[4]), "+f"(h[5]), "+f"(h[6]), "+f"(h[7]), "+f"(h[8]), "+f"(h[9]), "+f"(h[10]), "+f"(h[11]), "+f"(h[12]), "+f"(h[13]), "+f"(h[14]), "+f"(h[15]), "+f"(h[16]), "+f"(h[17]), "+f"(h[18]), "+f"(h[19])
      :: "memory");
  }
};
template<> struct TileMMA<6> {
  static __device__ __forceinline__ void issue(float* g, float* h, const uint32_t* w, uint64_t dx, uint64_t de, uint64_t dh, uint64_t dc) {
    asm volatile(
      "{\n.reg .b64 dx1, dx2, dx3;\n"
      "add.s64 dx1, %88, 2;\nadd.s64 dx2, %88, 4;\nadd.s64 dx3, %88, 6;\n"
      "wgmma.fence.sync.aligned;\n"
      "wgmma.mma_async.sync.aligned.m64n48k16.f32.bf16.bf16 {%0, %1, %2, %3, %4, %5, %6, %7, %8, %9, %10, %11, %12, %13, %14, %15, %16, %17, %18, %19, %20, %21, %22, %23}, {%84, %85, %86, %87}, %90, 0, 1, 1, 0;\n"
      "wgmma.mma_async.sync.aligned.m64n48k16.f32.bf16.bf16 {%0, %1, %2, %3, %4, %5, %6, %7, %8, %9, %10, %11, %12, %13, %14, %15, %16, %17, %18, %19, %20, %21, %22, %23}, {%64, %65, %66, %67}, %89, 1, 1, 1, 0;\n"
      "wgmma.mma_async.sync.aligned.m64n48k16.f32.bf16.bf16 {%0, %1, %2, %3, %4, %5, %6, %7, %8, %9, %10, %11, %12, %13, %14, %15, %16, %17, %18, %19, %20, %21, %22, %23}, {%48, %49, %50, %51}, %88, 1, 1, 1, 0;\n"
      "wgmma.mma_async.sync.aligned.m64n48k16.f32.bf16.bf16 {%0, %1, %2, %3, %4, %5, %6, %7, %8, %9, %10, %11, %12, %13, %14, %15, %16, %17, %18, %19, %20, %21, %22, %23}, {%52, %53, %54, %55}, dx1, 1, 1, 1, 0;\n"
      "wgmma.mma_async.sync.aligned.m64n48k16.f32.bf16.bf16 {%0, %1, %2, %3, %4, %5, %6, %7, %8, %9, %10, %11, %12, %13, %14, %15, %16, %17, %18, %19, %20, %21, %22, %23}, {%56, %57, %58, %59}, dx2, 1, 1, 1, 0;\n"
      "wgmma.mma_async.sync.aligned.m64n48k16.f32.bf16.bf16 {%0, %1, %2, %3, %4, %5, %6, %7, %8, %9, %10, %11, %12, %13, %14, %15, %16, %17, %18, %19, %20, %21, %22, %23}, {%60, %61, %62, %63}, dx3, 1, 1, 1, 0;\n"
      "wgmma.commit_group.sync.aligned;\n"
      "wgmma.mma_async.sync.aligned.m64n48k16.f32.bf16.bf16 {%24, %25, %26, %27, %28, %29, %30, %31, %32, %33, %34, %35, %36, %37, %38, %39, %40, %41, %42, %43, %44, %45, %46, %47}, {%68, %69, %70, %71}, %88, 0, 1, 1, 0;\n"
      "wgmma.mma_async.sync.aligned.m64n48k16.f32.bf16.bf16 {%24, %25, %26, %27, %28, %29, %30, %31, %32, %33, %34, %35, %36, %37, %38, %39, %40, %41, %42, %43, %44, %45, %46, %47}, {%72, %73, %74, %75}, dx1, 1, 1, 1, 0;\n"
      "wgmma.mma_async.sync.aligned.m64n48k16.f32.bf16.bf16 {%24, %25, %26, %27, %28, %29, %30, %31, %32, %33, %34, %35, %36, %37, %38, %39, %40, %41, %42, %43, %44, %45, %46, %47}, {%76, %77, %78, %79}, dx2, 1, 1, 1, 0;\n"
      "wgmma.mma_async.sync.aligned.m64n48k16.f32.bf16.bf16 {%24, %25, %26, %27, %28, %29, %30, %31, %32, %33, %34, %35, %36, %37, %38, %39, %40, %41, %42, %43, %44, %45, %46, %47}, {%80, %81, %82, %83}, dx3, 1, 1, 1, 0;\n"
      "wgmma.commit_group.sync.aligned;\n}\n"
      : "=f"(g[0]), "=f"(g[1]), "=f"(g[2]), "=f"(g[3]), "=f"(g[4]), "=f"(g[5]), "=f"(g[6]), "=f"(g[7]), "=f"(g[8]), "=f"(g[9]), "=f"(g[10]), "=f"(g[11]), "=f"(g[12]), "=f"(g[13]), "=f"(g[14]), "=f"(g[15]), "=f"(g[16]), "=f"(g[17]), "=f"(g[18]), "=f"(g[19]), "=f"(g[20]), "=f"(g[21]), "=f"(g[22]), "=f"(g[23]),
        "=f"(h[0]), "=f"(h[1]), "=f"(h[2]), "=f"(h[3]), "=f"(h[4]), "=f"(h[5]), "=f"(h[6]), "=f"(h[7]), "=f"(h[8]), "=f"(h[9]), "=f"(h[10]), "=f"(h[11]), "=f"(h[12]), "=f"(h[13]), "=f"(h[14]), "=f"(h[15]), "=f"(h[16]), "=f"(h[17]), "=f"(h[18]), "=f"(h[19]), "=f"(h[20]), "=f"(h[21]), "=f"(h[22]), "=f"(h[23])
      : "r"(w[0]), "r"(w[1]), "r"(w[2]), "r"(w[3]), "r"(w[4]), "r"(w[5]), "r"(w[6]), "r"(w[7]), "r"(w[8]), "r"(w[9]), "r"(w[10]), "r"(w[11]), "r"(w[12]), "r"(w[13]), "r"(w[14]), "r"(w[15]), "r"(w[16]), "r"(w[17]), "r"(w[18]), "r"(w[19]), "r"(w[20]), "r"(w[21]), "r"(w[22]), "r"(w[23]), "r"(w[24]), "r"(w[25]), "r"(w[26]), "r"(w[27]), "r"(w[28]), "r"(w[29]), "r"(w[30]), "r"(w[31]), "r"(w[32]), "r"(w[33]), "r"(w[34]), "r"(w[35]), "r"(w[36]), "r"(w[37]), "r"(w[38]), "r"(w[39]), "l"(dx), "l"(de), "l"(dh)
      : "memory");
  }
  static __device__ __forceinline__ void wait_g(float* g) {
    asm volatile("wgmma.wait_group.sync.aligned 1;\n"
      : "+f"(g[0]), "+f"(g[1]), "+f"(g[2]), "+f"(g[3]), "+f"(g[4]), "+f"(g[5]), "+f"(g[6]), "+f"(g[7]), "+f"(g[8]), "+f"(g[9]), "+f"(g[10]), "+f"(g[11]), "+f"(g[12]), "+f"(g[13]), "+f"(g[14]), "+f"(g[15]), "+f"(g[16]), "+f"(g[17]), "+f"(g[18]), "+f"(g[19]), "+f"(g[20]), "+f"(g[21]), "+f"(g[22]), "+f"(g[23])
      :: "memory");
  }
  static __device__ __forceinline__ void wait_h(float* h) {
    asm volatile("wgmma.wait_group.sync.aligned 0;\n"
      : "+f"(h[0]), "+f"(h[1]), "+f"(h[2]), "+f"(h[3]), "+f"(h[4]), "+f"(h[5]), "+f"(h[6]), "+f"(h[7]), "+f"(h[8]), "+f"(h[9]), "+f"(h[10]), "+f"(h[11]), "+f"(h[12]), "+f"(h[13]), "+f"(h[14]), "+f"(h[15]), "+f"(h[16]), "+f"(h[17]), "+f"(h[18]), "+f"(h[19]), "+f"(h[20]), "+f"(h[21]), "+f"(h[22]), "+f"(h[23])
      :: "memory");
  }
};
template<> struct TileMMA<7> {
  static __device__ __forceinline__ void issue(float* g, float* h, const uint32_t* w, uint64_t dx, uint64_t de, uint64_t dh, uint64_t dc) {
    asm volatile(
      "{\n.reg .b64 dx1, dx2, dx3;\n"
      "add.s64 dx1, %96, 2;\nadd.s64 dx2, %96, 4;\nadd.s64 dx3, %96, 6;\n"
      "wgmma.fence.sync.aligned;\n"
      "wgmma.mma_async.sync.aligned.m64n56k16.f32.bf16.bf16 {%0, %1, %2, %3, %4, %5, %6, %7, %8, %9, %10, %11, %12, %13, %14, %15, %16, %17, %18, %19, %20, %21, %22, %23, %24, %25, %26, %27}, {%92, %93, %94, %95}, %98, 0, 1, 1, 0;\n"
      "wgmma.mma_async.sync.aligned.m64n56k16.f32.bf16.bf16 {%0, %1, %2, %3, %4, %5, %6, %7, %8, %9, %10, %11, %12, %13, %14, %15, %16, %17, %18, %19, %20, %21, %22, %23, %24, %25, %26, %27}, {%72, %73, %74, %75}, %97, 1, 1, 1, 0;\n"
      "wgmma.mma_async.sync.aligned.m64n56k16.f32.bf16.bf16 {%0, %1, %2, %3, %4, %5, %6, %7, %8, %9, %10, %11, %12, %13, %14, %15, %16, %17, %18, %19, %20, %21, %22, %23, %24, %25, %26, %27}, {%56, %57, %58, %59}, %96, 1, 1, 1, 0;\n"
      "wgmma.mma_async.sync.aligned.m64n56k16.f32.bf16.bf16 {%0, %1, %2, %3, %4, %5, %6, %7, %8, %9, %10, %11, %12, %13, %14, %15, %16, %17, %18, %19, %20, %21, %22, %23, %24, %25, %26, %27}, {%60, %61, %62, %63}, dx1, 1, 1, 1, 0;\n"
      "wgmma.mma_async.sync.aligned.m64n56k16.f32.bf16.bf16 {%0, %1, %2, %3, %4, %5, %6, %7, %8, %9, %10, %11, %12, %13, %14, %15, %16, %17, %18, %19, %20, %21, %22, %23, %24, %25, %26, %27}, {%64, %65, %66, %67}, dx2, 1, 1, 1, 0;\n"
      "wgmma.mma_async.sync.aligned.m64n56k16.f32.bf16.bf16 {%0, %1, %2, %3, %4, %5, %6, %7, %8, %9, %10, %11, %12, %13, %14, %15, %16, %17, %18, %19, %20, %21, %22, %23, %24, %25, %26, %27}, {%68, %69, %70, %71}, dx3, 1, 1, 1, 0;\n"
      "wgmma.commit_group.sync.aligned;\n"
      "wgmma.mma_async.sync.aligned.m64n56k16.f32.bf16.bf16 {%28, %29, %30, %31, %32, %33, %34, %35, %36, %37, %38, %39, %40, %41, %42, %43, %44, %45, %46, %47, %48, %49, %50, %51, %52, %53, %54, %55}, {%76, %77, %78, %79}, %96, 0, 1, 1, 0;\n"
      "wgmma.mma_async.sync.aligned.m64n56k16.f32.bf16.bf16 {%28, %29, %30, %31, %32, %33, %34, %35, %36, %37, %38, %39, %40, %41, %42, %43, %44, %45, %46, %47, %48, %49, %50, %51, %52, %53, %54, %55}, {%80, %81, %82, %83}, dx1, 1, 1, 1, 0;\n"
      "wgmma.mma_async.sync.aligned.m64n56k16.f32.bf16.bf16 {%28, %29, %30, %31, %32, %33, %34, %35, %36, %37, %38, %39, %40, %41, %42, %43, %44, %45, %46, %47, %48, %49, %50, %51, %52, %53, %54, %55}, {%84, %85, %86, %87}, dx2, 1, 1, 1, 0;\n"
      "wgmma.mma_async.sync.aligned.m64n56k16.f32.bf16.bf16 {%28, %29, %30, %31, %32, %33, %34, %35, %36, %37, %38, %39, %40, %41, %42, %43, %44, %45, %46, %47, %48, %49, %50, %51, %52, %53, %54, %55}, {%88, %89, %90, %91}, dx3, 1, 1, 1, 0;\n"
      "wgmma.commit_group.sync.aligned;\n}\n"
      : "=f"(g[0]), "=f"(g[1]), "=f"(g[2]), "=f"(g[3]), "=f"(g[4]), "=f"(g[5]), "=f"(g[6]), "=f"(g[7]), "=f"(g[8]), "=f"(g[9]), "=f"(g[10]), "=f"(g[11]), "=f"(g[12]), "=f"(g[13]), "=f"(g[14]), "=f"(g[15]), "=f"(g[16]), "=f"(g[17]), "=f"(g[18]), "=f"(g[19]), "=f"(g[20]), "=f"(g[21]), "=f"(g[22]), "=f"(g[23]), "=f"(g[24]), "=f"(g[25]), "=f"(g[26]), "=f"(g[27]),
        "=f"(h[0]), "=f"(h[1]), "=f"(h[2]), "=f"(h[3]), "=f"(h[4]), "=f"(h[5]), "=f"(h[6]), "=f"(h[7]), "=f"(h[8]), "=f"(h[9]), "=f"(h[10]), "=f"(h[11]), "=f"(h[12]), "=f"(h[13]), "=f"(h[14]), "=f"(h[15]), "=f"(h[16]), "=f"(h[17]), "=f"(h[18]), "=f"(h[19]), "=f"(h[20]), "=f"(h[21]), "=f"(h[22]), "=f"(h[23]), "=f"(h[24]), "=f"(h[25]), "=f"(h[26]), "=f"(h[27])
      : "r"(w[0]), "r"(w[1]), "r"(w[2]), "r"(w[3]), "r"(w[4]), "r"(w[5]), "r"(w[6]), "r"(w[7]), "r"(w[8]), "r"(w[9]), "r"(w[10]), "r"(w[11]), "r"(w[12]), "r"(w[13]), "r"(w[14]), "r"(w[15]), "r"(w[16]), "r"(w[17]), "r"(w[18]), "r"(w[19]), "r"(w[20]), "r"(w[21]), "r"(w[22]), "r"(w[23]), "r"(w[24]), "r"(w[25]), "r"(w[26]), "r"(w[27]), "r"(w[28]), "r"(w[29]), "r"(w[30]), "r"(w[31]), "r"(w[32]), "r"(w[33]), "r"(w[34]), "r"(w[35]), "r"(w[36]), "r"(w[37]), "r"(w[38]), "r"(w[39]), "l"(dx), "l"(de), "l"(dh)
      : "memory");
  }
  static __device__ __forceinline__ void wait_g(float* g) {
    asm volatile("wgmma.wait_group.sync.aligned 1;\n"
      : "+f"(g[0]), "+f"(g[1]), "+f"(g[2]), "+f"(g[3]), "+f"(g[4]), "+f"(g[5]), "+f"(g[6]), "+f"(g[7]), "+f"(g[8]), "+f"(g[9]), "+f"(g[10]), "+f"(g[11]), "+f"(g[12]), "+f"(g[13]), "+f"(g[14]), "+f"(g[15]), "+f"(g[16]), "+f"(g[17]), "+f"(g[18]), "+f"(g[19]), "+f"(g[20]), "+f"(g[21]), "+f"(g[22]), "+f"(g[23]), "+f"(g[24]), "+f"(g[25]), "+f"(g[26]), "+f"(g[27])
      :: "memory");
  }
  static __device__ __forceinline__ void wait_h(float* h) {
    asm volatile("wgmma.wait_group.sync.aligned 0;\n"
      : "+f"(h[0]), "+f"(h[1]), "+f"(h[2]), "+f"(h[3]), "+f"(h[4]), "+f"(h[5]), "+f"(h[6]), "+f"(h[7]), "+f"(h[8]), "+f"(h[9]), "+f"(h[10]), "+f"(h[11]), "+f"(h[12]), "+f"(h[13]), "+f"(h[14]), "+f"(h[15]), "+f"(h[16]), "+f"(h[17]), "+f"(h[18]), "+f"(h[19]), "+f"(h[20]), "+f"(h[21]), "+f"(h[22]), "+f"(h[23]), "+f"(h[24]), "+f"(h[25]), "+f"(h[26]), "+f"(h[27])
      :: "memory");
  }
};
template<> struct TileMMA<8> {
  static __device__ __forceinline__ void issue(float* g, float* h, const uint32_t* w, uint64_t dx, uint64_t de, uint64_t dh, uint64_t dc) {
    asm volatile(
      "{\n.reg .b64 dx1, dx2, dx3;\n"
      "add.s64 dx1, %104, 2;\nadd.s64 dx2, %104, 4;\nadd.s64 dx3, %104, 6;\n"
      "wgmma.fence.sync.aligned;\n"
      "wgmma.mma_async.sync.aligned.m64n64k16.f32.bf16.bf16 {%0, %1, %2, %3, %4, %5, %6, %7, %8, %9, %10, %11, %12, %13, %14, %15, %16, %17, %18, %19, %20, %21, %22, %23, %24, %25, %26, %27, %28, %29, %30, %31}, {%100, %101, %102, %103}, %106, 0, 1, 1, 0;\n"
      "wgmma.mma_async.sync.aligned.m64n64k16.f32.bf16.bf16 {%0, %1, %2, %3, %4, %5, %6, %7, %8, %9, %10, %11, %12, %13, %14, %15, %16, %17, %18, %19, %20, %21, %22, %23, %24, %25, %26, %27, %28, %29, %30, %31}, {%80, %81, %82, %83}, %105, 1, 1, 1, 0;\n"
      "wgmma.mma_async.sync.aligned.m64n64k16.f32.bf16.bf16 {%0, %1, %2, %3, %4, %5, %6, %7, %8, %9, %10, %11, %12, %13, %14, %15, %16, %17, %18, %19, %20, %21, %22, %23, %24, %25, %26, %27, %28, %29, %30, %31}, {%64, %65, %66, %67}, %104, 1, 1, 1, 0;\n"
      "wgmma.mma_async.sync.aligned.m64n64k16.f32.bf16.bf16 {%0, %1, %2, %3, %4, %5, %6, %7, %8, %9, %10, %11, %12, %13, %14, %15, %16, %17, %18, %19, %20, %21, %22, %23, %24, %25, %26, %27, %28, %29, %30, %31}, {%68, %69, %70, %71}, dx1, 1, 1, 1, 0;\n"
      "wgmma.mma_async.sync.aligned.m64n64k16.f32.bf16.bf16 {%0, %1, %2, %3, %4, %5, %6, %7, %8, %9, %10, %11, %12, %13, %14, %15, %16, %17, %18, %19, %20, %21, %22, %23, %24, %25, %26, %27, %28, %29, %30, %31}, {%72, %73, %74, %75}, dx2, 1, 1, 1, 0;\n"
      "wgmma.mma_async.sync.aligned.m64n64k16.f32.bf16.bf16 {%0, %1, %2, %3, %4, %5, %6, %7, %8, %9, %10, %11, %12, %13, %14, %15, %16, %17, %18, %19, %20, %21, %22, %23, %24, %25, %26, %27, %28, %29, %30, %31}, {%76, %77, %78, %79}, dx3, 1, 1, 1, 0;\n"
      "wgmma.commit_group.sync.aligned;\n"
      "wgmma.mma_async.sync.aligned.m64n64k16.f32.bf16.bf16 {%32, %33, %34, %35, %36, %37, %38, %39, %40, %41, %42, %43, %44, %45, %46, %47, %48, %49, %50, %51, %52, %53, %54, %55, %56, %57, %58, %59, %60, %61, %62, %63}, {%84, %85, %86, %87}, %104, 0, 1, 1, 0;\n"
      "wgmma.mma_async.sync.aligned.m64n64k16.f32.bf16.bf16 {%32, %33, %34, %35, %36, %37, %38, %39, %40, %41, %42, %43, %44, %45, %46, %47, %48, %49, %50, %51, %52, %53, %54, %55, %56, %57, %58, %59, %60, %61, %62, %63}, {%88, %89, %90, %91}, dx1, 1, 1, 1, 0;\n"
      "wgmma.mma_async.sync.aligned.m64n64k16.f32.bf16.bf16 {%32, %33, %34, %35, %36, %37, %38, %39, %40, %41, %42, %43, %44, %45, %46, %47, %48, %49, %50, %51, %52, %53, %54, %55, %56, %57, %58, %59, %60, %61, %62, %63}, {%92, %93, %94, %95}, dx2, 1, 1, 1, 0;\n"
      "wgmma.mma_async.sync.aligned.m64n64k16.f32.bf16.bf16 {%32, %33, %34, %35, %36, %37, %38, %39, %40, %41, %42, %43, %44, %45, %46, %47, %48, %49, %50, %51, %52, %53, %54, %55, %56, %57, %58, %59, %60, %61, %62, %63}, {%96, %97, %98, %99}, dx3, 1, 1, 1, 0;\n"
      "wgmma.commit_group.sync.aligned;\n}\n"
      : "=f"(g[0]), "=f"(g[1]), "=f"(g[2]), "=f"(g[3]), "=f"(g[4]), "=f"(g[5]), "=f"(g[6]), "=f"(g[7]), "=f"(g[8]), "=f"(g[9]), "=f"(g[10]), "=f"(g[11]), "=f"(g[12]), "=f"(g[13]), "=f"(g[14]), "=f"(g[15]), "=f"(g[16]), "=f"(g[17]), "=f"(g[18]), "=f"(g[19]), "=f"(g[20]), "=f"(g[21]), "=f"(g[22]), "=f"(g[23]), "=f"(g[24]), "=f"(g[25]), "=f"(g[26]), "=f"(g[27]), "=f"(g[28]), "=f"(g[29]), "=f"(g[30]), "=f"(g[31]),
        "=f"(h[0]), "=f"(h[1]), "=f"(h[2]), "=f"(h[3]), "=f"(h[4]), "=f"(h[5]), "=f"(h[6]), "=f"(h[7]), "=f"(h[8]), "=f"(h[9]), "=f"(h[10]), "=f"(h[11]), "=f"(h[12]), "=f"(h[13]), "=f"(h[14]), "=f"(h[15]), "=f"(h[16]), "=f"(h[17]), "=f"(h[18]), "=f"(h[19]), "=f"(h[20]), "=f"(h[21]), "=f"(h[22]), "=f"(h[23]), "=f"(h[24]), "=f"(h[25]), "=f"(h[26]), "=f"(h[27]), "=f"(h[28]), "=f"(h[29]), "=f"(h[30]), "=f"(h[31])
      : "r"(w[0]), "r"(w[1]), "r"(w[2]), "r"(w[3]), "r"(w[4]), "r"(w[5]), "r"(w[6]), "r"(w[7]), "r"(w[8]), "r"(w[9]), "r"(w[10]), "r"(w[11]), "r"(w[12]), "r"(w[13]), "r"(w[14]), "r"(w[15]), "r"(w[16]), "r"(w[17]), "r"(w[18]), "r"(w[19]), "r"(w[20]), "r"(w[21]), "r"(w[22]), "r"(w[23]), "r"(w[24]), "r"(w[25]), "r"(w[26]), "r"(w[27]), "r"(w[28]), "r"(w[29]), "r"(w[30]), "r"(w[31]), "r"(w[32]), "r"(w[33]), "r"(w[34]), "r"(w[35]), "r"(w[36]), "r"(w[37]), "r"(w[38]), "r"(w[39]), "l"(dx), "l"(de), "l"(dh)
      : "memory");
  }
  static __device__ __forceinline__ void wait_g(float* g) {
    asm volatile("wgmma.wait_group.sync.aligned 1;\n"
      : "+f"(g[0]), "+f"(g[1]), "+f"(g[2]), "+f"(g[3]), "+f"(g[4]), "+f"(g[5]), "+f"(g[6]), "+f"(g[7]), "+f"(g[8]), "+f"(g[9]), "+f"(g[10]), "+f"(g[11]), "+f"(g[12]), "+f"(g[13]), "+f"(g[14]), "+f"(g[15]), "+f"(g[16]), "+f"(g[17]), "+f"(g[18]), "+f"(g[19]), "+f"(g[20]), "+f"(g[21]), "+f"(g[22]), "+f"(g[23]), "+f"(g[24]), "+f"(g[25]), "+f"(g[26]), "+f"(g[27]), "+f"(g[28]), "+f"(g[29]), "+f"(g[30]), "+f"(g[31])
      :: "memory");
  }
  static __device__ __forceinline__ void wait_h(float* h) {
    asm volatile("wgmma.wait_group.sync.aligned 0;\n"
      : "+f"(h[0]), "+f"(h[1]), "+f"(h[2]), "+f"(h[3]), "+f"(h[4]), "+f"(h[5]), "+f"(h[6]), "+f"(h[7]), "+f"(h[8]), "+f"(h[9]), "+f"(h[10]), "+f"(h[11]), "+f"(h[12]), "+f"(h[13]), "+f"(h[14]), "+f"(h[15]), "+f"(h[16]), "+f"(h[17]), "+f"(h[18]), "+f"(h[19]), "+f"(h[20]), "+f"(h[21]), "+f"(h[22]), "+f"(h[23]), "+f"(h[24]), "+f"(h[25]), "+f"(h[26]), "+f"(h[27]), "+f"(h[28]), "+f"(h[29]), "+f"(h[30]), "+f"(h[31])
      :: "memory");
  }
};
template<> struct TileMMA<9> {
  static __device__ __forceinline__ void issue(float* g, float* h, const uint32_t* w, uint64_t dx, uint64_t de, uint64_t dh, uint64_t dc) {
    asm volatile(
      "{\n.reg .b64 dx1, dx2, dx3;\n"
      "add.s64 dx1, %112, 2;\nadd.s64 dx2, %112, 4;\nadd.s64 dx3, %112, 6;\n"
      "wgmma.fence.sync.aligned;\n"
      "wgmma.mma_async.sync.aligned.m64n72k16.f32.bf16.bf16 {%0, %1, %2, %3, %4, %5, %6, %7, %8, %9, %10, %11, %12, %13, %14, %15, %16, %17, %18, %19, %20, %21, %22, %23, %24, %25, %26, %27, %28, %29, %30, %31, %32, %33, %34, %35}, {%108, %109, %110, %111}, %114, 0, 1, 1, 0;\n"
      "wgmma.mma_async.sync.aligned.m64n72k16.f32.bf16.bf16 {%0, %1, %2, %3, %4, %5, %6, %7, %8, %9, %10, %11, %12, %13, %14, %15, %16, %17, %18, %19, %20, %21, %22, %23, %24, %25, %26, %27, %28, %29, %30, %31, %32, %33, %34, %35}, {%88, %89, %90, %91}, %113, 1, 1, 1, 0;\n"
      "wgmma.mma_async.sync.aligned.m64n72k16.f32.bf16.bf16 {%0, %1, %2, %3, %4, %5, %6, %7, %8, %9, %10, %11, %12, %13, %14, %15, %16, %17, %18, %19, %20, %21, %22, %23, %24, %25, %26, %27, %28, %29, %30, %31, %32, %33, %34, %35}, {%72, %73, %74, %75}, %112, 1, 1, 1, 0;\n"
      "wgmma.mma_async.sync.aligned.m64n72k16.f32.bf16.bf16 {%0, %1, %2, %3, %4, %5, %6, %7, %8, %9, %10, %11, %12, %13, %14, %15, %16, %17, %18, %19, %20, %21, %22, %23, %24, %25, %26, %27, %28, %29, %30, %31, %32, %33, %34, %35}, {%76, %77, %78, %79}, dx1, 1, 1, 1, 0;\n"
      "wgmma.mma_async.sync.aligned.m64n72k16.f32.bf16.bf16 {%0, %1, %2, %3, %4, %5, %6, %7, %8, %9, %10, %11, %12, %13, %14, %15, %16, %17, %18, %19, %20, %21, %22, %23, %24, %25, %26, %27, %28, %29, %30, %31, %32, %33, %34, %35}, {%80, %81, %82, %83}, dx2, 1, 1, 1, 0;\n"
      "wgmma.mma_async.sync.aligned.m64n72k16.f32.bf16.bf16 {%0, %1, %2, %3, %4, %5, %6, %7, %8, %9, %10, %11, %12, %13, %14, %15, %16, %17, %18, %19, %20, %21, %22, %23, %24, %25, %26, %27, %28, %29, %30, %31, %32, %33, %34, %35}, {%84, %85, %86, %87}, dx3, 1, 1, 1, 0;\n"
      "wgmma.commit_group.sync.aligned;\n"
      "wgmma.mma_async.sync.aligned.m64n72k16.f32.bf16.bf16 {%36, %37, %38, %39, %40, %41, %42, %43, %44, %45, %46, %47, %48, %49, %50, %51, %52, %53, %54, %55, %56, %57, %58, %59, %60, %61, %62, %63, %64, %65, %66, %67, %68, %69, %70, %71}, {%92, %93, %94, %95}, %112, 0, 1, 1, 0;\n"
      "wgmma.mma_async.sync.aligned.m64n72k16.f32.bf16.bf16 {%36, %37, %38, %39, %40, %41, %42, %43, %44, %45, %46, %47, %48, %49, %50, %51, %52, %53, %54, %55, %56, %57, %58, %59, %60, %61, %62, %63, %64, %65, %66, %67, %68, %69, %70, %71}, {%96, %97, %98, %99}, dx1, 1, 1, 1, 0;\n"
      "wgmma.mma_async.sync.aligned.m64n72k16.f32.bf16.bf16 {%36, %37, %38, %39, %40, %41, %42, %43, %44, %45, %46, %47, %48, %49, %50, %51, %52, %53, %54, %55, %56, %57, %58, %59, %60, %61, %62, %63, %64, %65, %66, %67, %68, %69, %70, %71}, {%100, %101, %102, %103}, dx2, 1, 1, 1, 0;\n"
      "wgmma.mma_async.sync.aligned.m64n72k16.f32.bf16.bf16 {%36, %37, %38, %39, %40, %41, %42, %43, %44, %45, %46, %47, %48, %49, %50, %51, %52, %53, %54, %55, %56, %57, %58, %59, %60, %61, %62, %63, %64, %65, %66, %67, %68, %69, %70, %71}, {%104, %105, %106, %107}, dx3, 1, 1, 1, 0;\n"
      "wgmma.commit_group.sync.aligned;\n}\n"
      : "=f"(g[0]), "=f"(g[1]), "=f"(g[2]), "=f"(g[3]), "=f"(g[4]), "=f"(g[5]), "=f"(g[6]), "=f"(g[7]), "=f"(g[8]), "=f"(g[9]), "=f"(g[10]), "=f"(g[11]), "=f"(g[12]), "=f"(g[13]), "=f"(g[14]), "=f"(g[15]), "=f"(g[16]), "=f"(g[17]), "=f"(g[18]), "=f"(g[19]), "=f"(g[20]), "=f"(g[21]), "=f"(g[22]), "=f"(g[23]), "=f"(g[24]), "=f"(g[25]), "=f"(g[26]), "=f"(g[27]), "=f"(g[28]), "=f"(g[29]), "=f"(g[30]), "=f"(g[31]), "=f"(g[32]), "=f"(g[33]), "=f"(g[34]), "=f"(g[35]),
        "=f"(h[0]), "=f"(h[1]), "=f"(h[2]), "=f"(h[3]), "=f"(h[4]), "=f"(h[5]), "=f"(h[6]), "=f"(h[7]), "=f"(h[8]), "=f"(h[9]), "=f"(h[10]), "=f"(h[11]), "=f"(h[12]), "=f"(h[13]), "=f"(h[14]), "=f"(h[15]), "=f"(h[16]), "=f"(h[17]), "=f"(h[18]), "=f"(h[19]), "=f"(h[20]), "=f"(h[21]), "=f"(h[22]), "=f"(h[23]), "=f"(h[24]), "=f"(h[25]), "=f"(h[26]), "=f"(h[27]), "=f"(h[28]), "=f"(h[29]), "=f"(h[30]), "=f"(h[31]), "=f"(h[32]), "=f"(h[33]), "=f"(h[34]), "=f"(h[35])
      : "r"(w[0]), "r"(w[1]), "r"(w[2]), "r"(w[3]), "r"(w[4]), "r"(w[5]), "r"(w[6]), "r"(w[7]), "r"(w[8]), "r"(w[9]), "r"(w[10]), "r"(w[11]), "r"(w[12]), "r"(w[13]), "r"(w[14]), "r"(w[15]), "r"(w[16]), "r"(w[17]), "r"(w[18]), "r"(w[19]), "r"(w[20]), "r"(w[21]), "r"(w[22]), "r"(w[23]), "r"(w[24]), "r"(w[25]), "r"(w[26]), "r"(w[27]), "r"(w[28]), "r"(w[29]), "r"(w[30]), "r"(w[31]), "r"(w[32]), "r"(w[33]), "r"(w[34]), "r"(w[35]), "r"(w[36]), "r"(w[37]), "r"(w[38]), "r"(w[39]), "l"(dx), "l"(de), "l"(dh)
      : "memory");
  }
  static __device__ __forceinline__ void wait_g(float* g) {
    asm volatile("wgmma.wait_group.sync.aligned 1;\n"
      : "+f"(g[0]), "+f"(g[1]), "+f"(g[2]), "+f"(g[3]), "+f"(g[4]), "+f"(g[5]), "+f"(g[6]), "+f"(g[7]), "+f"(g[8]), "+f"(g[9]), "+f"(g[10]), "+f"(g[11]), "+f"(g[12]), "+f"(g[13]), "+f"(g[14]), "+f"(g[15]), "+f"(g[16]), "+f"(g[17]), "+f"(g[18]), "+f"(g[19]), "+f"(g[20]), "+f"(g[21]), "+f"(g[22]), "+f"(g[23]), "+f"(g[24]), "+f"(g[25]), "+f"(g[26]), "+f"(g[27]), "+f"(g[28]), "+f"(g[29]), "+f"(g[30]), "+f"(g[31]), "+f"(g[32]), "+f"(g[33]), "+f"(g[34]), "+f"(g[35])
      :: "memory");
  }
  static __device__ __forceinline__ void wait_h(float* h) {
    asm volatile("wgmma.wait_group.sync.aligned 0;\n"
      : "+f"(h[0]), "+f"(h[1]), "+f"(h[2]), "+f"(h[3]), "+f"(h[4]), "+f"(h[5]), "+f"(h[6]), "+f"(h[7]), "+f"(h[8]), "+f"(h[9]), "+f"(h[10]), "+f"(h[11]), "+f"(h[12]), "+f"(h[13]), "+f"(h[14]), "+f"(h[15]), "+f"(h[16]), "+f"(h[17]), "+f"(h[18]), "+f"(h[19]), "+f"(h[20]), "+f"(h[21]), "+f"(h[22]), "+f"(h[23]), "+f"(h[24]), "+f"(h[25]), "+f"(h[26]), "+f"(h[27]), "+f"(h[28]), "+f"(h[29]), "+f"(h[30]), "+f"(h[31]), "+f"(h[32]), "+f"(h[33]), "+f"(h[34]), "+f"(h[35])
      :: "memory");
  }
};
template<> struct TileMMA<10> {
  static __device__ __forceinline__ void issue(float* g, float* h, const uint32_t* w, uint64_t dx, uint64_t de, uint64_t dh, uint64_t dc) {
    asm volatile(
      "{\n.reg .b64 dx1, dx2, dx3;\n"
      "add.s64 dx1, %120, 2;\nadd.s64 dx2, %120, 4;\nadd.s64 dx3, %120, 6;\n"
      "wgmma.fence.sync.aligned;\n"
      "wgmma.mma_async.sync.aligned.m64n80k16.f32.bf16.bf16 {%0, %1, %2, %3, %4, %5, %6, %7, %8, %9, %10, %11, %12, %13, %14, %15, %16, %17, %18, %19, %20, %21, %22, %23, %24, %25, %26, %27, %28, %29, %30, %31, %32, %33, %34, %35, %36, %37, %38, %39}, {%116, %117, %118, %119}, %122, 0, 1, 1, 0;\n"
      "wgmma.mma_async.sync.aligned.m64n80k16.f32.bf16.bf16 {%0, %1, %2, %3, %4, %5, %6, %7, %8, %9, %10, %11, %12, %13, %14, %15, %16, %17, %18, %19, %20, %21, %22, %23, %24, %25, %26, %27, %28, %29, %30, %31, %32, %33, %34, %35, %36, %37, %38, %39}, {%96, %97, %98, %99}, %121, 1, 1, 1, 0;\n"
      "wgmma.mma_async.sync.aligned.m64n80k16.f32.bf16.bf16 {%0, %1, %2, %3, %4, %5, %6, %7, %8, %9, %10, %11, %12, %13, %14, %15, %16, %17, %18, %19, %20, %21, %22, %23, %24, %25, %26, %27, %28, %29, %30, %31, %32, %33, %34, %35, %36, %37, %38, %39}, {%80, %81, %82, %83}, %120, 1, 1, 1, 0;\n"
      "wgmma.mma_async.sync.aligned.m64n80k16.f32.bf16.bf16 {%0, %1, %2, %3, %4, %5, %6, %7, %8, %9, %10, %11, %12, %13, %14, %15, %16, %17, %18, %19, %20, %21, %22, %23, %24, %25, %26, %27, %28, %29, %30, %31, %32, %33, %34, %35, %36, %37, %38, %39}, {%84, %85, %86, %87}, dx1, 1, 1, 1, 0;\n"
      "wgmma.mma_async.sync.aligned.m64n80k16.f32.bf16.bf16 {%0, %1, %2, %3, %4, %5, %6, %7, %8, %9, %10, %11, %12, %13, %14, %15, %16, %17, %18, %19, %20, %21, %22, %23, %24, %25, %26, %27, %28, %29, %30, %31, %32, %33, %34, %35, %36, %37, %38, %39}, {%88, %89, %90, %91}, dx2, 1, 1, 1, 0;\n"
      "wgmma.mma_async.sync.aligned.m64n80k16.f32.bf16.bf16 {%0, %1, %2, %3, %4, %5, %6, %7, %8, %9, %10, %11, %12, %13, %14, %15, %16, %17, %18, %19, %20, %21, %22, %23, %24, %25, %26, %27, %28, %29, %30, %31, %32, %33, %34, %35, %36, %37, %38, %39}, {%92, %93, %94, %95}, dx3, 1, 1, 1, 0;\n"
      "wgmma.commit_group.sync.aligned;\n"
      "wgmma.mma_async.sync.aligned.m64n80k16.f32.bf16.bf16 {%40, %41, %42, %43, %44, %45, %46, %47, %48, %49, %50, %51, %52, %53, %54, %55, %56, %57, %58, %59, %60, %61, %62, %63, %64, %65, %66, %67, %68, %69, %70, %71, %72, %73, %74, %75, %76, %77, %78, %79}, {%100, %101, %102, %103}, %120, 0, 1, 1, 0;\n"
      "wgmma.mma_async.sync.aligned.m64n80k16.f32.bf16.bf16 {%40, %41, %42, %43, %44, %45, %46, %47, %48, %49, %50, %51, %52, %53, %54, %55, %56, %57, %58, %59, %60, %61, %62, %63, %64, %65, %66, %67, %68, %69, %70, %71, %72, %73, %74, %75, %76, %77, %78, %79}, {%104, %105, %106, %107}, dx1, 1, 1, 1, 0;\n"
      "wgmma.mma_async.sync.aligned.m64n80k16.f32.bf16.bf16 {%40, %41, %42, %43, %44, %45, %46, %47, %48, %49, %50, %51, %52, %53, %54, %55, %56, %57, %58, %59, %60, %61, %62, %63, %64, %65, %66, %67, %68, %69, %70, %71, %72, %73, %74, %75, %76, %77, %78, %79}, {%108, %109, %110, %111}, dx2, 1, 1, 1, 0;\n"
      "wgmma.mma_async.sync.aligned.m64n80k16.f32.bf16.bf16 {%40, %41, %42, %43, %44, %45, %46, %47, %48, %49, %50, %51, %52, %53, %54, %55, %56, %57, %58, %59, %60, %61, %62, %63, %64, %65, %66, %67, %68, %69, %70, %71, %72, %73, %74, %75, %76, %77, %78, %79}, {%112, %113, %114, %115}, dx3, 1, 1, 1, 0;\n"
      "wgmma.commit_group.sync.aligned;\n}\n"
      : "=f"(g[0]), "=f"(g[1]), "=f"(g[2]), "=f"(g[3]), "=f"(g[4]), "=f"(g[5]), "=f"(g[6]), "=f"(g[7]), "=f"(g[8]), "=f"(g[9]), "=f"(g[10]), "=f"(g[11]), "=f"(g[12]), "=f"(g[13]), "=f"(g[14]), "=f"(g[15]), "=f"(g[16]), "=f"(g[17]), "=f"(g[18]), "=f"(g[19]), "=f"(g[20]), "=f"(g[21]), "=f"(g[22]), "=f"(g[23]), "=f"(g[24]), "=f"(g[25]), "=f"(g[26]), "=f"(g[27]), "=f"(g[28]), "=f"(g[29]), "=f"(g[30]), "=f"(g[31]), "=f"(g[32]), "=f"(g[33]), "=f"(g[34]), "=f"(g[35]), "=f"(g[36]), "=f"(g[37]), "=f"(g[38]), "=f"(g[39]),
        "=f"(h[0]), "=f"(h[1]), "=f"(h[2]), "=f"(h[3]), "=f"(h[4]), "=f"(h[5]), "=f"(h[6]), "=f"(h[7]), "=f"(h[8]), "=f"(h[9]), "=f"(h[10]), "=f"(h[11]), "=f"(h[12]), "=f"(h[13]), "=f"(h[14]), "=f"(h[15]), "=f"(h[16]), "=f"(h[17]), "=f"(h[18]), "=f"(h[19]), "=f"(h[20]), "=f"(h[21]), "=f"(h[22]), "=f"(h[23]), "=f"(h[24]), "=f"(h[25]), "=f"(h[26]), "=f"(h[27]), "=f"(h[28]), "=f"(h[29]), "=f"(h[30]), "=f"(h[31]), "=f"(h[32]), "=f"(h[33]), "=f"(h[34]), "=f"(h[35]), "=f"(h[36]), "=f"(h[37]), "=f"(h[38]), "=f"(h[39])
      : "r"(w[0]), "r"(w[1]), "r"(w[2]), "r"(w[3]), "r"(w[4]), "r"(w[5]), "r"(w[6]), "r"(w[7]), "r"(w[8]), "r"(w[9]), "r"(w[10]), "r"(w[11]), "r"(w[12]), "r"(w[13]), "r"(w[14]), "r"(w[15]), "r"(w[16]), "r"(w[17]), "r"(w[18]), "r"(w[19]), "r"(w[20]), "r"(w[21]), "r"(w[22]), "r"(w[23]), "r"(w[24]), "r"(w[25]), "r"(w[26]), "r"(w[27]), "r"(w[28]), "r"(w[29]), "r"(w[30]), "r"(w[31]), "r"(w[32]), "r"(w[33]), "r"(w[34]), "r"(w[35]), "r"(w[36]), "r"(w[37]), "r"(w[38]), "r"(w[39]), "l"(dx), "l"(de), "l"(dh)
      : "memory");
  }
  static __device__ __forceinline__ void wait_g(float* g) {
    asm volatile("wgmma.wait_group.sync.aligned 1;\n"
      : "+f"(g[0]), "+f"(g[1]), "+f"(g[2]), "+f"(g[3]), "+f"(g[4]), "+f"(g[5]), "+f"(g[6]), "+f"(g[7]), "+f"(g[8]), "+f"(g[9]), "+f"(g[10]), "+f"(g[11]), "+f"(g[12]), "+f"(g[13]), "+f"(g[14]), "+f"(g[15]), "+f"(g[16]), "+f"(g[17]), "+f"(g[18]), "+f"(g[19]), "+f"(g[20]), "+f"(g[21]), "+f"(g[22]), "+f"(g[23]), "+f"(g[24]), "+f"(g[25]), "+f"(g[26]), "+f"(g[27]), "+f"(g[28]), "+f"(g[29]), "+f"(g[30]), "+f"(g[31]), "+f"(g[32]), "+f"(g[33]), "+f"(g[34]), "+f"(g[35]), "+f"(g[36]), "+f"(g[37]), "+f"(g[38]), "+f"(g[39])
      :: "memory");
  }
  static __device__ __forceinline__ void wait_h(float* h) {
    asm volatile("wgmma.wait_group.sync.aligned 0;\n"
      : "+f"(h[0]), "+f"(h[1]), "+f"(h[2]), "+f"(h[3]), "+f"(h[4]), "+f"(h[5]), "+f"(h[6]), "+f"(h[7]), "+f"(h[8]), "+f"(h[9]), "+f"(h[10]), "+f"(h[11]), "+f"(h[12]), "+f"(h[13]), "+f"(h[14]), "+f"(h[15]), "+f"(h[16]), "+f"(h[17]), "+f"(h[18]), "+f"(h[19]), "+f"(h[20]), "+f"(h[21]), "+f"(h[22]), "+f"(h[23]), "+f"(h[24]), "+f"(h[25]), "+f"(h[26]), "+f"(h[27]), "+f"(h[28]), "+f"(h[29]), "+f"(h[30]), "+f"(h[31]), "+f"(h[32]), "+f"(h[33]), "+f"(h[34]), "+f"(h[35]), "+f"(h[36]), "+f"(h[37]), "+f"(h[38]), "+f"(h[39])
      :: "memory");
  }
};
template<> struct TileMMA<11> {
  static __device__ __forceinline__ void issue(float* g, float* h, const uint32_t* w, uint64_t dx, uint64_t de, uint64_t dh, uint64_t dc) {
    asm volatile(
      "{\n.reg .b64 dx1, dx2, dx3;\n"
      "add.s64 dx1, %124, 2;\nadd.s64 dx2, %124, 4;\nadd.s64 dx3, %124, 6;\n"
      "wgmma.fence.sync.aligned;\n"
      "wgmma.mma_async.sync.aligned.m64n88k16.f32.bf16.bf16 {%0, %1, %2, %3, %4, %5, %6, %7, %8, %9, %10, %11, %12, %13, %14, %15, %16, %17, %18, %19, %20, %21, %22, %23, %24, %25, %26, %27, %28, %29, %30, %31, %32, %33, %34, %35, %36, %37, %38, %39, %40, %41, %42, %43}, {%120, %121, %122, %123}, %126, 0, 1, 1, 0;\n"
      "wgmma.mma_async.sync.aligned.m64n88k16.f32.bf16.bf16 {%0, %1, %2, %3, %4, %5, %6, %7, %8, %9, %10, %11, %12, %13, %14, %15, %16, %17, %18, %19, %20, %21, %22, %23, %24, %25, %26, %27, %28, %29, %30, %31, %32, %33, %34, %35, %36, %37, %38, %39, %40, %41, %42, %43}, %127, %125, 1, 1, 1, 0, 0;\n"
      "wgmma.mma_async.sync.aligned.m64n88k16.f32.bf16.bf16 {%0, %1, %2, %3, %4, %5, %6, %7, %8, %9, %10, %11, %12, %13, %14, %15, %16, %17, %18, %19, %20, %21, %22, %23, %24, %25, %26, %27, %28, %29, %30, %31, %32, %33, %34, %35, %36, %37, %38, %39, %40, %41, %42, %43}, {%88, %89, %90, %91}, %124, 1, 1, 1, 0;\n"
      "wgmma.mma_async.sync.aligned.m64n88k16.f32.bf16.bf16 {%0, %1, %2, %3, %4, %5, %6, %7, %8, %9, %10, %11, %12, %13, %14, %15, %16, %17, %18, %19, %20, %21, %22, %23, %24, %25, %26, %27, %28, %29, %30, %31, %32, %33, %34, %35, %36, %37, %38, %39, %40, %41, %42, %43}, {%92, %93, %94, %95}, dx1, 1, 1, 1, 0;\n"
      "wgmma.mma_async.sync.aligned.m64n88k16.f32.bf16.bf16 {%0, %1, %2, %3, %4, %5, %6, %7, %8, %9, %10, %11, %12, %13, %14, %15, %16, %17, %18, %19, %20, %21, %22, %23, %24, %25, %26, %27, %28, %29, %30, %31, %32, %33, %34, %35, %36, %37, %38, %39, %40, %41, %42, %43}, {%96, %97, %98, %99}, dx2, 1, 1, 1, 0;\n"
      "wgmma.mma_async.sync.aligned.m64n88k16.f32.bf16.bf16 {%0, %1, %2, %3, %4, %5, %6, %7, %8, %9, %10, %11, %12, %13, %14, %15, %16, %17, %18, %19, %20, %21, %22, %23, %24, %25, %26, %27, %28, %29, %30, %31, %32, %33, %34, %35, %36, %37, %38, %39, %40, %41, %42, %43}, {%100, %101, %102, %103}, dx3, 1, 1, 1, 0;\n"
      "wgmma.commit_group.sync.aligned;\n"
      "wgmma.mma_async.sync.aligned.m64n88k16.f32.bf16.bf16 {%44, %45, %46, %47, %48, %49, %50, %51, %52, %53, %54, %55, %56, %57, %58, %59, %60, %61, %62, %63, %64, %65, %66, %67, %68, %69, %70, %71, %72, %73, %74, %75, %76, %77, %78, %79, %80, %81, %82, %83, %84, %85, %86, %87}, {%104, %105, %106, %107}, %124, 0, 1, 1, 0;\n"
      "wgmma.mma_async.sync.aligned.m64n88k16.f32.bf16.bf16 {%44, %45, %46, %47, %48, %49, %50, %51, %52, %53, %54, %55, %56, %57, %58, %59, %60, %61, %62, %63, %64, %65, %66, %67, %68, %69, %70, %71, %72, %73, %74, %75, %76, %77, %78, %79, %80, %81, %82, %83, %84, %85, %86, %87}, {%108, %109, %110, %111}, dx1, 1, 1, 1, 0;\n"
      "wgmma.mma_async.sync.aligned.m64n88k16.f32.bf16.bf16 {%44, %45, %46, %47, %48, %49, %50, %51, %52, %53, %54, %55, %56, %57, %58, %59, %60, %61, %62, %63, %64, %65, %66, %67, %68, %69, %70, %71, %72, %73, %74, %75, %76, %77, %78, %79, %80, %81, %82, %83, %84, %85, %86, %87}, {%112, %113, %114, %115}, dx2, 1, 1, 1, 0;\n"
      "wgmma.mma_async.sync.aligned.m64n88k16.f32.bf16.bf16 {%44, %45, %46, %47, %48, %49, %50, %51, %52, %53, %54, %55, %56, %57, %58, %59, %60, %61, %62, %63, %64, %65, %66, %67, %68, %69, %70, %71, %72, %73, %74, %75, %76, %77, %78, %79, %80, %81, %82, %83, %84, %85, %86, %87}, {%116, %117, %118, %119}, dx3, 1, 1, 1, 0;\n"
      "wgmma.commit_group.sync.aligned;\n}\n"
      : "=f"(g[0]), "=f"(g[1]), "=f"(g[2]), "=f"(g[3]), "=f"(g[4]), "=f"(g[5]), "=f"(g[6]), "=f"(g[7]), "=f"(g[8]), "=f"(g[9]), "=f"(g[10]), "=f"(g[11]), "=f"(g[12]), "=f"(g[13]), "=f"(g[14]), "=f"(g[15]), "=f"(g[16]), "=f"(g[17]), "=f"(g[18]), "=f"(g[19]), "=f"(g[20]), "=f"(g[21]), "=f"(g[22]), "=f"(g[23]), "=f"(g[24]), "=f"(g[25]), "=f"(g[26]), "=f"(g[27]), "=f"(g[28]), "=f"(g[29]), "=f"(g[30]), "=f"(g[31]), "=f"(g[32]), "=f"(g[33]), "=f"(g[34]), "=f"(g[35]), "=f"(g[36]), "=f"(g[37]), "=f"(g[38]), "=f"(g[39]), "=f"(g[40]), "=f"(g[41]), "=f"(g[42]), "=f"(g[43]),
        "=f"(h[0]), "=f"(h[1]), "=f"(h[2]), "=f"(h[3]), "=f"(h[4]), "=f"(h[5]), "=f"(h[6]), "=f"(h[7]), "=f"(h[8]), "=f"(h[9]), "=f"(h[10]), "=f"(h[11]), "=f"(h[12]), "=f"(h[13]), "=f"(h[14]), "=f"(h[15]), "=f"(h[16]), "=f"(h[17]), "=f"(h[18]), "=f"(h[19]), "=f"(h[20]), "=f"(h[21]), "=f"(h[22]), "=f"(h[23]), "=f"(h[24]), "=f"(h[25]), "=f"(h[26]), "=f"(h[27]), "=f"(h[28]), "=f"(h[29]), "=f"(h[30]), "=f"(h[31]), "=f"(h[32]), "=f"(h[33]), "=f"(h[34]), "=f"(h[35]), "=f"(h[36]), "=f"(h[37]), "=f"(h[38]), "=f"(h[39]), "=f"(h[40]), "=f"(h[41]), "=f"(h[42]), "=f"(h[43])
      : "r"(w[0]), "r"(w[1]), "r"(w[2]), "r"(w[3]), "r"(w[4]), "r"(w[5]), "r"(w[6]), "r"(w[7]), "r"(w[8]), "r"(w[9]), "r"(w[10]), "r"(w[11]), "r"(w[12]), "r"(w[13]), "r"(w[14]), "r"(w[15]), "r"(w[20]), "r"(w[21]), "r"(w[22]), "r"(w[23]), "r"(w[24]), "r"(w[25]), "r"(w[26]), "r"(w[27]), "r"(w[28]), "r"(w[29]), "r"(w[30]), "r"(w[31]), "r"(w[32]), "r"(w[33]), "r"(w[34]), "r"(w[35]), "r"(w[36]), "r"(w[37]), "r"(w[38]), "r"(w[39]), "l"(dx), "l"(de), "l"(dh), "l"(dc)
      : "memory");
  }
  static __device__ __forceinline__ void wait_g(float* g) {
    asm volatile("wgmma.wait_group.sync.aligned 1;\n"
      : "+f"(g[0]), "+f"(g[1]), "+f"(g[2]), "+f"(g[3]), "+f"(g[4]), "+f"(g[5]), "+f"(g[6]), "+f"(g[7]), "+f"(g[8]), "+f"(g[9]), "+f"(g[10]), "+f"(g[11]), "+f"(g[12]), "+f"(g[13]), "+f"(g[14]), "+f"(g[15]), "+f"(g[16]), "+f"(g[17]), "+f"(g[18]), "+f"(g[19]), "+f"(g[20]), "+f"(g[21]), "+f"(g[22]), "+f"(g[23]), "+f"(g[24]), "+f"(g[25]), "+f"(g[26]), "+f"(g[27]), "+f"(g[28]), "+f"(g[29]), "+f"(g[30]), "+f"(g[31]), "+f"(g[32]), "+f"(g[33]), "+f"(g[34]), "+f"(g[35]), "+f"(g[36]), "+f"(g[37]), "+f"(g[38]), "+f"(g[39]), "+f"(g[40]), "+f"(g[41]), "+f"(g[42]), "+f"(g[43])
      :: "memory");
  }
  static __device__ __forceinline__ void wait_h(float* h) {
    asm volatile("wgmma.wait_group.sync.aligned 0;\n"
      : "+f"(h[0]), "+f"(h[1]), "+f"(h[2]), "+f"(h[3]), "+f"(h[4]), "+f"(h[5]), "+f"(h[6]), "+f"(h[7]), "+f"(h[8]), "+f"(h[9]), "+f"(h[10]), "+f"(h[11]), "+f"(h[12]), "+f"(h[13]), "+f"(h[14]), "+f"(h[15]), "+f"(h[16]), "+f"(h[17]), "+f"(h[18]), "+f"(h[19]), "+f"(h[20]), "+f"(h[21]), "+f"(h[22]), "+f"(h[23]), "+f"(h[24]), "+f"(h[25]), "+f"(h[26]), "+f"(h[27]), "+f"(h[28]), "+f"(h[29]), "+f"(h[30]), "+f"(h[31]), "+f"(h[32]), "+f"(h[33]), "+f"(h[34]), "+f"(h[35]), "+f"(h[36]), "+f"(h[37]), "+f"(h[38]), "+f"(h[39]), "+f"(h[40]), "+f"(h[41]), "+f"(h[42]), "+f"(h[43])
      :: "memory");
  }
};
__device__ __forceinline__ void node_mma2(float* u, float* a, const uint32_t* w, uint64_t dx) {
    asm volatile(
      "{\n.reg .b64 dx1, dx2, dx3, dy0, dy1, dy2, dy3;\n"
      "add.s64 dx1, %80, 2;\nadd.s64 dx2, %80, 4;\nadd.s64 dx3, %80, 6;\n"
      "add.s64 dy0, %80, 512;\nadd.s64 dy1, %80, 514;\nadd.s64 dy2, %80, 516;\nadd.s64 dy3, %80, 518;\n"
      "wgmma.fence.sync.aligned;\n"
      "wgmma.mma_async.sync.aligned.m64n64k16.f32.bf16.bf16 {%0, %1, %2, %3, %4, %5, %6, %7, %8, %9, %10, %11, %12, %13, %14, %15, %16, %17, %18, %19, %20, %21, %22, %23, %24, %25, %26, %27, %28, %29, %30, %31}, {%64, %65, %66, %67}, %80, 0, 1, 1, 0;\n"
      "wgmma.mma_async.sync.aligned.m64n64k16.f32.bf16.bf16 {%0, %1, %2, %3, %4, %5, %6, %7, %8, %9, %10, %11, %12, %13, %14, %15, %16, %17, %18, %19, %20, %21, %22, %23, %24, %25, %26, %27, %28, %29, %30, %31}, {%68, %69, %70, %71}, dx1, 1, 1, 1, 0;\n"
      "wgmma.mma_async.sync.aligned.m64n64k16.f32.bf16.bf16 {%0, %1, %2, %3, %4, %5, %6, %7, %8, %9, %10, %11, %12, %13, %14, %15, %16, %17, %18, %19, %20, %21, %22, %23, %24, %25, %26, %27, %28, %29, %30, %31}, {%72, %73, %74, %75}, dx2, 1, 1, 1, 0;\n"
      "wgmma.mma_async.sync.aligned.m64n64k16.f32.bf16.bf16 {%0, %1, %2, %3, %4, %5, %6, %7, %8, %9, %10, %11, %12, %13, %14, %15, %16, %17, %18, %19, %20, %21, %22, %23, %24, %25, %26, %27, %28, %29, %30, %31}, {%76, %77, %78, %79}, dx3, 1, 1, 1, 0;\n"
      "wgmma.commit_group.sync.aligned;\n"
      "wgmma.mma_async.sync.aligned.m64n64k16.f32.bf16.bf16 {%32, %33, %34, %35, %36, %37, %38, %39, %40, %41, %42, %43, %44, %45, %46, %47, %48, %49, %50, %51, %52, %53, %54, %55, %56, %57, %58, %59, %60, %61, %62, %63}, {%64, %65, %66, %67}, dy0, 0, 1, 1, 0;\n"
      "wgmma.mma_async.sync.aligned.m64n64k16.f32.bf16.bf16 {%32, %33, %34, %35, %36, %37, %38, %39, %40, %41, %42, %43, %44, %45, %46, %47, %48, %49, %50, %51, %52, %53, %54, %55, %56, %57, %58, %59, %60, %61, %62, %63}, {%68, %69, %70, %71}, dy1, 1, 1, 1, 0;\n"
      "wgmma.mma_async.sync.aligned.m64n64k16.f32.bf16.bf16 {%32, %33, %34, %35, %36, %37, %38, %39, %40, %41, %42, %43, %44, %45, %46, %47, %48, %49, %50, %51, %52, %53, %54, %55, %56, %57, %58, %59, %60, %61, %62, %63}, {%72, %73, %74, %75}, dy2, 1, 1, 1, 0;\n"
      "wgmma.mma_async.sync.aligned.m64n64k16.f32.bf16.bf16 {%32, %33, %34, %35, %36, %37, %38, %39, %40, %41, %42, %43, %44, %45, %46, %47, %48, %49, %50, %51, %52, %53, %54, %55, %56, %57, %58, %59, %60, %61, %62, %63}, {%76, %77, %78, %79}, dy3, 1, 1, 1, 0;\n"
      "wgmma.commit_group.sync.aligned;\n}\n"
      : "=f"(u[0]), "=f"(u[1]), "=f"(u[2]), "=f"(u[3]), "=f"(u[4]), "=f"(u[5]), "=f"(u[6]), "=f"(u[7]), "=f"(u[8]), "=f"(u[9]), "=f"(u[10]), "=f"(u[11]), "=f"(u[12]), "=f"(u[13]), "=f"(u[14]), "=f"(u[15]), "=f"(u[16]), "=f"(u[17]), "=f"(u[18]), "=f"(u[19]), "=f"(u[20]), "=f"(u[21]), "=f"(u[22]), "=f"(u[23]), "=f"(u[24]), "=f"(u[25]), "=f"(u[26]), "=f"(u[27]), "=f"(u[28]), "=f"(u[29]), "=f"(u[30]), "=f"(u[31]),
        "=f"(a[0]), "=f"(a[1]), "=f"(a[2]), "=f"(a[3]), "=f"(a[4]), "=f"(a[5]), "=f"(a[6]), "=f"(a[7]), "=f"(a[8]), "=f"(a[9]), "=f"(a[10]), "=f"(a[11]), "=f"(a[12]), "=f"(a[13]), "=f"(a[14]), "=f"(a[15]), "=f"(a[16]), "=f"(a[17]), "=f"(a[18]), "=f"(a[19]), "=f"(a[20]), "=f"(a[21]), "=f"(a[22]), "=f"(a[23]), "=f"(a[24]), "=f"(a[25]), "=f"(a[26]), "=f"(a[27]), "=f"(a[28]), "=f"(a[29]), "=f"(a[30]), "=f"(a[31])
      : "r"(w[0]), "r"(w[1]), "r"(w[2]), "r"(w[3]), "r"(w[4]), "r"(w[5]), "r"(w[6]), "r"(w[7]), "r"(w[8]), "r"(w[9]), "r"(w[10]), "r"(w[11]), "r"(w[12]), "r"(w[13]), "r"(w[14]), "r"(w[15]), "l"(dx)
      : "memory");
}

__device__ __forceinline__ uint32_t smem_u32(const void* p) { return (uint32_t)__cvta_generic_to_shared(p); }
__device__ __forceinline__ float ex2f(float x) { float y; asm("ex2.approx.ftz.f32 %0, %1;" : "=f"(y) : "f"(x)); return y; }
__device__ __forceinline__ float rcpf(float x) { float y; asm("rcp.approx.ftz.f32 %0, %1;" : "=f"(y) : "f"(x)); return y; }
__device__ __forceinline__ uint32_t pack_bf16(float lo, float hi) {
    uint32_t r; asm("cvt.rn.bf16x2.f32 %0, %1, %2;" : "=r"(r) : "f"(hi), "f"(lo)); return r;
}
__device__ __forceinline__ float bf_lo(uint32_t v) { return __uint_as_float(v << 16); }
__device__ __forceinline__ float bf_hi(uint32_t v) { return __uint_as_float(v & 0xFFFF0000u); }
template<int STRIDE>
__device__ __forceinline__ void cp16i(uint32_t dst, const char* base, uint32_t idx) {
    asm volatile("{\n.reg .b64 a;\nmad.wide.u32 a, %2, %3, %1;\ncp.async.cg.shared.global [%0], [a], 16;\n}\n" :: "r"(dst), "l"(base), "r"(idx), "n"(STRIDE) : "memory");
}
__device__ __forceinline__ void cp16e(uint32_t dst, const char* base, uint32_t idx, uint64_t pol) {
    asm volatile("{\n.reg .b64 a;\nmad.wide.u32 a, %2, 32, %1;\ncp.async.cg.shared.global.L2::cache_hint [%0], [a], 16, %3;\n}\n" :: "r"(dst), "l"(base), "r"(idx), "l"(pol) : "memory");
}
template<int STRIDE>
__device__ __forceinline__ void cp16z(uint32_t dst, const char* base, uint32_t idx, int k, int n, uint64_t pol) {
    if (STRIDE == 32)
        asm volatile("{\n.reg .b64 a;\n.reg .pred p;\nsetp.ge.s32 p, %3, %4;\nmad.wide.u32 a, %2, 32, %1;\ncp.async.cg.shared.global.L2::cache_hint [%0], [a], 16, p, %5;\n}\n"
                     :: "r"(dst), "l"(base), "r"(idx), "r"(k), "r"(n), "l"(pol) : "memory");
    else
        asm volatile("{\n.reg .b64 a;\n.reg .pred p;\nsetp.ge.s32 p, %3, %4;\nmad.wide.u32 a, %2, 128, %1;\ncp.async.cg.shared.global [%0], [a], 16, p;\n}\n"
                     :: "r"(dst), "l"(base), "r"(idx), "r"(k), "r"(n) : "memory");
}
template<int HI, bool Z>
__device__ __forceinline__ void cpx(uint32_t hi, uint32_t dst, uint32_t p, uint32_t lo, int k, int n) {
    if (Z) asm volatile("{\n.reg .b32 l;\n.reg .b64 a;\n.reg .pred q;\nsetp.ge.s32 q, %5, %6;\ndp2a.lo.u32.u32 l, %1, %2, %3;\nmov.b64 a, {l, %0};\ncp.async.cg.shared.global [%4], [a], 16, q;\n}\n"
                        :: "r"(hi), "r"(p), "r"(HI ? 0x8000u : 0x80u), "r"(lo), "r"(dst), "r"(k), "r"(n) : "memory");
    else asm volatile("{\n.reg .b32 l;\n.reg .b64 a;\ndp2a.lo.u32.u32 l, %1, %2, %3;\nmov.b64 a, {l, %0};\ncp.async.cg.shared.global [%4], [a], 16;\n}\n"
                      :: "r"(hi), "r"(p), "r"(HI ? 0x8000u : 0x80u), "r"(lo), "r"(dst) : "memory");
}
template<bool Z>
__device__ __forceinline__ void cpe(uint32_t hi, uint32_t dst, uint32_t idx, uint32_t lo, int k, int n, uint64_t pol) {
    if (Z) asm volatile("{\n.reg .b32 l;\n.reg .b64 a;\n.reg .pred q;\nsetp.ge.s32 q, %5, %6;\nmad.lo.u32 l, %1, 32, %2;\nmov.b64 a, {l, %0};\ncp.async.cg.shared.global.L2::cache_hint [%3], [a], 16, q, %4;\n}\n"
                        :: "r"(hi), "r"(idx), "r"(lo), "r"(dst), "l"(pol), "r"(k), "r"(n) : "memory");
    else asm volatile("{\n.reg .b32 l;\n.reg .b64 a;\nmad.lo.u32 l, %1, 32, %2;\nmov.b64 a, {l, %0};\ncp.async.cg.shared.global.L2::cache_hint [%3], [a], 16, %4;\n}\n"
                      :: "r"(hi), "r"(idx), "r"(lo), "r"(dst), "l"(pol) : "memory");
}
template<int N> __device__ __forceinline__ void cp_wait() { asm volatile("cp.async.wait_group %0;" :: "n"(N) : "memory"); }
__device__ __forceinline__ void mbar_init(uint32_t bar, int cnt) { asm volatile("mbarrier.init.shared.b64 [%0], %1;" :: "r"(bar), "r"(cnt) : "memory"); }
__device__ __forceinline__ void mbar_arrive(uint32_t bar) { asm volatile("mbarrier.arrive.shared.b64 _, [%0];" :: "r"(bar) : "memory"); }
__device__ __forceinline__ void mbar_expect(uint32_t bar, uint32_t bytes) { asm volatile("mbarrier.arrive.expect_tx.shared.b64 _, [%0], %1;" :: "r"(bar), "r"(bytes) : "memory"); }
__device__ __forceinline__ void mbar_cp_arrive(uint32_t bar) { asm volatile("cp.async.mbarrier.arrive.noinc.shared.b64 [%0];" :: "r"(bar) : "memory"); }
__device__ __forceinline__ void mbar_wait(uint32_t bar, uint32_t parity) {
    asm volatile("{\n.reg .pred p;\n.reg .u32 n;\nmbarrier.try_wait.parity.shared.b64 p, [%0], %1;\n@p bra DONE_%=;\nmov.u32 n, 0;\n"
                 "WAIT_%=:\nmbarrier.try_wait.parity.shared.b64 p, [%0], %1, 0x100000;\n@p bra DONE_%=;\n"
                 "add.u32 n, n, 1;\nsetp.lt.u32 p, n, 0x400000;\n@p bra WAIT_%=;\ntrap;\nDONE_%=:\n}\n"
                 :: "r"(bar), "r"(parity) : "memory");
}
__device__ __forceinline__ void mbar_wait_c(uint32_t bar, uint32_t parity) {
    asm volatile("{\n.reg .pred p;\nWAIT_%=:\nmbarrier.try_wait.parity.shared.b64 p, [%0], %1;\n@p bra DONE_%=;\nbra WAIT_%=;\nDONE_%=:\n}\n"
                 :: "r"(bar), "r"(parity) : "memory");
}
__device__ __forceinline__ void mbar_wait_h(uint32_t bar, uint32_t parity) {
    asm volatile("{\n.reg .pred p;\nWAIT_%=:\nmbarrier.try_wait.parity.shared.b64 p, [%0], %1, 0x100000;\n@p bra DONE_%=;\nbra WAIT_%=;\nDONE_%=:\n}\n"
                 :: "r"(bar), "r"(parity) : "memory");
}
__device__ __forceinline__ uint32_t lds32(uint32_t a) { uint32_t v; asm volatile("ld.shared.u32 %0, [%1];" : "=r"(v) : "r"(a) : "memory"); return v; }
__device__ __forceinline__ void sts32(uint32_t a, uint32_t v) { asm volatile("st.shared.u32 [%0], %1;" :: "r"(a), "r"(v) : "memory"); }
__device__ __forceinline__ uint2 lds64(uint32_t a) { uint2 v; asm volatile("ld.shared.v2.u32 {%0,%1}, [%2];" : "=r"(v.x), "=r"(v.y) : "r"(a) : "memory"); return v; }
__device__ __forceinline__ uint4 lds128(uint32_t a) { uint4 v; asm volatile("ld.shared.v4.u32 {%0,%1,%2,%3}, [%4];" : "=r"(v.x), "=r"(v.y), "=r"(v.z), "=r"(v.w) : "r"(a) : "memory"); return v; }
__device__ __forceinline__ void sts128(uint32_t a, uint4 v) { asm volatile("st.shared.v4.u32 [%0], {%1,%2,%3,%4};" :: "r"(a), "r"(v.x), "r"(v.y), "r"(v.z), "r"(v.w) : "memory"); }
__device__ __forceinline__ void ldsm4t(uint32_t* v, uint32_t a) {
    asm volatile("ldmatrix.sync.aligned.m8n8.x4.trans.shared.b16 {%0,%1,%2,%3}, [%4];" : "=r"(v[0]), "=r"(v[1]), "=r"(v[2]), "=r"(v[3]) : "r"(a) : "memory");
}
__device__ __forceinline__ void stsm4t(uint32_t a, const uint32_t* v) {
    asm volatile("stmatrix.sync.aligned.m8n8.x4.trans.shared.b16 [%0], {%1,%2,%3,%4};" :: "r"(a), "r"(v[0]), "r"(v[1]), "r"(v[2]), "r"(v[3]) : "memory");
}
__device__ __forceinline__ int atoms_inc(uint32_t a) { int v; asm volatile("atom.shared.add.u32 %0, [%1], 1;" : "=r"(v) : "r"(a) : "memory"); return v; }
__device__ __forceinline__ bool elect_one() {
    uint32_t el;
    asm volatile("{\n.reg .pred p;\nelect.sync _|p, 0xffffffff;\nselp.u32 %0, 1, 0, p;\n}" : "=r"(el));
    return el != 0;
}
__device__ __forceinline__ float tanhf_a(float x) { float y; asm("tanh.approx.f32 %0, %1;" : "=f"(y) : "f"(x)); return y; }
__device__ __forceinline__ const char* as_pair(const void* p, uint32_t scratch) {
    const char* r;
    asm volatile("st.shared.u64 [%1], %2;\nld.volatile.shared.u64 %0, [%1];" : "=l"(r) : "r"(scratch), "l"(p) : "memory");
    return r;
}
__device__ __forceinline__ void ld_unit(uint4& v, const char* p, bool ok) {
    asm volatile("{\n.reg .pred q;\nsetp.ne.u32 q, %5, 0;\n@q ld.relaxed.gpu.global.v4.u32 {%0,%1,%2,%3}, [%4];\n}"
                 : "+r"(v.x), "+r"(v.y), "+r"(v.z), "+r"(v.w) : "l"(p), "r"((uint32_t)ok) : "memory");
}
__device__ __forceinline__ void ld_unit(uint2& v, const char* p, bool ok) {
    asm volatile("{\n.reg .pred q;\nsetp.ne.u32 q, %3, 0;\n@q ld.relaxed.gpu.global.v2.u32 {%0,%1}, [%2];\n}"
                 : "+r"(v.x), "+r"(v.y) : "l"(p), "r"((uint32_t)ok) : "memory");
}
__device__ __forceinline__ void bulk_ld(uint32_t dst, const void* src, int bytes, uint32_t bar) {
    mbar_expect(bar, bytes);
    if (bytes > 0) asm volatile("cp.async.bulk.shared::cluster.global.mbarrier::complete_tx::bytes [%0], [%1], %2, [%3];" :: "r"(dst), "l"(src), "r"(bytes), "r"(bar) : "memory");
}
__device__ __forceinline__ void bulk_st(void* dst, uint32_t src, int bytes) {
    asm volatile("cp.async.bulk.global.shared::cta.bulk_group [%0], [%1], %2;" :: "l"(dst), "r"(src), "r"(bytes) : "memory");
}

__device__ __forceinline__ void finish(uint4& a, const uint4& xu, const uint4& xv) {
    asm("{\n.reg .b32 z;\nfma.rn.relu.bf16x2 z, %0, %3, %1;\nadd.rn.bf16x2 %0, z, %2;\n}" : "+r"(a.x) : "r"(xu.x), "r"(xv.x), "r"(0x3F803F80u));
    asm("{\n.reg .b32 z;\nfma.rn.relu.bf16x2 z, %0, %3, %1;\nadd.rn.bf16x2 %0, z, %2;\n}" : "+r"(a.y) : "r"(xu.y), "r"(xv.y), "r"(0x3F803F80u));
    asm("{\n.reg .b32 z;\nfma.rn.relu.bf16x2 z, %0, %3, %1;\nadd.rn.bf16x2 %0, z, %2;\n}" : "+r"(a.z) : "r"(xu.z), "r"(xv.z), "r"(0x3F803F80u));
    asm("{\n.reg .b32 z;\nfma.rn.relu.bf16x2 z, %0, %3, %1;\nadd.rn.bf16x2 %0, z, %2;\n}" : "+r"(a.w) : "r"(xu.w), "r"(xv.w), "r"(0x3F803F80u));
}

__device__ __forceinline__ void node_rows(uint32_t p, const float* a) {
    #pragma unroll
    for (int i = 0; i < 4; i++) {
        const float* u = a + 8 * i;
        const uint32_t v[4] = {pack_bf16(u[0], u[1]), pack_bf16(u[2], u[3]), pack_bf16(u[4], u[5]), pack_bf16(u[6], u[7])};
        stsm4t(p + i * 2048, v);
    }
}

constexpr float EPS2 = 2e-6f;
constexpr float TAU = 2.5e-5f;

template<bool HALF>
__device__ __forceinline__ void make_wfrag(uint32_t* f, const uint32_t* v) {
    const uint32_t v0 = v[0], v1 = v[1], v2 = v[2], v3 = v[3];
    f[0] = __byte_perm(v0, v1, 0x5410); f[1] = __byte_perm(v0, v1, 0x7632);
    f[2] = __byte_perm(v2, v3, 0x5410); f[3] = __byte_perm(v2, v3, 0x7632);
    if (HALF) {
        #pragma unroll
        for (int i = 0; i < 4; i++) asm("mul.rn.bf16x2 %0, %0, %1;" : "+r"(f[i]) : "r"(0x3F003F00u));
    }
}

template<int NP>
__device__ __forceinline__ void epi_fast(const float* g, const float* h, float m1, float m2,
                                         float& n0, float& d0, float& n1, float& d1, float& dmin)
{
    constexpr int JC = NP >= 6 ? NP - 3 : NP >= 4 ? NP - 2 : NP - 1;
    constexpr int JT = NP < 3 ? -1 : JC < NP - 1 ? JC : NP - 2;
    #pragma unroll
    for (int j = 0; j < NP; j++) {
        float t0 = tanhf_a(g[4*j+0]), t1 = tanhf_a(g[4*j+1]), t2 = tanhf_a(g[4*j+2]), t3 = tanhf_a(g[4*j+3]);
        auto add_d = [&]() {
            if (j == 0) { d0 = t0 + (2.f * (JT + 1) + EPS2); d1 = t2 + (2.f * (JT + 1) + EPS2); } else { d0 += t0; d1 += t2; }
            d0 += t1; d1 += t3;
        };
        if (j <= JT) add_d();
        if (j == NP - 1) { t0 = fmaf(t0, m1, m1); t1 = fmaf(t1, m2, m2); t2 = fmaf(t2, m1, m1); t3 = fmaf(t3, m2, m2); }
        else { t0 += 1.f; t1 += 1.f; t2 += 1.f; t3 += 1.f; }
        if (j > JT) add_d();
        if (j == 0) { n0 = t0 * h[0]; n1 = t2 * h[2]; } else { n0 = fmaf(t0, h[4*j], n0); n1 = fmaf(t2, h[4*j+2], n1); }
        n0 = fmaf(t1, h[4*j+1], n0); n1 = fmaf(t3, h[4*j+3], n1);
        if (j == JC) dmin = fminf(d0, d1);
    }
}

__device__ __noinline__ float4 epi_exact(const float4* gh, int np, int dv)
{
    float n0 = 0.f, d0 = EPS2, n1 = 0.f, d1 = EPS2;
    #pragma unroll 2
    for (int j = 0; j < np; j++) {
        const float4 g = gh[j], h = gh[NPMAX + j];
        const float ma = (2 * j < dv) ? 2.f : 0.f, mb = (2 * j + 1 < dv) ? 2.f : 0.f;
        const float e0 = ma * rcpf(1.f + ex2f(-2.f * LOG2E * g.x)), e1 = mb * rcpf(1.f + ex2f(-2.f * LOG2E * g.y));
        const float e2 = ma * rcpf(1.f + ex2f(-2.f * LOG2E * g.z)), e3 = mb * rcpf(1.f + ex2f(-2.f * LOG2E * g.w));
        d0 += e0 + e1; n0 = fmaf(e0, h.x, fmaf(e1, h.y, n0));
        d1 += e2 + e3; n1 = fmaf(e2, h.z, fmaf(e3, h.w, n1));
    }
    return make_float4(n0, d0, n1, d1);
}
template<int NP>
__device__ __forceinline__ void epi_dump(const float* g, const float* h, float4* gh) {
    #pragma unroll
    for (int i = 0; i < NP; i++) {
        gh[i] = make_float4(g[4*i], g[4*i+1], g[4*i+2], g[4*i+3]);
        gh[NPMAX + i] = make_float4(h[4*i], h[4*i+1], h[4*i+2], h[4*i+3]);
    }
}

__device__ __noinline__ void slow_bin(const __nv_bfloat16* x, const __nv_bfloat16* ea, const int* src, const int* dst,
                                      const __nv_bfloat16* wa, const __nv_bfloat16* wb, const __nv_bfloat16* wc,
                                      const __nv_bfloat16* wu, const __nv_bfloat16* wv, __nv_bfloat16* out,
                                      int E, int node0, int nn, int nthr)
{
    const int tid = threadIdx.x, lane = tid & 31;
    for (int i = tid; i < nn * 128; i += nthr) g_slow[(size_t)node0 * 128 + i] = 0.f;
    asm volatile("bar.sync 1, %0;" :: "r"(nthr) : "memory");
    for (int e0 = (tid >> 5) * 32; e0 < E; e0 += nthr) {
        int d = (e0 + lane < E) ? dst[e0 + lane] - node0 : -1;
        unsigned m = __ballot_sync(~0u, d >= 0 && d < nn);
        while (m) {
            int l = __ffs(m) - 1; m &= m - 1;
            int e = e0 + l, n = node0 + __shfl_sync(~0u, d, l), s = src[e];
            float g0 = 0, g1 = 0, h0 = 0, h1 = 0;
            for (int k = 0; k < 64; k++) {
                float xs = __bfloat162float(x[(size_t)s * 64 + k]), xd = __bfloat162float(x[(size_t)n * 64 + k]);
                uint32_t b2 = *(const uint32_t*)(wb + k * 64 + 2 * lane), v2 = *(const uint32_t*)(wv + k * 64 + 2 * lane);
                uint32_t a2 = *(const uint32_t*)(wa + k * 64 + 2 * lane);
                g0 = fmaf(xs, bf_lo(b2), fmaf(xd, bf_lo(a2), g0)); g1 = fmaf(xs, bf_hi(b2), fmaf(xd, bf_hi(a2), g1));
                h0 = fmaf(xs, bf_lo(v2), h0); h1 = fmaf(xs, bf_hi(v2), h1);
            }
            for (int k = 0; k < 16; k++) {
                float ev = __bfloat162float(ea[(size_t)e * 16 + k]);
                uint32_t c2 = *(const uint32_t*)(wc + k * 64 + 2 * lane);
                g0 = fmaf(ev, bf_lo(c2), g0); g1 = fmaf(ev, bf_hi(c2), g1);
            }
            float s0 = rcpf(1.f + ex2f(-LOG2E * g0)), s1 = rcpf(1.f + ex2f(-LOG2E * g1));
            float* acc = g_slow + (size_t)n * 128 + 4 * lane;
            atomicAdd(acc + 0, s0 * h0); atomicAdd(acc + 1, s0);
            atomicAdd(acc + 2, s1 * h1); atomicAdd(acc + 3, s1);
        }
    }
    __threadfence();
    asm volatile("bar.sync 1, %0;" :: "r"(nthr) : "memory");
    for (int i = tid; i < nn * 32; i += nthr) {
        int n = node0 + (i >> 5), cp = i & 31;
        float4 a = __ldcg((const float4*)(g_slow + (size_t)n * 128 + 4 * cp));
        float u0 = 0, u1 = 0;
        for (int k = 0; k < 64; k++) {
            float xd = __bfloat162float(x[(size_t)n * 64 + k]);
            uint32_t w2 = *(const uint32_t*)(wu + k * 64 + 2 * cp);
            u0 = fmaf(xd, bf_lo(w2), u0); u1 = fmaf(xd, bf_hi(w2), u1);
        }
        uint32_t xv = *(const uint32_t*)(x + (size_t)n * 64 + 2 * cp);
        float z0 = u0 + a.x / (a.y + 1e-6f), z1 = u1 + a.z / (a.w + 1e-6f);
        *(uint32_t*)(out + (size_t)n * 64 + 2 * cp) = pack_bf16(bf_lo(xv) + fmaxf(z0, 0.f), bf_hi(xv) + fmaxf(z1, 0.f));
    }
}

__global__ void __launch_bounds__(256) slow_kernel(const __nv_bfloat16* x, const __nv_bfloat16* ea, const int* src, const int* dst,
        const __nv_bfloat16* wa, const __nv_bfloat16* wb, const __nv_bfloat16* wc, const __nv_bfloat16* wu, const __nv_bfloat16* wv,
        __nv_bfloat16* out, int N, int E, int npb)
{
    int node0 = blockIdx.x * npb;
    slow_bin(x, ea, src, dst, wa, wb, wc, wu, wv, out, E, node0, max(0, min(npb, N - node0)), 256);
}

constexpr int XS_BYTES = NPMAX * 1024;
constexpr int ES_BYTES = NPMAX * 256;
constexpr int SM_XS = 0;
constexpr int SM_XU = SM_XS + 3 * NSTAGE * XS_BYTES;
constexpr int SM_TAB = SM_XU + NPB_MAX * 128;
constexpr int SM_ES = SM_TAB + (NPB_MAX + 2) * 128;
constexpr int SM_WC = SM_ES + 3 * NSTAGE * ES_BYTES;
constexpr int SM_OH = SM_WC + 2048;
constexpr int SM_EID = SM_OH + 256;
constexpr int SM_SRC = SM_EID + (SLOT_CAP + 32) * 4;
constexpr int SM_TINFO = SM_SRC + (SLOT_CAP + 32) * 2;
constexpr int SM_MISC = SM_TINFO + TILE_CAP * 32;
constexpr int SM_CLAIM = SM_TAB + (NPB_MAX + 1) * 128;
constexpr int SM_BARS = SM_MISC + 32 * 4;
constexpr int SM_ABAR = SM_BARS + 6 * 48;
constexpr int SM_XBAR = SM_ABAR + 10 * 8;
constexpr int SM_SBAR = SM_XBAR + 4 * 8;
constexpr int SM_GBAR = SM_SBAR + 3 * 8;
constexpr int SM_WL = SM_GBAR + 97 * 8;
constexpr int WST = 9;
constexpr int SMEM_BYTES = SM_WL + (96 + WST) * 8;
constexpr int SM_P2 = 0, SM_P1 = 6 * 384 * 16;
constexpr int SM_DEG = SM_P1 + P1B;
constexpr int SM_CNT = SM_DEG + 512 * 4;
constexpr int SM_CLS = SM_CNT + 512 * 4;
constexpr int SM_HIST = SM_CLS + NCLS * 4;
constexpr int SM_XLIST = SM_HIST + 136 * 4;
constexpr int SM_SORT = SM_XLIST + XCAP * 8;
constexpr int SM_BASE = SM_SORT + NPB_MAX * 4;
constexpr int SM_PAIR = SM_BASE + (NPB_MAX + 4) * 2;
constexpr int SM_IDX = SM_EID;
constexpr int SM_WR = SM_TAB;
static_assert(TILE_CAP <= 128 && TR >= 2 && SM_ES % 256 == 0 && NSTAGE == 2 && SM_BARS % 16 == 0 && SM_TINFO % 16 == 0 && SM_EID % 128 == 0 && SM_TAB % 1024 == 0 && SM_XU % 1024 == 0 && SM_TINFO % 8 == 0 && SM_OH % 16 == 0 && SM_SORT % 16 == 0 && SM_PAIR % 8 == 0, "align");
static_assert(P1B % 16 == 0 && P2B <= SM_P1 && NB_MAX <= 6 * 24 && SM_PAIR + 128 * 8 <= SM_XU && CH_MAX * 4 <= SM_SRC - SM_EID && SM_DEG >= 3 << 14, "alias");
static_assert(SMEM_BYTES <= 232448, "smem");
constexpr uint32_t C_BRK = 16  , C_CONT = 32, C_MORE = 64;
constexpr uint32_t ONE_F = 0x3F800000u;
constexpr int NONE = NPB_MAX;

__device__ __forceinline__ uint2 tile_info(uint32_t e) {
    const uint32_t y = (uint32_t)((int)e >> 16) & (ONE_F | 0x1FFFu);
    return make_uint2(e, (e & 0x1F000000u) ? y | 0x80000000u : y);
}
__device__ __forceinline__ bool unpad(uint32_t w1, int np, float ga, float gb, float& d0, float& d1, int& dv) {
    const int pad = (int)w1 < 0 ? (w1 >> 8) & 31 : 0;
    dv = 2 * np - 2 - pad + ((int)w1 > 127) + ((int)w1 >= (int)ONE_F);
    float t0 = TAU * 2 * np, t1 = t0;
    if (pad) {
        t0 = fmaxf(t0, d0 * (1.f / 1024)); t1 = fmaxf(t1, d1 * (1.f / 1024));
        asm volatile("tanh.approx.f32 %0, %0;\ntanh.approx.f32 %1, %1;" : "+f"(ga), "+f"(gb));
        d0 -= pad * (1.f + ga); d1 -= pad * (1.f + gb);
    }
    if (dv == 0) { d0 = d1 = EPS2; t0 = t1 = 0.f; }
    return __any_sync(~0u, d0 < t0 || d1 < t1);
}
__device__ __forceinline__ uint64_t desc_sw128(uint32_t a) {
    return (uint64_t)((a & 0x3FFFF) >> 4) | ((uint64_t)1 << 16) | ((uint64_t)64 << 32) | ((uint64_t)1 << 62);
}

__device__ __forceinline__ uint32_t sel(bool c, uint32_t a, uint32_t b) {
    uint32_t r; asm("{\n.reg .pred p;\nsetp.ne.u32 p, %1, 0;\nselp.b32 %0, %2, %3, p;\n}" : "=r"(r) : "r"((uint32_t)c), "r"(a), "r"(b)); return r;
}
__device__ __forceinline__ void tile_entry(uint8_t* smem, uint32_t sv, int dg, int mn, int t, int tl, int np, int done, uint32_t flags, int next) {
    const uint32_t nd = sv & 0xFFFF, w0 = nd * 128 + ((nd & 7) << 4);
    const int dv = min(max(dg - done, 0), 2 * np), r = 2 * np - dv;
    const bool gen = mn - done < 2 * np - 2;
    const uint32_t w1 = (uint32_t)np | flags | sel(gen || flags, C_BRK, 0u) | sel(r < 2, 0x8000u >> (8 * r), (r - 2) << 8);
    *(uint2*)(smem + SM_TINFO + tl * 32 + t * 8) = make_uint2(sel(dv, (sv >> 16) + done, 0) | (sel(gen, 13 + (np > 5) + (np > 8), np) << 16) | (next << 20) | ((uint32_t)dv << 27), w0 | sel(np, w1 << 16, 0u));
}
__device__ __noinline__ void tiles_many(uint8_t* smem, uint32_t sv, int dg, int mn, int id, int left, unsigned sm) {
    int* misc = (int*)(smem + SM_MISC);
    int nt = (left + NPMAX - 1) / NPMAX, tl = id >> 2, done = 0, nx = 0;
    if ((id & 3) == 0) { nx = atomicAdd(&misc[5], nt - 1); if (nx + nt - 1 > TILE_CAP) misc[1] = 1; }
    nx = __shfl_sync(sm, nx, id & 28);
    if (nx + nt - 1 > TILE_CAP) left = 0;
    uint32_t cont = 0;
    #pragma unroll 1
    while (left > 0) {
        const int np = (left + nt - 1) / nt;
        left -= np; nt--;
        tile_entry(smem, sv, dg, mn, id & 3, tl, np, done, cont | (left > 0 ? C_MORE : 0u), left > 0 ? nx : 0);
        tl = nx++; cont = C_CONT; done += 2 * np;
    }
}
__device__ __forceinline__ void tables(uint8_t* smem, uint32_t sbase, int id0, int ngroups) {
    const int t = id0 & 3;
    uint4 s4[3];
    uint32_t me[3], sv[3];
    #pragma unroll
    for (int k = 0; k < 3; k++) { s4[k] = lds128(sbase + SM_SORT + (id0 & ~3) * 4 + k * 512); me[k] = lds32(sbase + SM_SORT + id0 * 4 + k * 512); }
    #pragma unroll
    for (int k = 0; k < 3; k++) asm volatile("ld.shared.u16 %0, [%1];" : "=r"(sv[k]) : "r"(sbase + SM_BASE + (me[k] & 0xFFFF) * 2) : "memory");
    int mn[3], left[3];
    uint32_t more = 0;
    #pragma unroll
    for (int k = 0; k < 3; k++) {
        const int g = (id0 >> 2) + 32 * k, nx = ngroups + 4 + g;
        sv[k] = sv[k] << 16 | (me[k] & 0xFFFF);
        mn[k] = min(min(s4[k].x, s4[k].y), min(s4[k].z, s4[k].w)) >> 16;
        left[k] = ((max(max(s4[k].x, s4[k].y), max(s4[k].z, s4[k].w)) >> 16) + 1) >> 1;
        const bool two = left[k] > NPMAX;
        more |= two << k;
        tile_entry(smem, sv[k], me[k] >> 16, mn[k], t, sel(g >= ngroups + 4, ngroups, g), sel(two, min((left[k] + 1) >> 1, NPMAX), sel(left[k], max(left[k], NPMIN), 0)), 0, sel(two, C_MORE, 0u), sel(two, nx & 127, 0));
    }
    #pragma unroll 1
    for (int id = id0; __any_sync(~0u, more); id += 128) {
        const int nx = ngroups + 4 + (id >> 2);
        const bool odd = left[0] > 2 * NPMAX || ((more & 1) && nx >= TILE_CAP - TILE_X);
        const unsigned sm = __ballot_sync(~0u, odd);
        if (__builtin_expect(odd, 0)) tiles_many(smem, sv[0], me[0] >> 16, mn[0], id, left[0], sm);
        else if (more & 1) tile_entry(smem, sv[0], me[0] >> 16, mn[0], t, nx, left[0] >> 1, (left[0] + 1) & ~1, C_CONT, 0);
        __syncwarp();
        more >>= 1;
        sv[0] = sv[1]; sv[1] = sv[2]; me[0] = me[1]; me[1] = me[2]; mn[0] = mn[1]; mn[1] = mn[2]; left[0] = left[1]; left[1] = left[2];
    }
}
__device__ __forceinline__ uint32_t to_list(uint32_t sbase, uint32_t e, uint32_t bin) {
    uint32_t j; asm volatile("atom.shared.inc.u32 %0, [%1], 0x7fffffff;" : "=r"(j) : "r"(sbase + SM_MISC + 8) : "memory");
    j = min(j, 63u);
    sts32(sbase + SM_P1 + j * 4, e | ((j < 63 ? bin : 255u) << 16));
    return j;
}

template<bool LO32>
__global__ void __launch_bounds__(THREADS, 1)
gcn_kernel(const int* __restrict__ dst, unsigned* gbar, char* gs, const int* __restrict__ src, int E, int ch, int N, int npb, uint32_t magic,
           const __nv_bfloat16* __restrict__ x, const __nv_bfloat16* __restrict__ ea,
           const __nv_bfloat16* __restrict__ wa, const __nv_bfloat16* __restrict__ wb, const __nv_bfloat16* __restrict__ wc,
           const __nv_bfloat16* __restrict__ wu, const __nv_bfloat16* __restrict__ wv,
           __nv_bfloat16* out, int4 wrow, const __grid_constant__ CUtensorMap tm2, const __grid_constant__ CUtensorMap tmw,
           const __grid_constant__ CUtensorMap tmc, const __grid_constant__ CUtensorMap tmx)
{
    extern __shared__ __align__(1024) uint8_t smem[];
    int* cls = (int*)(smem + SM_CLS);
    int* misc = (int*)(smem + SM_MISC);
    uint32_t* xlist = (uint32_t*)(smem + SM_XLIST);
    WG0(); WS(0);
    const uint32_t sbase = smem_u32(smem);
    const int tid = threadIdx.x, lane = tid & 31;
    const int b = blockIdx.x, nb = gridDim.x;
    const int cnt = max(0, min(ch, E - b * ch));
    const int node0 = b * npb;
    auto src_ld = [&](int v) { bulk_ld(sbase + SM_XU + v * 8192, src + b * ch + v * 2048, min(max(cnt * 4 - v * 8192, 0), 8192), sbase + SM_SBAR + v * 8); };
    auto dst_ld = [&](int v) { bulk_ld(sbase + SM_IDX + v * 8192, dst + b * ch + v * 2048, min(max(cnt * 4 - v * 8192, 0), 8192), sbase + SM_ABAR + v * 8); };
    auto box_ld = [&](uint32_t dst, const CUtensorMap* tm, int col, int row, uint32_t bar) {
        asm volatile("cp.async.bulk.tensor.2d.shared::cluster.global.mbarrier::complete_tx::bytes [%0], [%1, {%3, %4}], [%2];"
            :: "r"(dst), "l"((uint64_t)tm), "r"(bar), "r"(col), "r"(row) : "memory");
    };
    auto w_ld = [&]() {
        mbar_expect(sbase + SM_ABAR + 24, 272 * 128);
        box_ld(sbase + SM_WR, &tmw, 0, wrow.y, sbase + SM_ABAR + 24); box_ld(sbase + SM_WR + 64 * 128, &tmc, 0, 0, sbase + SM_ABAR + 24);
        box_ld(sbase + SM_WR + 80 * 128, &tmw, 0, wrow.w, sbase + SM_ABAR + 24); box_ld(sbase + SM_WR + 144 * 128, &tmw, 0, wrow.x, sbase + SM_ABAR + 24);
        box_ld(sbase + SM_WR + 208 * 128, &tmw, 0, wrow.z, sbase + SM_ABAR + 24);
    };
    auto x_ld = [&](int k) {
        mbar_expect(sbase + SM_XBAR + k * 8, 16384);
        box_ld(sbase + SM_XU + k * 16384, &tmx, 0, node0 + 128 * k, sbase + SM_XBAR + k * 8);
    };
    uint32_t tag = 0;
    if (tid < 32) asm volatile("ld.relaxed.gpu.global.u32 %0, [%1];" : "=r"(tag) : "l"(gbar));
    if (tid >> 5 == 11) {
        if (elect_one()) {
            mbar_init(sbase + SM_ABAR, 1);
            asm volatile("fence.mbarrier_init.release.cluster;" ::: "memory");
            dst_ld(0);
        }
    }
    if (tid >= 384) {
        if (elect_one()) {
            const int v = (tid >> 5) & 3;
            if (v) mbar_init(sbase + SM_ABAR + v * 8, 1);
            asm volatile("fence.mbarrier_init.release.cluster;" ::: "memory");
            if (v == 1) dst_ld(v);
            if (v == 3) {
                mbar_init(sbase + SM_ABAR + 40, 1); mbar_init(sbase + SM_GBAR + 96 * 8, 32); mbar_init(sbase + SM_ABAR + 72, 384); mbar_init(sbase + SM_XBAR + 24, 512);
            }
            #pragma unroll 1
            for (int j = 0; j < 3; j++) {
                #pragma unroll
                for (int i = 0; i < 8; i++) mbar_init(sbase + SM_GBAR + (v * 24 + j * 8 + i) * 8, 32);
                if (j == 1 && v == 2) dst_ld(v);
            }
            if (tid < 480) {
                #pragma unroll
                for (int i = 0; i < 2; i++) { mbar_init(sbase + SM_BARS + (v * 2 + i) * 48, 64); mbar_init(sbase + SM_BARS + (v * 2 + i) * 48 + 8, 128); }
                mbar_init(sbase + SM_ABAR + 48 + v * 8, 128); mbar_init(sbase + SM_XBAR + v * 8, 1); mbar_init(sbase + SM_SBAR + v * 8, 1);
            }
            asm volatile("fence.mbarrier_init.release.cluster;" ::: "memory");
        }
    }
    if (tid >= 128 && tid < 132) asm volatile("prefetch.tensormap [%0];" :: "l"((uint64_t)(tid == 128 ? &tmw : tid == 129 ? &tmc : tid == 130 ? &tm2 : &tmx)) : "memory");
    const int warp = (int)__reduce_max_sync(~0u, (unsigned)tid >> 5);
    const int wg = warp >> 2, w = warp & 3;
    const int q = lane >> 2, t = lane & 3;
    const int ch0 = 16 * w + 2 * q;
    const int nn = max(0, min(npb, N - node0));
    if (sbase & 1023) __trap();

    sts32(sbase + (tid < NPB_MAX ? SM_DEG : SM_CNT) + tid * 4, tid < NPB_MAX ? 0 : 0xC0000000u);
    if (tid < NCLS + NB_MAX) cls[tid] = tid < NCLS ? 0 : (tid - NCLS) * CE + 64;
    else if (wg == 2) {
        if (w < 2) {
            *(uint32_t*)(smem + SM_OH + (tid & 63) * 4) = t != (q >> 1) ? 0u : (w == 0 ? 0x00003F00u : 0x3F000000u);
        } else if (w == 2) *(uint32_t*)(smem + SM_TAB + NPB_MAX * 128 + lane * 4) = 0u;
        else misc[lane] = lane == 5 ? TILE_CAP - TILE_X : 0;
    }
    if (warp == 13 && lane < WST * 2) sts32(sbase + SM_WL + 768 + lane * 4, NONE * 0x10001u);
    if (warp == 14) sts32(sbase + SM_TINFO + 96 * 32 + lane * 4, 0);
    if (warp == 15) sts32(sbase + SM_CLAIM + lane * 4, lane == 0 ? 3 : 0x40000000);
    if (wg < 3) {
        #pragma unroll 1
        for (int i = tid; i < P2B / 32; i += 384) { sts128(sbase + SM_P2 + i * 16, make_uint4(0, 0, 0, 0)); sts128(sbase + SM_P2 + P2B / 2 + i * 16, make_uint4(0, 0, 0, 0)); }
    }
    if (tid == 0) sts32(sbase + SM_PAIR, tag);
    if (wg < 3) { asm volatile("bar.sync 1, 384;" ::: "memory"); tag = lds32(sbase + SM_PAIR); }
    tag = (tag & 1) | 2;
    if (wg < 3) {
        const uint32_t d0 = ((NPB_MAX + ((2 * lane) & 15) + 16 * (b & 1)) * 4 | (tag << 14)) * 0x10001u, d1 = d0 + 0x40004u;
        #pragma unroll
        for (int i = 0; i < 3; i++) if (i < 2 || tid + 768 < P1B / 16) sts128(sbase + SM_P1 + (tid + 384 * i) * 16, make_uint4(d0, d0, d1, d1));
    }
    if (warp == 15 && elect_one()) w_ld();
    WS(1);
    __syncthreads();
    if (wg == 3) tag = (lds32(sbase + SM_PAIR) & 1) | 2;

    uint32_t ent[EPT];
    #pragma unroll
    for (int v = 0; v < EPT / 4; v++) {
        mbar_wait_c(sbase + SM_ABAR + v * 8, 0);
        if (((v == 0 && (warp == 13 || warp == 14)) || (v == 1 && warp == 15)) && elect_one()) src_ld(warp - 13);
        const uint32_t off = v * (THREADS * 4) + tid * 4;
        if (off < (uint32_t)cnt) {
            const uint32_t ia = sbase + SM_IDX + off * 4;
            const uint4 u = lds128(ia);
            uint32_t dv[4] = {u.x, u.y, u.z, u.w}, ps[4], ck[4];
            uint32_t* en = ent + 4 * v;
            #pragma unroll
            for (int k = 0; k < 4; k++) {
                dv[k] = min(dv[k], (uint32_t)(nb * npb - 1));
                ps[k] = __umulhi(dv[k], magic); en[k] = atoms_inc(sbase + SM_HIST + ps[k] * 4);
            }
            #pragma unroll
            for (int k = 0; k < 4; k++) {
                dv[k] = (dv[k] - ps[k] * npb) * 4 + (tag << 14);
                ck[k] = en[k] - ps[k] * CE;
                en[k] ^= ps[k] * 4 & 60;
            }
            if (__builtin_expect(max(max(ck[0], ck[1]), max(ck[2], ck[3])) >= 64 + CE, 0)) {
                #pragma unroll
                for (int k = 0; k < 4; k++) if (ck[k] >= 64 + CE) en[k] = to_list(sbase, dv[k], ps[k]);
            }
            #pragma unroll
            for (int k = 0; k < 4; k++)
                asm volatile("{\n.reg .pred p;\nsetp.ge.u32 p, %2, 64;\n@p st.shared.u16 [%0], %1;\n}" :: "r"(sbase + SM_P1 + 128 + en[k] * 2), "r"(dv[k]), "r"(en[k]) : "memory");
        }
    }
    WS(5);
    __syncthreads();
    auto send = [&](int o, uint32_t a, int bytes) {
        if (warp == 14 && elect_one()) {
            asm volatile("fence.proxy.async.shared::cta;" ::: "memory");
            bulk_st(gs + b * (P1B + P2B) + o, a, bytes);
            asm volatile("cp.async.bulk.commit_group;" ::: "memory");
        }
    };
    send(0, sbase + SM_P1, 256 + nb * (CE * 2));
    #pragma unroll
    for (int v = 0; v < EPT / 4; v++) {
        mbar_wait_c(sbase + SM_SBAR + v * 8, 0);
        const uint32_t off = v * (THREADS * 4) + tid * 4;
        if (off < (uint32_t)cnt) {
            const uint4 sv = lds128(sbase + SM_XU + off * 4);
            const uint32_t ss[4] = {sv.x, sv.y, sv.z, sv.w};
            #pragma unroll
            for (int k = 0; k < 4; k++) sts32(sbase + SM_P2 + ent[4*v+k] * 4, (ss[k] & 0xFFFF) | (((off + k) << 19) + (tag << 16)));
        }
    }
    WS(7);
    __syncthreads();
    send(P1B, sbase + SM_P2, 256 + nb * (CE * 4));
    WSL(8);

    const int ngroups = (nn + 3) >> 2;
    if (wg == 3) {
        asm volatile("setmaxnreg.dec.sync.aligned.u32 56;");
        WS(2);
        const char* const ga = as_pair((const char*)x + (w < 3 ? 0 : (size_t)node0 * 128) + (lane & 7) * 16, sbase + SM_PAIR + (tid & 127) * 8);
        const char* const gb = as_pair(w < 3 ? (const char*)ea + (lane & 1) * 16 : (const char*)out + (size_t)node0 * 128 + (lane & 7) * 16, sbase + SM_PAIR + (tid & 127) * 8);
        WS(3);
        const uint32_t dm = ((NPB_MAX + lane) * 4 | (tag << 14)) * 0x10001u;
        const uint32_t db = sbase + SM_DEG - (tag << 14);
        const char* gl = gs + ((tid & 127) >> 2) * (P1B + P2B) + t * 16;
        uint4 rl[5];
        #pragma unroll
        for (int i = 0; i < 5; i++) rl[i].w = ((tid & 127) >> 2) + 32 * i < nb ? 0 : dm;
        auto p2_ld = [&]() {
            mbar_expect(sbase + SM_ABAR + 40, nb * (CE * 4));
            box_ld(sbase + SM_P2, &tm2, P1B / 4 + 64 + b * CE, 0, sbase + SM_ABAR + 40);
        };
        asm volatile("cp.async.bulk.wait_group.read 0;" ::: "memory");
        asm volatile("bar.sync 6, 128;" ::: "memory");
        WSL(12);
        uint32_t spins = 0;
        #pragma unroll 1
        for (int r = 0;; r++) {
            #pragma unroll
            for (int i = 0; i < 5; i++) rl[i].x = rl[i].y = rl[i].z = dm;
            while (true) {
                #pragma unroll
                for (int i = 0; i < 5; i++) ld_unit(rl[i], gl + i * (32 * (P1B + P2B)), (rl[i].w ^ dm) & 0xC000);
                if (spins == 0) asm volatile("bar.sync 5, 512;" ::: "memory");
                if (++spins > (1u << 22)) __trap();
                if (!__any_sync(~0u, ((rl[0].w ^ dm) | (rl[1].w ^ dm) | (rl[2].w ^ dm) | (rl[3].w ^ dm) | (rl[4].w ^ dm)) & 0xC000)) break;
            }
            WS(4);
            uint32_t own = 0;
            #pragma unroll
            for (int i = 0; i < 5; i++) {
                const uint32_t bb = b << 16;
                own |= (min(min(rl[i].x ^ bb, rl[i].y ^ bb), min(rl[i].z ^ bb, rl[i].w ^ bb)) < 0x10000u) << i;
            }
            while (own != 0) {
                const int i = __ffs(own) - 1; own &= own - 1;
                const uint4 u = i == 0 ? rl[0] : i == 1 ? rl[1] : i == 2 ? rl[2] : i == 3 ? rl[3] : rl[4];
                const uint32_t e[4] = {u.x ^ (b << 16), u.y ^ (b << 16), u.z ^ (b << 16), u.w ^ (b << 16)};
                const uint32_t s = (((tid & 127) >> 2) + 32 * i << 16) + (4 * r + t << 26);
                int n;
                asm volatile("atom.shared.add.u32 %0, [%1], %2;" : "=r"(n) : "r"(sbase + SM_MISC), "r"((e[0] < 0x10000u) + (e[1] < 0x10000u) + (e[2] < 0x10000u) + (e[3] < 0x10000u)) : "memory");
                #pragma unroll
                for (int k = 0; k < 4; k++) asm volatile("red.shared.add.u32 [%0], 1;" :: "r"(db + min(e[k], dm & 0xFFFF)) : "memory");
                if (n + 4 > XCAP) { misc[1] = 1; n = 0; }
                #pragma unroll
                for (int k = 0; k < 4; k++) if (e[k] < 0x10000u) xlist[n++] = e[k] | (s + (k << 24));
            }
            __syncwarp();
            if (__builtin_expect(!__any_sync(~0u, t == 3 && min(min(min(rl[0].w, rl[1].w), min(rl[2].w, rl[3].w)), rl[4].w) < 0x1000000u), 1)) break;
            if (r == 3) { misc[1] = 1; break; }
            #pragma unroll
            for (int i = 0; i < 5; i++) rl[i].w = __shfl_sync(~0u, rl[i].w, lane | 3) < 0x1000000u ? 0 : dm;
            gl += 64;
        }
        WS(11);
        asm volatile("bar.sync 7, 512;" ::: "memory");
        auto rest_ld = [&]() {
            if (w == 2 && elect_one()) {
                p2_ld(); x_ld(2);
            }
            __syncwarp();
        };
        WS(9);
        {
            int dg[3], cl[3], cr[3];
            #pragma unroll
            for (int k = 0; k < 3; k++) dg[k] = lds32(sbase + SM_DEG + ((tid & 127) + 128 * k) * 4);
            const uint2 m01 = lds64(sbase + SM_MISC);
            const int xi = (tid + 96) & 127, nx = m01.y ? 0 : m01.x;
            const uint32_t xe = xlist[xi];
            #pragma unroll
            for (int k = 0; k < 3; k++) {
                cl[k] = NCLS - 1 - (dg[k] <= 40 ? dg[k] : min(41 + ((dg[k] - 41) >> 3), NCLS - 1));
                cr[k] = atoms_inc(sbase + ((tid & 127) + 128 * k < nn ? SM_CLS + cl[k] * 4 : SM_DEG + NPB_MAX * 4));
            }
            rest_ld();
            asm volatile("bar.sync 6, 128;" ::: "memory");
            WS(13);
            const uint2 c = lds64(sbase + SM_CLS + lane * 8);
            uint32_t inc = c.x + c.y;
            #pragma unroll
            for (int o = 1; o < 32; o <<= 1) { const uint32_t y = __shfl_up_sync(~0u, inc, o); if (lane >= o) inc += y; }
            inc = (inc - c.x - c.y) | (inc - c.y) << 16;
            #pragma unroll
            for (int k = 0; k < 3; k++) {
                const int id = (tid & 127) + 128 * k;
                const uint32_t e = __shfl_sync(~0u, inc, cl[k] >> 1);
                const uint32_t pos = id < nn ? (cl[k] & 1 ? e >> 16 : e & 0xFFFF) + cr[k] : id, nd = id < nn ? id : NONE;
                sts32(sbase + SM_SORT + pos * 4, nd | min(dg[k], 65535) << 16);
                asm volatile("st.shared.u16 [%0], %1;" :: "r"(sbase + SM_WL + pos * 2), "r"(nd) : "memory");
            }
            if (tid == 511) misc[4] = (nn - c.y + 3) >> 2;
            asm volatile("bar.sync 4, 512;" ::: "memory");
            WS(14);
            uint32_t xs = 0x80000000u, xv = tag << 16;
            auto x_get = [&]() { asm volatile("ld.relaxed.gpu.global.u32 %0, [%1];" : "=r"(xv) : "l"(gs + ((xe >> 16) & 0xFF) * (P1B + P2B) + P1B + (xe >> 24) * 4) : "memory"); };
            if (xi < nx) {
                asm volatile("atom.shared.add.u32 %0, [%1], 4;" : "=r"(xs) : "r"(db + (SM_CNT - SM_DEG) + (xe & 0xFFFF)) : "memory");
                x_get();
            }
            tables(smem, sbase, (tid + 32) & 127, ngroups);
            __syncwarp();
            while (__any_sync(~0u, ((xv >> 16) & 3) != tag)) { if (((xv >> 16) & 3) != tag) x_get(); if (++spins > (1u << 22)) __trap(); }
            if (xs < 4 * SLOT_CAP) {
                sts32(sbase + SM_EID + xs, ((xe >> 16) & 0xFF) * ch + (xv >> 19));
                asm volatile("st.shared.u16 [%0], %1;" :: "r"(sbase + SM_SRC + (xs >> 1)), "r"(xv) : "memory");
            }
            mbar_arrive(sbase + SM_XBAR + 24);
            asm volatile("bar.sync 6, 128;" ::: "memory");
        }
        WS(10);
        WGD();
        const int r4 = lane >> 3, c8 = lane & 7;
        const uint32_t sb = __reduce_or_sync(~0u, sbase);
        if (w < 3) {
            const char* gx = ga; const char* ge = gb;
            const uint32_t gx0 = (uint32_t)(uint64_t)gx, ge0 = (uint32_t)(uint64_t)ge, hi = (uint64_t)gx >> 32, he = (uint64_t)ge >> 32;
            const int s = (lane >> 1) & 3;
            const uint32_t xs0 = sb + SM_XS + w * NSTAGE * XS_BYTES;
            const uint32_t es0 = sb + SM_ES + w * NSTAGE * ES_BYTES + r4 * 64 + (((lane ^ (r4 >> 1)) & 1) << 4) + (s >> 1) * 256 + (s & 1) * 32;
            const uint32_t bars = sb + SM_BARS + w * 96;
            const uint32_t xoffA = (2 * r4) * 128 + ((c8 ^ (2 * r4)) << 4), xoffB = (2 * r4 + 1) * 128 + ((c8 ^ (2 * r4 + 1)) << 4);
            uint64_t pol;
            asm volatile("createpolicy.fractional.L2::evict_first.b64 %0, 1.0;" : "=l"(pol));
            uint32_t first = 1;
            WS(15);
            uint32_t ph = 1, cur = w;
            uint32_t hist = 96 * 0x010101u;
            auto done3 = [&]() { mbar_arrive(sb + SM_GBAR + ((hist >> 16) & 0xFF) * 8); };
            const uint32_t ca = sb + SM_CLAIM + lane * 4, pa = sb + SM_TINFO + r4 * 8;
            const uint2 p0 = lds64(pa + w * 32);
            const bool go = lds32(sb + SM_MISC + 4) == 0 && nn > 0;
            uint32_t pw = go ? p0.x : 0, brk = (p0.y >> 16) & C_BRK;
            const uint32_t se0 = sb + SM_EID + s * 4, xab = xoffB - xoffA, das = 2 * (xs0 + xoffA) + XS_BYTES, des = 2 * es0 + ES_BYTES, brs = 2 * bars + 48;
            uint32_t da = xs0 + xoffA, de = es0, br = bars;
            #pragma unroll 1
            while (true) {
                const uint32_t pt = __reduce_or_sync(~0u, pw);
                uint32_t se, sx;
                asm("dp2a.lo.u32.u32 %0, %1, 4, %2;" : "=r"(se) : "r"(pw), "r"(se0));
                asm("dp2a.lo.u32.u32 %0, %1, 2, %2;" : "=r"(sx) : "r"(pw), "r"(sb + SM_SRC));
                const int dv = pw >> 27;
                const uint32_t db = da + xab;
                const uint32_t sel = (pt >> 16) & 15, nx = (pt >> 20) & 127;
                uint32_t g;
                auto claim = [&]() { asm volatile("atom.shared.add.u32 %0, [%1], %2;" : "=r"(g) : "r"(ca), "r"(nx == 0 ? 1u : 0u) : "memory"); };
                if (sel == 0) break;
                claim();
                switch (sel) {
#define CASE(L, P, GEN) case L: { \
                        uint32_t oe[(P + 1) / 2], o[P]; \
                        if (first) asm volatile("bar.sync 3, 480;" ::: "memory"); \
                        _Pragma("unroll") for (int j = 0; j < (P + 1) / 2; j++) oe[j] = lds32(se + j * 16); \
                        _Pragma("unroll") for (int j = 0; j < P; j++) o[j] = lds32(sx + j * 4); \
                        mbar_wait_h(br + 8, ph); \
                        _Pragma("unroll") for (int j = 0; j < (P + 1) / 2; j++) \
                            if (LO32) { if (!GEN && 2 * j + 2 < P) cpe<false>(he, de + j * 512, oe[j], ge0, 0, 0, pol); \
                                else if (2 * j + 1 < NPMAX || s < 2) cpe<true>(he, de + j * 512, oe[j], ge0, 4 * j + s, dv, pol); } \
                            else if (!GEN && 2 * j + 2 < P) cp16e(de + j * 512, ge, oe[j], pol); else if (2 * j + 1 < NPMAX || s < 2) cp16z<32>(de + j * 512, ge, oe[j], 4 * j + s, dv, pol); \
                        _Pragma("unroll") for (int j = 0; j < P - 1; j++) { \
                            if (LO32) { cpx<0, GEN>(hi, da + j * 1024, o[j], gx0, 2 * j, dv); cpx<1, GEN>(hi, db + j * 1024, o[j], gx0, 2 * j + 1, dv); } \
                            else if (GEN) { cp16z<128>(da + j * 1024, gx, o[j] & 0xFFFFu, 2 * j, dv, 0); cp16z<128>(db + j * 1024, gx, o[j] >> 16, 2 * j + 1, dv, 0); } \
                            else { cp16i<128>(da + j * 1024, gx, o[j] & 0xFFFFu); cp16i<128>(db + j * 1024, gx, o[j] >> 16); } } \
                        if (LO32) { cpx<0, true>(hi, da + (P - 1) * 1024, o[P - 1], gx0, 2 * P - 2, dv); cpx<1, true>(hi, db + (P - 1) * 1024, o[P - 1], gx0, 2 * P - 1, dv); } \
                        else { cp16z<128>(da + (P - 1) * 1024, gx, o[P - 1] & 0xFFFFu, 2 * P - 2, dv, 0); cp16z<128>(db + (P - 1) * 1024, gx, o[P - 1] >> 16, 2 * P - 1, dv, 0); } \
                    } break;
                    CASE(6, 6, false) CASE(7, 7, false) CASE(8, 8, false) CASE(9, 9, false) CASE(10, 10, false) CASE(11, 11, false)
                    CASE(15, NPMAX, true) CASE(14, 8, true) default: CASE(13, 5, true)
#undef CASE
                }
                first = 0;
                mbar_cp_arrive(br);
                done3();
                g = __reduce_min_sync(~0u, g);
                {
                    const uint2 e = lds64(pa + (nx == 0 ? g : nx) * 32);
                    const uint2 v = tile_info(e.y);
                    pw = e.x;
                    asm volatile("st.shared.v2.u32 [%0], {%1, %2};" :: "r"(br + 16 + r4 * 8), "r"(v.x), "r"((v.y & ~C_BRK) | brk) : "memory");
                    brk = v.y & C_BRK;
                }
                mbar_arrive(br);
                hist = (hist << 8) | (nx == 0 ? cur : 96u);
                cur = nx == 0 ? g : cur;
                ph ^= br != bars; br = brs - br; da = das - da; de = des - de;
            }
            if (first) asm volatile("bar.sync 3, 480;" ::: "memory");
            if (go) {
                mbar_wait(sb + SM_ABAR + 72, 0);
                const int g0 = 3 * max((ngroups + 2) / 3 - TR, 0) + w;
                uint32_t ra[TR], gb[TR]; uint4 xv[TR], xu[TR]; char* po[TR];
                const int gz = misc[4];
                #pragma unroll
                for (int k = 0; k < TR; k++) {
                    uint32_t nd;
                    asm volatile("ld.shared.u16 %0, [%1];" : "=r"(nd) : "r"(sb + SM_WL + (g0 + 3 * k) * 8 + r4 * 2) : "memory");
                    xv[k] = __ldg((const uint4*)(gx + (size_t)(node0 + (nd == NONE ? 0u : nd)) * 128));
                    const uint32_t ro = sb + nd * 128 + ((c8 ^ (nd & 7)) << 4);
                    xu[k] = lds128(ro + SM_XU);
                    const bool some = g0 + 3 * k < gz;
                    ra[k] = some ? ro + SM_TAB : sb + SM_MISC + 64;
                    gb[k] = some ? sb + SM_GBAR + (g0 + 3 * k) * 8 : sb + SM_ABAR + 72;
                    po[k] = nd != NONE ? (char*)out + (size_t)(node0 + nd) * 128 + c8 * 16 : nullptr;
                    asm volatile("" : "+r"(ra[k]), "+r"(gb[k]), "+l"(po[k]));
                }
                #pragma unroll 1
                for (int k = 0; k < 3; k++) {
                    mbar_wait(k < 2 ? br + 8 : sb + SM_ABAR + 48 + w * 8, k < 2 ? ph : 0);
                    done3(); hist <<= 8;
                    ph ^= br != bars; br = brs - br;
                }
                #pragma unroll
                for (int k = 0; k < TR; k++) {
                    mbar_wait_c(gb[k], 0);
                    uint4 a = lds128(ra[k]);
                    finish(a, xu[k], xv[k]);
                    if (po[k]) *(uint4*)po[k] = a;
                }
            }
            cp_wait<0>();
        } else {
            const char* gx = ga; const char* ob = gb;
            mbar_wait(sb + SM_ABAR + 72, 0);
            WS(15);
            if (b == 0 && lane == 0) asm volatile("red.relaxed.gpu.global.add.u32 [%0], 1;" :: "l"(gbar) : "memory");
            const int rounds = misc[1] ? 0 : max((ngroups + 2) / 3 - TR, 0);
            const int gz = misc[4], fast = __reduce_min_sync(~0u, min(rounds, gz / 3));
            uint32_t wl = sb + SM_WL + r4 * 2, gbar = sb + SM_GBAR;
            auto row_at = [&](uint32_t a) { uint32_t n; asm volatile("ld.shared.u16 %0, [%1];" : "=r"(n) : "r"(a) : "memory"); return n; };
            auto fetch = [&](uint32_t n, uint4& v) {
                asm volatile("{\n.reg .b64 p;\nmad.wide.u32 p, %5, 128, %4;\nld.global.nc.L1::no_allocate.v4.u32 {%0,%1,%2,%3}, [p];\n}"
                             : "=r"(v.x), "=r"(v.y), "=r"(v.z), "=r"(v.w) : "l"(gx), "r"(n));
            };
            auto store = [&](uint32_t n, const uint4& a) {
                asm volatile("{\n.reg .b64 p;\nmad.wide.u32 p, %1, 128, %0;\nst.global.v4.u32 [p], {%2,%3,%4,%5};\n}" :: "l"(ob), "r"(n), "r"(a.x), "r"(a.y), "r"(a.z), "r"(a.w) : "memory");
            };
            uint32_t n0[3]; uint4 x0[3];
            if (fast) {
                #pragma unroll
                for (int r = 0; r < 3; r++) { n0[r] = row_at(wl + r * 8); fetch(n0[r], x0[r]); }
            }
            #pragma unroll 1
            for (int k = 0; k < fast; k++) {
                wl += 24;
                #pragma unroll
                for (int r = 0; r < 3; r++) {
                    const uint32_t nd = n0[r], ro = sb + nd * 128 + ((c8 ^ (nd & 7)) << 4);
                    const uint4 xu = lds128(ro + SM_XU);
                    n0[r] = row_at(wl + r * 8);
                    mbar_wait(gbar + r * 8, 0);
                    uint4 a = lds128(ro + SM_TAB);
                    finish(a, xu, x0[r]);
                    fetch(n0[r], x0[r]);
                    store(nd, a);
                }
                gbar += 24;
            }
            #pragma unroll 1
            for (int g = 3 * fast; g < 3 * rounds; g++) {
                const uint32_t nd = row_at(sb + SM_WL + r4 * 2 + g * 8), ro = sb + nd * 128 + ((c8 ^ (nd & 7)) << 4);
                uint4 xv, a = make_uint4(0, 0, 0, 0);
                fetch(nd, xv);
                if (g < gz) { mbar_wait(sb + SM_GBAR + g * 8, 0); a = lds128(ro + SM_TAB); }
                finish(a, lds128(ro + SM_XU), xv);
                store(nd, a);
            }
        }
    } else {
        asm volatile("setmaxnreg.inc.sync.aligned.u32 152;");
        float4 lgh[2 * NPMAX];
        uint32_t wf[40], wn[16], wt[16];
        const uint32_t mo0 = sbase + SM_TAB + (8 * (lane >> 4) + (lane & 7)) * 128 + (((2 * w + ((lane >> 3) & 1)) ^ (lane & 7)) << 4);
        mbar_wait_c(sbase + SM_ABAR + 24, 0);
        {
            const uint32_t wo = sbase + SM_WR + (2 * t) * 128 + ((ch0 * 2) ^ (t * 32));
            #pragma unroll
            for (int ks = 0; ks < 9; ks++) {
                uint32_t wr[4];
                #pragma unroll
                for (int i = 0; i < 4; i++) wr[i] = lds32((wo ^ ((i & 1) * 16)) + (16 * ks + (i & 1) + 4 * (i & 2)) * 128);
                if (ks < 5) make_wfrag<true>(wf + 4 * ks, wr); else make_wfrag<false>(wf + 4 * ks, wr);
            }
            #pragma unroll
            for (int ks = 0; ks < 4; ks++) { ldsm4t(wn + 4 * ks, mo0 + (144 + 16 * ks) * 128); ldsm4t(wt + 4 * ks, mo0 + (208 + 16 * ks) * 128); }
            if (wg == 2) {
                const uint32_t a = sbase + SM_WC + (16 * w + q) * 32 + t * 4, sw = (q >> 2) << 4;
                sts32(a + sw, wf[16]); sts32(a + 256 + sw, wf[17]); sts32(a + (sw ^ 16), wf[18]); sts32(a + 256 + (sw ^ 16), wf[19]);
                asm volatile("fence.proxy.async.shared::cta;" ::: "memory");
            }
            #pragma unroll
            for (int i = 0; i < 36; i++) asm volatile("" : "+r"(wf[i]));
        }
        WS(9);
        constexpr int NU = 6;
        const uint32_t dm = ((NPB_MAX + lane) * 4 | (tag << 14)) * 0x10001u;
        const char* const g1 = gs + (tid >> 4) * (P1B + P2B) + 256 + b * (CE * 2) + (lane & 15) * 8;
        const bool last = 2 * warp + 24 * (NU - 1) < nb;
        uint2 r1[NU];
        #pragma unroll
        for (int i = 0; i < NU; i++) r1[i] = make_uint2(dm, (tid >> 4) + 24 * i < nb ? 0 : dm);
        uint32_t spins = 0;
        asm volatile("bar.sync 5, 512;" ::: "memory");
        while (true) {
            #pragma unroll
            for (int i = 0; i < NU; i++) ld_unit(r1[i], g1 + i * (24 * (P1B + P2B)), (r1[i].y ^ dm) & 0xC000);
            #pragma unroll
            for (int i = 0; i < 4; i++) sts128(mo0 + wg * 16384 + 8192 + i * 2048, make_uint4(wt[4*i], wt[4*i+1], wt[4*i+2], wt[4*i+3]));
            uint32_t bad = 0;
            #pragma unroll
            for (int i = 0; i < NU; i++) bad |= r1[i].y ^ dm;
            const bool more = __any_sync(~0u, bad & 0xC000);
            if (spins == 0) WS(2);
            if (!more) break;
            if (++spins > (1u << 22)) __trap();
        }
        WS(3);
        const uint32_t db = sbase + SM_DEG - (tag << 14);
        uint32_t rk[NU][4];
        #pragma unroll
        for (int i = 0; i < NU; i++) {
            #pragma unroll
            for (int k = 0; k < 4; k++) {
                asm("dp2a.lo.u32.u32 %0, %1, %2, %3;" : "=r"(rk[i][k]) : "r"(k < 2 ? r1[i].x : r1[i].y), "r"(k & 1 ? 0x100u : 1u), "r"(db));
                if (i < NU - 1 || last) asm volatile("red.shared.add.u32 [%0], 1;" :: "r"(rk[i][k]) : "memory");
            }
        }
        WS(10);
        asm volatile("bar.sync 7, 512;" ::: "memory");
        WS(11);
        {
            const uint32_t ev = (lds32(sbase + SM_DEG + tid * 4) + 1) & ~1u;
            uint32_t inc = ev, base = 0;
            #pragma unroll
            for (int o = 1; o < 32; o <<= 1) { const uint32_t y = __shfl_up_sync(~0u, inc, o); if (lane >= o) inc += y; }
            if (lane == 31) {
                asm volatile("atom.shared.add.u32 %0, [%1], %2;" : "=r"(base) : "r"(sbase + SM_MISC + 24), "r"(inc) : "memory");
                if (base + inc > SLOT_CAP) misc[1] = 1;
            }
            const uint32_t s0 = min(__shfl_sync(~0u, base, 31) + inc - ev, SLOT_CAP);
            sts32(sbase + SM_CNT + tid * 4, 4 * s0);
            asm volatile("st.shared.u16 [%0], %1;" :: "r"(sbase + SM_BASE + tid * 2), "r"(s0) : "memory");
        }
        asm volatile("bar.arrive 4, 512;" ::: "memory");
        asm volatile("bar.sync 1, 384;" ::: "memory");
        WS(13);
        #pragma unroll
        for (int i = 0; i < NU; i++) {
            if (i < NU - 1 || last) {
                #pragma unroll
                for (int k = 0; k < 4; k++) asm volatile("atom.shared.add.u32 %0, [%0+%1], 4;" : "+r"(rk[i][k]) : "n"(SM_CNT - SM_DEG) : "memory");
            }
        }
        WS(14);
        uint4 r2[NU];
        mbar_wait_c(sbase + SM_ABAR + 40, 0);
        WS(4);
        #pragma unroll
        for (int i = 0; i < NU; i++) r2[i] = lds128(sbase + SM_P2 + (i < NU - 1 ? tid + 384 * i : min(tid + 384 * i, P2B / 16 - 1)) * 16);
        while (true) {
            uint32_t bad = 0;
            #pragma unroll
            for (int i = 0; i < NU; i++) if (i < NU - 1 || last) bad |= (r2[i].x ^ (tag << 16)) & ~(rk[i][0] >> 14);
            if (__builtin_expect(!__any_sync(~0u, bad & 0x30000), 1)) break;
            #pragma unroll
            for (int i = 0; i < NU; i++)
                ld_unit(r2[i], g1 + (P1B + b * (CE * 2) + (lane & 15) * 8 + i * (24 * (P1B + P2B))), (i < NU - 1 || last) && ((r2[i].x ^ (tag << 16)) & ~(rk[i][0] >> 14) & 0x30000));
            if (++spins > (1u << 22)) __trap();
        }
        WS(16);
        const uint32_t sbu = __reduce_or_sync(~0u, sbase);
        auto place = [&](uint32_t s4, uint32_t v, uint32_t eb) {
            asm volatile("{\n.reg .pred p;\nsetp.lt.u32 p, %0, %5;\n@p st.shared.u32 [%1], %2;\n@p st.shared.u16 [%3], %4;\n}"
                         :: "r"(s4), "r"(sbu + SM_EID + s4), "r"(eb + (v >> 19)), "r"(sbu + SM_SRC + (s4 >> 1)), "r"(v), "n"(4 * SLOT_CAP) : "memory");
        };
        #pragma unroll
        for (int i = 0; i < NU; i++) {
            const uint32_t eb = ((tid >> 4) + 24 * i) * ch;
            if (i == 2 && warp == 10 && elect_one()) { x_ld(1); x_ld(0); }
            if (i < NU - 1 || last) { place(rk[i][0], r2[i].x, eb); place(rk[i][1], r2[i].y, eb); place(rk[i][2], r2[i].z, eb); place(rk[i][3], r2[i].w, eb); }
        }
        WS(1);
        WGD();
        asm volatile("bar.arrive 3, 480;" ::: "memory");
        {
        int lane;
        asm volatile("mov.u32 %0, %%laneid;" : "=r"(lane));
        const int q = lane >> 2, t = lane & 3, ch0 = 16 * w + 2 * q;
        const uint32_t sbase = sbu;
        { const uint2 z = lds64(sbase + SM_OH + 8); wf[37] = z.x; wf[38] = z.y; }
        const uint32_t c2 = __shfl_sync(~0u, ch0 * 2, lane), t8 = __shfl_sync(~0u, t * 8, lane);
        float g[4 * NPMAX], h[4 * NPMAX];
        float4 cyr = make_float4(0.f, 0.f, 0.f, 0.f);
        {
            const uint32_t mo = sbase + (8 * (lane >> 4) + (lane & 7)) * 128 + (((2 * w + ((lane >> 3) & 1)) ^ (lane & 7)) << 4);
            mbar_wait_c(sbase + SM_XBAR + wg * 8, 0);
            WSP(4);
            node_mma2(g, h, wn, desc_sw128(sbase + SM_XU + wg * 16384));
            TileMMA<8>::wait_g(g);
            node_rows(mo + SM_TAB + wg * 16384, g);
            TileMMA<8>::wait_h(h);
            WSP(5);
            #pragma unroll
            for (int i = 0; i < 4; i++) {
                const uint4 f = lds128(mo + SM_TAB + wg * 16384 + 8192 + i * 2048);
                wn[4*i] = f.x; wn[4*i+1] = f.y; wn[4*i+2] = f.z; wn[4*i+3] = f.w;
            }
            __syncwarp();
            node_rows(mo + SM_TAB + wg * 16384 + 8192, h);
            mbar_arrive(sbase + SM_XBAR + 24);
            WSP(2);
            node_mma2(g, h, wn, desc_sw128(sbase + SM_XU + wg * 16384));
            TileMMA<8>::wait_g(g);
            asm volatile("bar.sync %0, 128;" :: "r"(8 + wg) : "memory");
            node_rows(mo + SM_XU + wg * 16384, g);
            TileMMA<8>::wait_h(h);
            WSP(3);
            asm volatile("bar.sync %0, 128;" :: "r"(8 + wg) : "memory");
            node_rows(mo + SM_XU + wg * 16384 + 8192, h);
            mbar_arrive(sbase + SM_ABAR + 72);
            mbar_wait_c(sbase + SM_XBAR + 24, 0);
            if (__builtin_expect(lds32(sbase + SM_MISC + 4) != 0, 0)) { slow_bin(x, ea, src, dst, wa, wb, wc, wu, wv, out, E, node0, nn, 384); return; }
            WS(6);
        }
        const uint64_t wcd = __reduce_or_sync(~0u, (((sbase + SM_WC) & 0x3FFFF) >> 4) | (8u << 16)) | EDHI;
        const uint32_t bar0 = __reduce_or_sync(~0u, sbase + SM_BARS + wg * 96);
        const uint32_t xd0 = __reduce_or_sync(~0u, (((sbase + SM_XS + wg * NSTAGE * XS_BYTES) & 0x3FFFF) >> 4) | (1u << 16));
        const uint32_t ed0 = __reduce_or_sync(~0u, (((sbase + SM_ES + wg * NSTAGE * ES_BYTES) & 0x3FFFF) >> 4) | (8u << 16));
        const uint64_t ohd = __reduce_or_sync(~0u, (((sbase + SM_OH) & 0x3FFFF) >> 4) | (8u << 16));
        const uint32_t tabx = __reduce_or_sync(~0u, sbase + SM_TAB);
        const uint32_t bars = __reduce_or_sync(~0u, 2 * bar0 + 48), xds = __reduce_or_sync(~0u, 2 * xd0 + XS_BYTES / 16), eds = __reduce_or_sync(~0u, 2 * ed0 + ES_BYTES / 16);
        uint32_t bar = bar0, xd = xd0, ed = ed0, ph = 0, code, w1, ta, pta = NONE * 128 + c2;
        float pn0 = 0.f, pd0 = 1.f, pn1 = 0.f, pd1 = 1.f;
        uint2 ni = tile_info(lds32(sbase + SM_TINFO + wg * 32 + t * 8 + 4));
        auto fetch_a = [&]() {
            ta = (ni.x & 0xFFFFu) ^ c2;
            wf[36] = lds32(tabx + ta); wf[39] = lds32(tabx + ta);
            code = __reduce_or_sync(~0u, ni.y);
        };
        auto emit = [&]() { sts32(tabx + pta, pack_bf16(pn0 * rcpf(pd0), pn1 * rcpf(pd1))); };
        auto carry = [&]() {
            if (w1 & C_CONT) { pn0 += cyr.x; pd0 += cyr.y; pn1 += cyr.z; pd1 += cyr.w; }
            if (w1 & C_MORE) { cyr = make_float4(pn0, pd0 - EPS2, pn1, pd1 - EPS2); pn0 = pn1 = 0.f; pta = NONE * 128 + c2; }
        };
        auto next = [&](uint32_t fb) {
            pta = ta;
            w1 = ni.y;
            ni = lds64(fb + 16 + t8);
        };
        fetch_a();
        while (true) {
            switch (code & 15) {
                default: goto finished;
#define TILE(P) { \
                    float dmin; \
                    do { \
                        mbar_wait_c(bar, ph); \
                        TileMMA<P>::issue(g, h, wf, xd | (0x40000040ull << 32), ed | EDHI, ohd, wcd); \
                        const uint32_t eb = bar + 8; \
                        ph ^= bar != bar0; bar = bars - bar; xd = xds - xd; ed = eds - ed; \
                          \
                        asm volatile("{\n.reg .pred p;\nsetp.eq.u32 p, %0, 77;\n@p trap;\n}" :: "r"(xds) : "memory"); \
                        emit(); next(eb - 8); \
                        TileMMA<P>::wait_g(g); fetch_a(); TileMMA<P>::wait_h(h); \
                        mbar_arrive(eb); \
                        float m1; \
                        asm("set.gt.f32.f32 %0, %1, 0f0000007F;" : "=f"(m1) : "f"(__uint_as_float(w1))); \
                        epi_fast<P>(g, h, m1, __uint_as_float(w1), pn0, pd0, pn1, pd1, dmin); \
                    } while (!(__any_sync(~0u, dmin < TAU * 2 * P) | ((code & 31) != P))); \
                    if (__builtin_expect(__any_sync(~0u, (int)w1 < 0 || dmin < TAU * 2 * P), 0)) { \
                        int dv; \
                        if (unpad(w1, P, g[P > 1 ? 4 * P - 7 : 0], g[P > 1 ? 4 * P - 5 : 0], pd0, pd1, dv)) { \
                            FBT(2); \
                            epi_dump<P>(g, h, lgh); \
                            FBT(3); \
                            const float4 r = epi_exact(lgh, P, dv); \
                            pn0 = r.x; pd0 = r.y; pn1 = r.z; pd1 = r.w; \
                            if (pd0 != 77.f) FBT(4); \
                        } \
                    } \
                    if (code & C_BRK) { carry(); if (P != 11 && (code & 15) == P) goto L##P; } \
                    if (P == 11) {         \
                        const uint32_t a = tabx + (SM_WC - SM_TAB) + (c2 & 0x60) * 16 + (c2 & 0x1C) * 8 + (t8 >> 1), sw = c2 & 16; \
                        wf[16] = lds32(a + sw); wf[17] = lds32(a + 256 + sw); wf[18] = lds32(a + (sw ^ 16)); wf[19] = lds32(a + 256 + (sw ^ 16)); \
                    } }
#define CASE(P, UP, DN) case P: L##P: TILE(P) \
                    if (P > NPMIN && (code & 15) == P - 1) goto L##DN; \
                    if (P <= 6 && (code & 15) == 0) goto finished; \
                    if ((code & 15) == UP) goto L##UP; \
                    break;
                CASE(11, 11, 10) CASE(10, 11, 9) CASE(9, 10, 8) CASE(8, 9, 7) CASE(7, 8, 6) CASE(6, 7, 5) CASE(5, 6, 4) CASE(4, 5, 4)
#undef CASE
#undef TILE
            }
        }
finished:
        emit();
        mbar_arrive(sbase + SM_ABAR + 48 + wg * 8);
        }
    }
    WS(17); WG1();
}

}

extern "C" void kernel_launch(void* const* d_in, const int* in_sizes, int n_in, void* d_out, int out_size) {
    const __nv_bfloat16* x = (const __nv_bfloat16*)d_in[0];
    const __nv_bfloat16* ea = (const __nv_bfloat16*)d_in[1];
    const int* src = (const int*)d_in[2];
    const int* dst = (const int*)d_in[3];
    const __nv_bfloat16* wa = (const __nv_bfloat16*)d_in[4];
    const __nv_bfloat16* wb = (const __nv_bfloat16*)d_in[5];
    const __nv_bfloat16* wc = (const __nv_bfloat16*)d_in[6];
    const __nv_bfloat16* wu = (const __nv_bfloat16*)d_in[7];
    const __nv_bfloat16* wv = (const __nv_bfloat16*)d_in[8];
    __nv_bfloat16* out = (__nv_bfloat16*)d_out;
    int N = in_sizes[0] / 64, E = in_sizes[2];
    static int sms = 0;
    static CUtensorMap tm2;
    static bool tm_ok = false;
    typedef CUresult (*EncFn)(CUtensorMap*, CUtensorMapDataType, cuuint32_t, void*, const cuuint64_t*, const cuuint64_t*, const cuuint32_t*,
                              const cuuint32_t*, CUtensorMapInterleave, CUtensorMapSwizzle, CUtensorMapL2promotion, CUtensorMapFloatOOBfill);
    static void* fn = nullptr;
    static void* gp = nullptr; static void* gb = nullptr;
    if (!sms) {
        cudaDeviceGetAttribute(&sms, cudaDevAttrMultiProcessorCount, 0);
        cudaDriverEntryPointQueryResult qr;
        cudaGetDriverEntryPoint("cuTensorMapEncodeTiled", &fn, cudaEnableDefault, &qr);
        cudaGetSymbolAddress(&gp, g_str); cudaGetSymbolAddress(&gb, g_bar);
        if (fn && gp && gb) {
            const cuuint32_t rows = sms < NB_MAX ? sms : NB_MAX;
            cuuint64_t g2[2] = {(P1B + P2B) / 4, NB_MAX}, gs[1] = {P1B + P2B};
            cuuint32_t b2[2] = {CE, rows}, es[2] = {1, 1};
            tm_ok = ((EncFn)fn)(&tm2, CU_TENSOR_MAP_DATA_TYPE_UINT32, 2, gp, g2, gs, b2, es, CU_TENSOR_MAP_INTERLEAVE_NONE, CU_TENSOR_MAP_SWIZZLE_NONE,
                                CU_TENSOR_MAP_L2_PROMOTION_NONE, CU_TENSOR_MAP_FLOAT_OOB_FILL_NONE) == CUDA_SUCCESS;
        }
        cudaFuncSetAttribute(gcn_kernel<true>, cudaFuncAttributeMaxDynamicSharedMemorySize, SMEM_LAUNCH);
        cudaFuncSetAttribute(gcn_kernel<false>, cudaFuncAttributeMaxDynamicSharedMemorySize, SMEM_LAUNCH);
    }
    auto rows = [&](CUtensorMap* tm, const void* base, uint64_t n, uint32_t box) {
        cuuint64_t gd[2] = {64, n}, gs[1] = {128};
        cuuint32_t bx[2] = {64, box}, es[2] = {1, 1};
        return ((EncFn)fn)(tm, CU_TENSOR_MAP_DATA_TYPE_BFLOAT16, 2, (void*)base, gd, gs, bx, es, CU_TENSOR_MAP_INTERLEAVE_NONE, CU_TENSOR_MAP_SWIZZLE_128B,
                           CU_TENSOR_MAP_L2_PROMOTION_NONE, CU_TENSOR_MAP_FLOAT_OOB_FILL_NONE) == CUDA_SUCCESS;
    };
    const uintptr_t wp[4] = {(uintptr_t)wa, (uintptr_t)wb, (uintptr_t)wu, (uintptr_t)wv};
    uintptr_t w0 = wp[0], w1 = wp[0], wal = 0;
    for (int i = 1; i < 4; i++) { w0 = wp[i] < w0 ? wp[i] : w0; w1 = wp[i] > w1 ? wp[i] : w1; wal |= wp[i] - wp[0]; }
    int4 wrow = make_int4((int)((wp[0] - w0) >> 7), (int)((wp[1] - w0) >> 7), (int)((wp[2] - w0) >> 7), (int)((wp[3] - w0) >> 7));
    CUtensorMap tmw, tmc, tmx;
    const bool maps = tm_ok && N > 0 && !(wal & 127) && ((w1 - w0) >> 7) < (1u << 30) && rows(&tmw, (void*)w0, ((w1 - w0) >> 7) + 64, 64) && rows(&tmc, wc, 16, 16) && rows(&tmx, x, N, 128);
    int nb = sms < NB_MAX ? sms : NB_MAX;
    int npb = (N + nb - 1) / nb;
    int ch = (((E + nb - 1) / nb) + 3) & ~3;
    if (!maps || npb > NPB_MAX || ch > CH_MAX || (E & 3) || N > 65535 || npb < 2 || (((uintptr_t)src | (uintptr_t)dst | (uintptr_t)wa | (uintptr_t)wb | (uintptr_t)wc | (uintptr_t)wu | (uintptr_t)wv) & 15)) {
        int g = 1024, p = (N + g - 1) / g;
        slow_kernel<<<g, 256>>>(x, ea, src, dst, wa, wb, wc, wu, wv, out, N, E, p < 1 ? 1 : p);
        return;
    }
    uint32_t magic = (uint32_t)((1ull << 32) / (uint32_t)npb) + 1u;
    void* args[] = {&dst, &gb, &gp, &src, &E, &ch, &N, &npb, &magic, &x, &ea, &wa, &wb, &wc, &wu, &wv, &out, &wrow, &tm2, &tmw, &tmc, &tmx};
    const bool lo32 = ((uintptr_t)x >> 32) == (((uintptr_t)x + (size_t)N * 128 - 1) >> 32) && ((uintptr_t)ea >> 32) == (((uintptr_t)ea + (size_t)E * 32 - 1) >> 32);
    cudaLaunchCooperativeKernel(lo32 && !FORCE64 ? (const void*)gcn_kernel<true> : (const void*)gcn_kernel<false>, dim3(nb), dim3(THREADS), args, SMEM_LAUNCH, cudaStreamPerThread);
}
```

```cpp
#include <cuda_runtime.h>
#include <cuda.h>
#include <cuda_bf16.h>
#include <stdint.h>

namespace {

constexpr int N_MAX = 65536;
constexpr int NPMIN = 4;
constexpr int NPMAX = 11;
constexpr int THREADS = 512;
constexpr int EPT = 12;
constexpr int CH_MAX = THREADS * EPT;
constexpr int NB_MAX = 134;
constexpr int GAL = 128;
constexpr int CE = 64;
constexpr int P1B = (256 + NB_MAX * CE * 2 + GAL - 1) / GAL * GAL;
constexpr int P2B = (256 + NB_MAX * CE * 4 + GAL - 1) / GAL * GAL;
constexpr int NPB_MAX = 384;
constexpr int SLOT_CAP = 6784;
constexpr int TILE_CAP = 124;
constexpr int TILE_X = 8;
constexpr int NCLS = 64;
constexpr int XCAP = 128;
constexpr int NSTAGE = 2;
constexpr int TR = 2;
constexpr float LOG2E = 1.4426950408889634f;

__device__ __align__(128) uint4 g_str[NB_MAX * (P1B + P2B) / 16];
__device__ __align__(128) unsigned g_bar[32];
__device__ float g_slow[N_MAX * 128];

#define WS(k)
#define WGD()
#define ZS(k)
#define FBT(k)
#define WSP(k)
#define WSL(k)
#define WSG(k)
#define WG0()
#define WG1()
#define SMEM_LAUNCH SMEM_BYTES
#define FORCE64 0
#define EDHI ((16ull << 32) | (3ull << 62))
template<int NP> struct TileMMA;
template<> struct TileMMA<4> {
  static __device__ __forceinline__ void issue(float* g, float* h, const uint32_t* w, uint64_t dx, uint64_t de, uint64_t dh, uint64_t dc) {
    asm volatile(
      "{\n.reg .b64 dx1, dx2, dx3;\n"
      "add.s64 dx1, %72, 2;\nadd.s64 dx2, %72, 4;\nadd.s64 dx3, %72, 6;\n"
      "wgmma.fence.sync.aligned;\n"
      "wgmma.mma_async.sync.aligned.m64n32k16.f32.bf16.bf16 {%0, %1, %2, %3, %4, %5, %6, %7, %8, %9, %10, %11, %12, %13, %14, %15}, {%68, %69, %70, %71}, %74, 0, 1, 1, 0;\n"
      "wgmma.mma_async.sync.aligned.m64n32k16.f32.bf16.bf16 {%0, %1, %2, %3, %4, %5, %6, %7, %8, %9, %10, %11, %12, %13, %14, %15}, {%48, %49, %50, %51}, %73, 1, 1, 1, 0;\n"
      "wgmma.mma_async.sync.aligned.m64n32k16.f32.bf16.bf16 {%0, %1, %2, %3, %4, %5, %6, %7, %8, %9, %10, %11, %12, %13, %14, %15}, {%32, %33, %34, %35}, %72, 1, 1, 1, 0;\n"
      "wgmma.mma_async.sync.aligned.m64n32k16.f32.bf16.bf16 {%0, %1, %2, %3, %4, %5, %6, %7, %8, %9, %10, %11, %12, %13, %14, %15}, {%36, %37, %38, %39}, dx1, 1, 1, 1, 0;\n"
      "wgmma.mma_async.sync.aligned.m64n32k16.f32.bf16.bf16 {%0, %1, %2, %3, %4, %5, %6, %7, %8, %9, %10, %11, %12, %13, %14, %15}, {%40, %41, %42, %43}, dx2, 1, 1, 1, 0;\n"
      "wgmma.mma_async.sync.aligned.m64n32k16.f32.bf16.bf16 {%0, %1, %2, %3, %4, %5, %6, %7, %8, %9, %10, %11, %12, %13, %14, %15}, {%44, %45, %46, %47}, dx3, 1, 1, 1, 0;\n"
      "wgmma.commit_group.sync.aligned;\n"
      "wgmma.mma_async.sync.aligned.m64n32k16.f32.bf16.bf16 {%16, %17, %18, %19, %20, %21, %22, %23, %24, %25, %26, %27, %28, %29, %30, %31}, {%52, %53, %54, %55}, %72, 0, 1, 1, 0;\n"
      "wgmma.mma_async.sync.aligned.m64n32k16.f32.bf16.bf16 {%16, %17, %18, %19, %20, %21, %22, %23, %24, %25, %26, %27, %28, %29, %30, %31}, {%56, %57, %58, %59}, dx1, 1, 1, 1, 0;\n"
      "wgmma.mma_async.sync.aligned.m64n32k16.f32.bf16.bf16 {%16, %17, %18, %19, %20, %21, %22, %23, %24, %25, %26, %27, %28, %29, %30, %31}, {%60, %61, %62, %63}, dx2, 1, 1, 1, 0;\n"
      "wgmma.mma_async.sync.aligned.m64n32k16.f32.bf16.bf16 {%16, %17, %18, %19, %20, %21, %22, %23, %24, %25, %26, %27, %28, %29, %30, %31}, {%64, %65, %66, %67}, dx3, 1, 1, 1, 0;\n"
      "wgmma.commit_group.sync.aligned;\n}\n"
      : "=f"(g[0]), "=f"(g[1]), "=f"(g[2]), "=f"(g[3]), "=f"(g[4]), "=f"(g[5]), "=f"(g[6]), "=f"(g[7]), "=f"(g[8]), "=f"(g[9]), "=f"(g[10]), "=f"(g[11]), "=f"(g[12]), "=f"(g[13]), "=f"(g[14]), "=f"(g[15]),
        "=f"(h[0]), "=f"(h[1]), "=f"(h[2]), "=f"(h[3]), "=f"(h[4]), "=f"(h[5]), "=f"(h[6]), "=f"(h[7]), "=f"(h[8]), "=f"(h[9]), "=f"(h[10]), "=f"(h[11]), "=f"(h[12]), "=f"(h[13]), "=f"(h[14]), "=f"(h[15])
      : "r"(w[0]), "r"(w[1]), "r"(w[2]), "r"(w[3]), "r"(w[4]), "r"(w[5]), "r"(w[6]), "r"(w[7]), "r"(w[8]), "r"(w[9]), "r"(w[10]), "r"(w[11]), "r"(w[12]), "r"(w[13]), "r"(w[14]), "r"(w[15]), "r"(w[16]), "r"(w[17]), "r"(w[18]), "r"(w[19]), "r"(w[20]), "r"(w[21]), "r"(w[22]), "r"(w[23]), "r"(w[24]), "r"(w[25]), "r"(w[26]), "r"(w[27]), "r"(w[28]), "r"(w[29]), "r"(w[30]), "r"(w[31]), "r"(w[32]), "r"(w[33]), "r"(w[34]), "r"(w[35]), "r"(w[36]), "r"(w[37]), "r"(w[38]), "r"(w[39]), "l"(dx), "l"(de), "l"(dh)
      : "memory");
  }
  static __device__ __forceinline__ void wait_g(float* g) {
    asm volatile("wgmma.wait_group.sync.aligned 1;\n"
      : "+f"(g[0]), "+f"(g[1]), "+f"(g[2]), "+f"(g[3]), "+f"(g[4]), "+f"(g[5]), "+f"(g[6]), "+f"(g[7]), "+f"(g[8]), "+f"(g[9]), "+f"(g[10]), "+f"(g[11]), "+f"(g[12]), "+f"(g[13]), "+f"(g[14]), "+f"(g[15])
      :: "memory");
  }
  static __device__ __forceinline__ void wait_h(float* h) {
    asm volatile("wgmma.wait_group.sync.aligned 0;\n"
      : "+f"(h[0]), "+f"(h[1]), "+f"(h[2]), "+f"(h[3]), "+f"(h[4]), "+f"(h[5]), "+f"(h[6]), "+f"(h[7]), "+f"(h[8]), "+f"(h[9]), "+f"(h[10]), "+f"(h[11]), "+f"(h[12]), "+f"(h[13]), "+f"(h[14]), "+f"(h[15])
      :: "memory");
  }
};
template<> struct TileMMA<5> {
  static __device__ __forceinline__ void issue(float* g, float* h, const uint32_t* w, uint64_t dx, uint64_t de, uint64_t dh, uint64_t dc) {
    asm volatile(
      "{\n.reg .b64 dx1, dx2, dx3;\n"
      "add.s64 dx1, %80, 2;\nadd.s64 dx2, %80, 4;\nadd.s64 dx3, %80, 6;\n"
      "wgmma.fence.sync.aligned;\n"
      "wgmma.mma_async.sync.aligned.m64n40k16.f32.bf16.bf16 {%0, %1, %2, %3, %4, %5, %6, %7, %8, %9, %10, %11, %12, %13, %14, %15, %16, %17, %18, %19}, {%76, %77, %78, %79}, %82, 0, 1, 1, 0;\n"
      "wgmma.mma_async.sync.aligned.m64n40k16.f32.bf16.bf16 {%0, %1, %2, %3, %4, %5, %6, %7, %8, %9, %10, %11, %12, %13, %14, %15, %16, %17, %18, %19}, {%56, %57, %58, %59}, %81, 1, 1, 1, 0;\n"
      "wgmma.mma_async.sync.aligned.m64n40k16.f32.bf16.bf16 {%0, %1, %2, %3, %4, %5, %6, %7, %8, %9, %10, %11, %12, %13, %14, %15, %16, %17, %18, %19}, {%40, %41, %42, %43}, %80, 1, 1, 1, 0;\n"
      "wgmma.mma_async.sync.aligned.m64n40k16.f32.bf16.bf16 {%0, %1, %2, %3, %4, %5, %6, %7, %8, %9, %10, %11, %12, %13, %14, %15, %16, %17, %18, %19}, {%44, %45, %46, %47}, dx1, 1, 1, 1, 0;\n"
      "wgmma.mma_async.sync.aligned.m64n40k16.f32.bf16.bf16 {%0, %1, %2, %3, %4, %5, %6, %7, %8, %9, %10, %11, %12, %13, %14, %15, %16, %17, %18, %19}, {%48, %49, %50, %51}, dx2, 1, 1, 1, 0;\n"
      "wgmma.mma_async.sync.aligned.m64n40k16.f32.bf16.bf16 {%0, %1, %2, %3, %4, %5, %6, %7, %8, %9, %10, %11, %12, %13, %14, %15, %16, %17, %18, %19}, {%52, %53, %54, %55}, dx3, 1, 1, 1, 0;\n"
      "wgmma.commit_group.sync.aligned;\n"
      "wgmma.mma_async.sync.aligned.m64n40k16.f32.bf16.bf16 {%20, %21, %22, %23, %24, %25, %26, %27, %28, %29, %30, %31, %32, %33, %34, %35, %36, %37, %38, %39}, {%60, %61, %62, %63}, %80, 0, 1, 1, 0;\n"
      "wgmma.mma_async.sync.aligned.m64n40k16.f32.bf16.bf16 {%20, %21, %22, %23, %24, %25, %26, %27, %28, %29, %30, %31, %32, %33, %34, %35, %36, %37, %38, %39}, {%64, %65, %66, %67}, dx1, 1, 1, 1, 0;\n"
      "wgmma.mma_async.sync.aligned.m64n40k16.f32.bf16.bf16 {%20, %21, %22, %23, %24, %25, %26, %27, %28, %29, %30, %31, %32, %33, %34, %35, %36, %37, %38, %39}, {%68, %69, %70, %71}, dx2, 1, 1, 1, 0;\n"
      "wgmma.mma_async.sync.aligned.m64n40k16.f32.bf16.bf16 {%20, %21, %22, %23, %24, %25, %26, %27, %28, %29, %30, %31, %32, %33, %34, %35, %36, %37, %38, %39}, {%72, %73, %74, %75}, dx3, 1, 1, 1, 0;\n"
      "wgmma.commit_group.sync.aligned;\n}\n"
      : "=f"(g[0]), "=f"(g[1]), "=f"(g[2]), "=f"(g[3]), "=f"(g[4]), "=f"(g[5]), "=f"(g[6]), "=f"(g[7]), "=f"(g[8]), "=f"(g[9]), "=f"(g[10]), "=f"(g[11]), "=f"(g[12]), "=f"(g[13]), "=f"(g[14]), "=f"(g[15]), "=f"(g[16]), "=f"(g[17]), "=f"(g[18]), "=f"(g[19]),
        "=f"(h[0]), "=f"(h[1]), "=f"(h[2]), "=f"(h[3]), "=f"(h[4]), "=f"(h[5]), "=f"(h[6]), "=f"(h[7]), "=f"(h[8]), "=f"(h[9]), "=f"(h[10]), "=f"(h[11]), "=f"(h[12]), "=f"(h[13]), "=f"(h[14]), "=f"(h[15]), "=f"(h[16]), "=f"(h[17]), "=f"(h[18]), "=f"(h[19])
      : "r"(w[0]), "r"(w[1]), "r"(w[2]), "r"(w[3]), "r"(w[4]), "r"(w[5]), "r"(w[6]), "r"(w[7]), "r"(w[8]), "r"(w[9]), "r"(w[10]), "r"(w[11]), "r"(w[12]), "r"(w[13]), "r"(w[14]), "r"(w[15]), "r"(w[16]), "r"(w[17]), "r"(w[18]), "r"(w[19]), "r"(w[20]), "r"(w[21]), "r"(w[22]), "r"(w[23]), "r"(w[24]), "r"(w[25]), "r"(w[26]), "r"(w[27]), "r"(w[28]), "r"(w[29]), "r"(w[30]), "r"(w[31]), "r"(w[32]), "r"(w[33]), "r"(w[34]), "r"(w[35]), "r"(w[36]), "r"(w[37]), "r"(w[38]), "r"(w[39]), "l"(dx), "l"(de), "l"(dh)
      : "memory");
  }
  static __device__ __forceinline__ void wait_g(float* g) {
    asm volatile("wgmma.wait_group.sync.aligned 1;\n"
      : "+f"(g[0]), "+f"(g[1]), "+f"(g[2]), "+f"(g[3]), "+f"(g[4]), "+f"(g[5]), "+f"(g[6]), "+f"(g[7]), "+f"(g[8]), "+f"(g[9]), "+f"(g[10]), "+f"(g[11]), "+f"(g[12]), "+f"(g[13]), "+f"(g[14]), "+f"(g[15]), "+f"(g[16]), "+f"(g[17]), "+f"(g[18]), "+f"(g[19])
      :: "memory");
  }
  static __device__ __forceinline__ void wait_h(float* h) {
    asm volatile("wgmma.wait_group.sync.aligned 0;\n"
      : "+f"(h[0]), "+f"(h[1]), "+f"(h[2]), "+f"(h[3]), "+f"(h[4]), "+f"(h[5]), "+f"(h[6]), "+f"(h[7]), "+f"(h[8]), "+f"(h[9]), "+f"(h[10]), "+f"(h[11]), "+f"(h[12]), "+f"(h[13]), "+f"(h[14]), "+f"(h[15]), "+f"(h[16]), "+f"(h[17]), "+f"(h[18]), "+f"(h[19])
      :: "memory");
  }
};
template<> struct TileMMA<6> {
  static __device__ __forceinline__ void issue(float* g, float* h, const uint32_t* w, uint64_t dx, uint64_t de, uint64_t dh, uint64_t dc) {
    asm volatile(
      "{\n.reg .b64 dx1, dx2, dx3;\n"
      "add.s64 dx1, %88, 2;\nadd.s64 dx2, %88, 4;\nadd.s64 dx3, %88, 6;\n"
      "wgmma.fence.sync.aligned;\n"
      "wgmma.mma_async.sync.aligned.m64n48k16.f32.bf16.bf16 {%0, %1, %2, %3, %4, %5, %6, %7, %8, %9, %10, %11, %12, %13, %14, %15, %16, %17, %18, %19, %20, %21, %22, %23}, {%84, %85, %86, %87}, %90, 0, 1, 1, 0;\n"
      "wgmma.mma_async.sync.aligned.m64n48k16.f32.bf16.bf16 {%0, %1, %2, %3, %4, %5, %6, %7, %8, %9, %10, %11, %12, %13, %14, %15, %16, %17, %18, %19, %20, %21, %22, %23}, {%64, %65, %66, %67}, %89, 1, 1, 1, 0;\n"
      "wgmma.mma_async.sync.aligned.m64n48k16.f32.bf16.bf16 {%0, %1, %2, %3, %4, %5, %6, %7, %8, %9, %10, %11, %12, %13, %14, %15, %16, %17, %18, %19, %20, %21, %22, %23}, {%48, %49, %50, %51}, %88, 1, 1, 1, 0;\n"
      "wgmma.mma_async.sync.aligned.m64n48k16.f32.bf16.bf16 {%0, %1, %2, %3, %4, %5, %6, %7, %8, %9, %10, %11, %12, %13, %14, %15, %16, %17, %18, %19, %20, %21, %22, %23}, {%52, %53, %54, %55}, dx1, 1, 1, 1, 0;\n"
      "wgmma.mma_async.sync.aligned.m64n48k16.f32.bf16.bf16 {%0, %1, %2, %3, %4, %5, %6, %7, %8, %9, %10, %11, %12, %13, %14, %15, %16, %17, %18, %19, %20, %21, %22, %23}, {%56, %57, %58, %59}, dx2, 1, 1, 1, 0;\n"
      "wgmma.mma_async.sync.aligned.m64n48k16.f32.bf16.bf16 {%0, %1, %2, %3, %4, %5, %6, %7, %8, %9, %10, %11, %12, %13, %14, %15, %16, %17, %18, %19, %20, %21, %22, %23}, {%60, %61, %62, %63}, dx3, 1, 1, 1, 0;\n"
      "wgmma.commit_group.sync.aligned;\n"
      "wgmma.mma_async.sync.aligned.m64n48k16.f32.bf16.bf16 {%24, %25, %26, %27, %28, %29, %30, %31, %32, %33, %34, %35, %36, %37, %38, %39, %40, %41, %42, %43, %44, %45, %46, %47}, {%68, %69, %70, %71}, %88, 0, 1, 1, 0;\n"
      "wgmma.mma_async.sync.aligned.m64n48k16.f32.bf16.bf16 {%24, %25, %26, %27, %28, %29, %30, %31, %32, %33, %34, %35, %36, %37, %38, %39, %40, %41, %42, %43, %44, %45, %46, %47}, {%72, %73, %74, %75}, dx1, 1, 1, 1, 0;\n"
      "wgmma.mma_async.sync.aligned.m64n48k16.f32.bf16.bf16 {%24, %25, %26, %27, %28, %29, %30, %31, %32, %33, %34, %35, %36, %37, %38, %39, %40, %41, %42, %43, %44, %45, %46, %47}, {%76, %77, %78, %79}, dx2, 1, 1, 1, 0;\n"
      "wgmma.mma_async.sync.aligned.m64n48k16.f32.bf16.bf16 {%24, %25, %26, %27, %28, %29, %30, %31, %32, %33, %34, %35, %36, %37, %38, %39, %40, %41, %42, %43, %44, %45, %46, %47}, {%80, %81, %82, %83}, dx3, 1, 1, 1, 0;\n"
      "wgmma.commit_group.sync.aligned;\n}\n"
      : "=f"(g[0]), "=f"(g[1]), "=f"(g[2]), "=f"(g[3]), "=f"(g[4]), "=f"(g[5]), "=f"(g[6]), "=f"(g[7]), "=f"(g[8]), "=f"(g[9]), "=f"(g[10]), "=f"(g[11]), "=f"(g[12]), "=f"(g[13]), "=f"(g[14]), "=f"(g[15]), "=f"(g[16]), "=f"(g[17]), "=f"(g[18]), "=f"(g[19]), "=f"(g[20]), "=f"(g[21]), "=f"(g[22]), "=f"(g[23]),
        "=f"(h[0]), "=f"(h[1]), "=f"(h[2]), "=f"(h[3]), "=f"(h[4]), "=f"(h[5]), "=f"(h[6]), "=f"(h[7]), "=f"(h[8]), "=f"(h[9]), "=f"(h[10]), "=f"(h[11]), "=f"(h[12]), "=f"(h[13]), "=f"(h[14]), "=f"(h[15]), "=f"(h[16]), "=f"(h[17]), "=f"(h[18]), "=f"(h[19]), "=f"(h[20]), "=f"(h[21]), "=f"(h[22]), "=f"(h[23])
      : "r"(w[0]), "r"(w[1]), "r"(w[2]), "r"(w[3]), "r"(w[4]), "r"(w[5]), "r"(w[6]), "r"(w[7]), "r"(w[8]), "r"(w[9]), "r"(w[10]), "r"(w[11]), "r"(w[12]), "r"(w[13]), "r"(w[14]), "r"(w[15]), "r"(w[16]), "r"(w[17]), "r"(w[18]), "r"(w[19]), "r"(w[20]), "r"(w[21]), "r"(w[22]), "r"(w[23]), "r"(w[24]), "r"(w[25]), "r"(w[26]), "r"(w[27]), "r"(w[28]), "r"(w[29]), "r"(w[30]), "r"(w[31]), "r"(w[32]), "r"(w[33]), "r"(w[34]), "r"(w[35]), "r"(w[36]), "r"(w[37]), "r"(w[38]), "r"(w[39]), "l"(dx), "l"(de), "l"(dh)
      : "memory");
  }
  static __device__ __forceinline__ void wait_g(float* g) {
    asm volatile("wgmma.wait_group.sync.aligned 1;\n"
      : "+f"(g[0]), "+f"(g[1]), "+f"(g[2]), "+f"(g[3]), "+f"(g[4]), "+f"(g[5]), "+f"(g[6]), "+f"(g[7]), "+f"(g[8]), "+f"(g[9]), "+f"(g[10]), "+f"(g[11]), "+f"(g[12]), "+f"(g[13]), "+f"(g[14]), "+f"(g[15]), "+f"(g[16]), "+f"(g[17]), "+f"(g[18]), "+f"(g[19]), "+f"(g[20]), "+f"(g[21]), "+f"(g[22]), "+f"(g[23])
      :: "memory");
  }
  static __device__ __forceinline__ void wait_h(float* h) {
    asm volatile("wgmma.wait_group.sync.aligned 0;\n"
      : "+f"(h[0]), "+f"(h[1]), "+f"(h[2]), "+f"(h[3]), "+f"(h[4]), "+f"(h[5]), "+f"(h[6]), "+f"(h[7]), "+f"(h[8]), "+f"(h[9]), "+f"(h[10]), "+f"(h[11]), "+f"(h[12]), "+f"(h[13]), "+f"(h[14]), "+f"(h[15]), "+f"(h[16]), "+f"(h[17]), "+f"(h[18]), "+f"(h[19]), "+f"(h[20]), "+f"(h[21]), "+f"(h[22]), "+f"(h[23])
      :: "memory");
  }
};
template<> struct TileMMA<7> {
  static __device__ __forceinline__ void issue(float* g, float* h, const uint32_t* w, uint64_t dx, uint64_t de, uint64_t dh, uint64_t dc) {
    asm volatile(
      "{\n.reg .b64 dx1, dx2, dx3;\n"
      "add.s64 dx1, %96, 2;\nadd.s64 dx2, %96, 4;\nadd.s64 dx3, %96, 6;\n"
      "wgmma.fence.sync.aligned;\n"
      "wgmma.mma_async.sync.aligned.m64n56k16.f32.bf16.bf16 {%0, %1, %2, %3, %4, %5, %6, %7, %8, %9, %10, %11, %12, %13, %14, %15, %16, %17, %18, %19, %20, %21, %22, %23, %24, %25, %26, %27}, {%92, %93, %94, %95}, %98, 0, 1, 1, 0;\n"
      "wgmma.mma_async.sync.aligned.m64n56k16.f32.bf16.bf16 {%0, %1, %2, %3, %4, %5, %6, %7, %8, %9, %10, %11, %12, %13, %14, %15, %16, %17, %18, %19, %20, %21, %22, %23, %24, %25, %26, %27}, {%72, %73, %74, %75}, %97, 1, 1, 1, 0;\n"
      "wgmma.mma_async.sync.aligned.m64n56k16.f32.bf16.bf16 {%0, %1, %2, %3, %4, %5, %6, %7, %8, %9, %10, %11, %12, %13, %14, %15, %16, %17, %18, %19, %20, %21, %22, %23, %24, %25, %26, %27}, {%56, %57, %58, %59}, %96, 1, 1, 1, 0;\n"
      "wgmma.mma_async.sync.aligned.m64n56k16.f32.bf16.bf16 {%0, %1, %2, %3, %4, %5, %6, %7, %8, %9, %10, %11, %12, %13, %14, %15, %16, %17, %18, %19, %20, %21, %22, %23, %24, %25, %26, %27}, {%60, %61, %62, %63}, dx1, 1, 1, 1, 0;\n"
      "wgmma.mma_async.sync.aligned.m64n56k16.f32.bf16.bf16 {%0, %1, %2, %3, %4, %5, %6, %7, %8, %9, %10, %11, %12, %13, %14, %15, %16, %17, %18, %19, %20, %21, %22, %23, %24, %25, %26, %27}, {%64, %65, %66, %67}, dx2, 1, 1, 1, 0;\n"
      "wgmma.mma_async.sync.aligned.m64n56k16.f32.bf16.bf16 {%0, %1, %2, %3, %4, %5, %6, %7, %8, %9, %10, %11, %12, %13, %14, %15, %16, %17, %18, %19, %20, %21, %22, %23, %24, %25, %26, %27}, {%68, %69, %70, %71}, dx3, 1, 1, 1, 0;\n"
      "wgmma.commit_group.sync.aligned;\n"
      "wgmma.mma_async.sync.aligned.m64n56k16.f32.bf16.bf16 {%28, %29, %30, %31, %32, %33, %34, %35, %36, %37, %38, %39, %40, %41, %42, %43, %44, %45, %46, %47, %48, %49, %50, %51, %52, %53, %54, %55}, {%76, %77, %78, %79}, %96, 0, 1, 1, 0;\n"
      "wgmma.mma_async.sync.aligned.m64n56k16.f32.bf16.bf16 {%28, %29, %30, %31, %32, %33, %34, %35, %36, %37, %38, %39, %40, %41, %42, %43, %44, %45, %46, %47, %48, %49, %50, %51, %52, %53, %54, %55}, {%80, %81, %82, %83}, dx1, 1, 1, 1, 0;\n"
      "wgmma.mma_async.sync.aligned.m64n56k16.f32.bf16.bf16 {%28, %29, %30, %31, %32, %33, %34, %35, %36, %37, %38, %39, %40, %41, %42, %43, %44, %45, %46, %47, %48, %49, %50, %51, %52, %53, %54, %55}, {%84, %85, %86, %87}, dx2, 1, 1, 1, 0;\n"
      "wgmma.mma_async.sync.aligned.m64n56k16.f32.bf16.bf16 {%28, %29, %30, %31, %32, %33, %34, %35, %36, %37, %38, %39, %40, %41, %42, %43, %44, %45, %46, %47, %48, %49, %50, %51, %52, %53, %54, %55}, {%88, %89, %90, %91}, dx3, 1, 1, 1, 0;\n"
      "wgmma.commit_group.sync.aligned;\n}\n"
      : "=f"(g[0]), "=f"(g[1]), "=f"(g[2]), "=f"(g[3]), "=f"(g[4]), "=f"(g[5]), "=f"(g[6]), "=f"(g[7]), "=f"(g[8]), "=f"(g[9]), "=f"(g[10]), "=f"(g[11]), "=f"(g[12]), "=f"(g[13]), "=f"(g[14]), "=f"(g[15]), "=f"(g[16]), "=f"(g[17]), "=f"(g[18]), "=f"(g[19]), "=f"(g[20]), "=f"(g[21]), "=f"(g[22]), "=f"(g[23]), "=f"(g[24]), "=f"(g[25]), "=f"(g[26]), "=f"(g[27]),
        "=f"(h[0]), "=f"(h[1]), "=f"(h[2]), "=f"(h[3]), "=f"(h[4]), "=f"(h[5]), "=f"(h[6]), "=f"(h[7]), "=f"(h[8]), "=f"(h[9]), "=f"(h[10]), "=f"(h[11]), "=f"(h[12]), "=f"(h[13]), "=f"(h[14]), "=f"(h[15]), "=f"(h[16]), "=f"(h[17]), "=f"(h[18]), "=f"(h[19]), "=f"(h[20]), "=f"(h[21]), "=f"(h[22]), "=f"(h[23]), "=f"(h[24]), "=f"(h[25]), "=f"(h[26]), "=f"(h[27])
      : "r"(w[0]), "r"(w[1]), "r"(w[2]), "r"(w[3]), "r"(w[4]), "r"(w[5]), "r"(w[6]), "r"(w[7]), "r"(w[8]), "r"(w[9]), "r"(w[10]), "r"(w[11]), "r"(w[12]), "r"(w[13]), "r"(w[14]), "r"(w[15]), "r"(w[16]), "r"(w[17]), "r"(w[18]), "r"(w[19]), "r"(w[20]), "r"(w[21]), "r"(w[22]), "r"(w[23]), "r"(w[24]), "r"(w[25]), "r"(w[26]), "r"(w[27]), "r"(w[28]), "r"(w[29]), "r"(w[30]), "r"(w[31]), "r"(w[32]), "r"(w[33]), "r"(w[34]), "r"(w[35]), "r"(w[36]), "r"(w[37]), "r"(w[38]), "r"(w[39]), "l"(dx), "l"(de), "l"(dh)
      : "memory");
  }
  static __device__ __forceinline__ void wait_g(float* g) {
    asm volatile("wgmma.wait_group.sync.aligned 1;\n"
      : "+f"(g[0]), "+f"(g[1]), "+f"(g[2]), "+f"(g[3]), "+f"(g[4]), "+f"(g[5]), "+f"(g[6]), "+f"(g[7]), "+f"(g[8]), "+f"(g[9]), "+f"(g[10]), "+f"(g[11]), "+f"(g[12]), "+f"(g[13]), "+f"(g[14]), "+f"(g[15]), "+f"(g[16]), "+f"(g[17]), "+f"(g[18]), "+f"(g[19]), "+f"(g[20]), "+f"(g[21]), "+f"(g[22]), "+f"(g[23]), "+f"(g[24]), "+f"(g[25]), "+f"(g[26]), "+f"(g[27])
      :: "memory");
  }
  static __device__ __forceinline__ void wait_h(float* h) {
    asm volatile("wgmma.wait_group.sync.aligned 0;\n"
      : "+f"(h[0]), "+f"(h[1]), "+f"(h[2]), "+f"(h[3]), "+f"(h[4]), "+f"(h[5]), "+f"(h[6]), "+f"(h[7]), "+f"(h[8]), "+f"(h[9]), "+f"(h[10]), "+f"(h[11]), "+f"(h[12]), "+f"(h[13]), "+f"(h[14]), "+f"(h[15]), "+f"(h[16]), "+f"(h[17]), "+f"(h[18]), "+f"(h[19]), "+f"(h[20]), "+f"(h[21]), "+f"(h[22]), "+f"(h[23]), "+f"(h[24]), "+f"(h[25]), "+f"(h[26]), "+f"(h[27])
      :: "memory");
  }
};
template<> struct TileMMA<8> {
  static __device__ __forceinline__ void issue(float* g, float* h, const uint32_t* w, uint64_t dx, uint64_t de, uint64_t dh, uint64_t dc) {
    asm volatile(
      "{\n.reg .b64 dx1, dx2, dx3;\n"
      "add.s64 dx1, %104, 2;\nadd.s64 dx2, %104, 4;\nadd.s64 dx3, %104, 6;\n"
      "wgmma.fence.sync.aligned;\n"
      "wgmma.mma_async.sync.aligned.m64n64k16.f32.bf16.bf16 {%0, %1, %2, %3, %4, %5, %6, %7, %8, %9, %10, %11, %12, %13, %14, %15, %16, %17, %18, %19, %20, %21, %22, %23, %24, %25, %26, %27, %28, %29, %30, %31}, {%100, %101, %102, %103}, %106, 0, 1, 1, 0;\n"
      "wgmma.mma_async.sync.aligned.m64n64k16.f32.bf16.bf16 {%0, %1, %2, %3, %4, %5, %6, %7, %8, %9, %10, %11, %12, %13, %14, %15, %16, %17, %18, %19, %20, %21, %22, %23, %24, %25, %26, %27, %28, %29, %30, %31}, {%80, %81, %82, %83}, %105, 1, 1, 1, 0;\n"
      "wgmma.mma_async.sync.aligned.m64n64k16.f32.bf16.bf16 {%0, %1, %2, %3, %4, %5, %6, %7, %8, %9, %10, %11, %12, %13, %14, %15, %16, %17, %18, %19, %20, %21, %22, %23, %24, %25, %26, %27, %28, %29, %30, %31}, {%64, %65, %66, %67}, %104, 1, 1, 1, 0;\n"
      "wgmma.mma_async.sync.aligned.m64n64k16.f32.bf16.bf16 {%0, %1, %2, %3, %4, %5, %6, %7, %8, %9, %10, %11, %12, %13, %14, %15, %16, %17, %18, %19, %20, %21, %22, %23, %24, %25, %26, %27, %28, %29, %30, %31}, {%68, %69, %70, %71}, dx1, 1, 1, 1, 0;\n"
      "wgmma.mma_async.sync.aligned.m64n64k16.f32.bf16.bf16 {%0, %1, %2, %3, %4, %5, %6, %7, %8, %9, %10, %11, %12, %13, %14, %15, %16, %17, %18, %19, %20, %21, %22, %23, %24, %25, %26, %27, %28, %29, %30, %31}, {%72, %73, %74, %75}, dx2, 1, 1, 1, 0;\n"
      "wgmma.mma_async.sync.aligned.m64n64k16.f32.bf16.bf16 {%0, %1, %2, %3, %4, %5, %6, %7, %8, %9, %10, %11, %12, %13, %14, %15, %16, %17, %18, %19, %20, %21, %22, %23, %24, %25, %26, %27, %28, %29, %30, %31}, {%76, %77, %78, %79}, dx3, 1, 1, 1, 0;\n"
      "wgmma.commit_group.sync.aligned;\n"
      "wgmma.mma_async.sync.aligned.m64n64k16.f32.bf16.bf16 {%32, %33, %34, %35, %36, %37, %38, %39, %40, %41, %42, %43, %44, %45, %46, %47, %48, %49, %50, %51, %52, %53, %54, %55, %56, %57, %58, %59, %60, %61, %62, %63}, {%84, %85, %86, %87}, %104, 0, 1, 1, 0;\n"
      "wgmma.mma_async.sync.aligned.m64n64k16.f32.bf16.bf16 {%32, %33, %34, %35, %36, %37, %38, %39, %40, %41, %42, %43, %44, %45, %46, %47, %48, %49, %50, %51, %52, %53, %54, %55, %56, %57, %58, %59, %60, %61, %62, %63}, {%88, %89, %90, %91}, dx1, 1, 1, 1, 0;\n"
      "wgmma.mma_async.sync.aligned.m64n64k16.f32.bf16.bf16 {%32, %33, %34, %35, %36, %37, %38, %39, %40, %41, %42, %43, %44, %45, %46, %47, %48, %49, %50, %51, %52, %53, %54, %55, %56, %57, %58, %59, %60, %61, %62, %63}, {%92, %93, %94, %95}, dx2, 1, 1, 1, 0;\n"
      "wgmma.mma_async.sync.aligned.m64n64k16.f32.bf16.bf16 {%32, %33, %34, %35, %36, %37, %38, %39, %40, %41, %42, %43, %44, %45, %46, %47, %48, %49, %50, %51, %52, %53, %54, %55, %56, %57, %58, %59, %60, %61, %62, %63}, {%96, %97, %98, %99}, dx3, 1, 1, 1, 0;\n"
      "wgmma.commit_group.sync.aligned;\n}\n"
      : "=f"(g[0]), "=f"(g[1]), "=f"(g[2]), "=f"(g[3]), "=f"(g[4]), "=f"(g[5]), "=f"(g[6]), "=f"(g[7]), "=f"(g[8]), "=f"(g[9]), "=f"(g[10]), "=f"(g[11]), "=f"(g[12]), "=f"(g[13]), "=f"(g[14]), "=f"(g[15]), "=f"(g[16]), "=f"(g[17]), "=f"(g[18]), "=f"(g[19]), "=f"(g[20]), "=f"(g[21]), "=f"(g[22]), "=f"(g[23]), "=f"(g[24]), "=f"(g[25]), "=f"(g[26]), "=f"(g[27]), "=f"(g[28]), "=f"(g[29]), "=f"(g[30]), "=f"(g[31]),
        "=f"(h[0]), "=f"(h[1]), "=f"(h[2]), "=f"(h[3]), "=f"(h[4]), "=f"(h[5]), "=f"(h[6]), "=f"(h[7]), "=f"(h[8]), "=f"(h[9]), "=f"(h[10]), "=f"(h[11]), "=f"(h[12]), "=f"(h[13]), "=f"(h[14]), "=f"(h[15]), "=f"(h[16]), "=f"(h[17]), "=f"(h[18]), "=f"(h[19]), "=f"(h[20]), "=f"(h[21]), "=f"(h[22]), "=f"(h[23]), "=f"(h[24]), "=f"(h[25]), "=f"(h[26]), "=f"(h[27]), "=f"(h[28]), "=f"(h[29]), "=f"(h[30]), "=f"(h[31])
      : "r"(w[0]), "r"(w[1]), "r"(w[2]), "r"(w[3]), "r"(w[4]), "r"(w[5]), "r"(w[6]), "r"(w[7]), "r"(w[8]), "r"(w[9]), "r"(w[10]), "r"(w[11]), "r"(w[12]), "r"(w[13]), "r"(w[14]), "r"(w[15]), "r"(w[16]), "r"(w[17]), "r"(w[18]), "r"(w[19]), "r"(w[20]), "r"(w[21]), "r"(w[22]), "r"(w[23]), "r"(w[24]), "r"(w[25]), "r"(w[26]), "r"(w[27]), "r"(w[28]), "r"(w[29]), "r"(w[30]), "r"(w[31]), "r"(w[32]), "r"(w[33]), "r"(w[34]), "r"(w[35]), "r"(w[36]), "r"(w[37]), "r"(w[38]), "r"(w[39]), "l"(dx), "l"(de), "l"(dh)
      : "memory");
  }
  static __device__ __forceinline__ void wait_g(float* g) {
    asm volatile("wgmma.wait_group.sync.aligned 1;\n"
      : "+f"(g[0]), "+f"(g[1]), "+f"(g[2]), "+f"(g[3]), "+f"(g[4]), "+f"(g[5]), "+f"(g[6]), "+f"(g[7]), "+f"(g[8]), "+f"(g[9]), "+f"(g[10]), "+f"(g[11]), "+f"(g[12]), "+f"(g[13]), "+f"(g[14]), "+f"(g[15]), "+f"(g[16]), "+f"(g[17]), "+f"(g[18]), "+f"(g[19]), "+f"(g[20]), "+f"(g[21]), "+f"(g[22]), "+f"(g[23]), "+f"(g[24]), "+f"(g[25]), "+f"(g[26]), "+f"(g[27]), "+f"(g[28]), "+f"(g[29]), "+f"(g[30]), "+f"(g[31])
      :: "memory");
  }
  static __device__ __forceinline__ void wait_h(float* h) {
    asm volatile("wgmma.wait_group.sync.aligned 0;\n"
      : "+f"(h[0]), "+f"(h[1]), "+f"(h[2]), "+f"(h[3]), "+f"(h[4]), "+f"(h[5]), "+f"(h[6]), "+f"(h[7]), "+f"(h[8]), "+f"(h[9]), "+f"(h[10]), "+f"(h[11]), "+f"(h[12]), "+f"(h[13]), "+f"(h[14]), "+f"(h[15]), "+f"(h[16]), "+f"(h[17]), "+f"(h[18]), "+f"(h[19]), "+f"(h[20]), "+f"(h[21]), "+f"(h[22]), "+f"(h[23]), "+f"(h[24]), "+f"(h[25]), "+f"(h[26]), "+f"(h[27]), "+f"(h[28]), "+f"(h[29]), "+f"(h[30]), "+f"(h[31])
      :: "memory");
  }
};
template<> struct TileMMA<9> {
  static __device__ __forceinline__ void issue(float* g, float* h, const uint32_t* w, uint64_t dx, uint64_t de, uint64_t dh, uint64_t dc) {
    asm volatile(
      "{\n.reg .b64 dx1, dx2, dx3;\n"
      "add.s64 dx1, %112, 2;\nadd.s64 dx2, %112, 4;\nadd.s64 dx3, %112, 6;\n"
      "wgmma.fence.sync.aligned;\n"
      "wgmma.mma_async.sync.aligned.m64n72k16.f32.bf16.bf16 {%0, %1, %2, %3, %4, %5, %6, %7, %8, %9, %10, %11, %12, %13, %14, %15, %16, %17, %18, %19, %20, %21, %22, %23, %24, %25, %26, %27, %28, %29, %30, %31, %32, %33, %34, %35}, {%108, %109, %110, %111}, %114, 0, 1, 1, 0;\n"
      "wgmma.mma_async.sync.aligned.m64n72k16.f32.bf16.bf16 {%0, %1, %2, %3, %4, %5, %6, %7, %8, %9, %10, %11, %12, %13, %14, %15, %16, %17, %18, %19, %20, %21, %22, %23, %24, %25, %26, %27, %28, %29, %30, %31, %32, %33, %34, %35}, {%88, %89, %90, %91}, %113, 1, 1, 1, 0;\n"
      "wgmma.mma_async.sync.aligned.m64n72k16.f32.bf16.bf16 {%0, %1, %2, %3, %4, %5, %6, %7, %8, %9, %10, %11, %12, %13, %14, %15, %16, %17, %18, %19, %20, %21, %22, %23, %24, %25, %26, %27, %28, %29, %30, %31, %32, %33, %34, %35}, {%72, %73, %74, %75}, %112, 1, 1, 1, 0;\n"
      "wgmma.mma_async.sync.aligned.m64n72k16.f32.bf16.bf16 {%0, %1, %2, %3, %4, %5, %6, %7, %8, %9, %10, %11, %12, %13, %14, %15, %16, %17, %18, %19, %20, %21, %22, %23, %24, %25, %26, %27, %28, %29, %30, %31, %32, %33, %34, %35}, {%76, %77, %78, %79}, dx1, 1, 1, 1, 0;\n"
      "wgmma.mma_async.sync.aligned.m64n72k16.f32.bf16.bf16 {%0, %1, %2, %3, %4, %5, %6, %7, %8, %9, %10, %11, %12, %13, %14, %15, %16, %17, %18, %19, %20, %21, %22, %23, %24, %25, %26, %27, %28, %29, %30, %31, %32, %33, %34, %35}, {%80, %81, %82, %83}, dx2, 1, 1, 1, 0;\n"
      "wgmma.mma_async.sync.aligned.m64n72k16.f32.bf16.bf16 {%0, %1, %2, %3, %4, %5, %6, %7, %8, %9, %10, %11, %12, %13, %14, %15, %16, %17, %18, %19, %20, %21, %22, %23, %24, %25, %26, %27, %28, %29, %30, %31, %32, %33, %34, %35}, {%84, %85, %86, %87}, dx3, 1, 1, 1, 0;\n"
      "wgmma.commit_group.sync.aligned;\n"
      "wgmma.mma_async.sync.aligned.m64n72k16.f32.bf16.bf16 {%36, %37, %38, %39, %40, %41, %42, %43, %44, %45, %46, %47, %48, %49, %50, %51, %52, %53, %54, %55, %56, %57, %58, %59, %60, %61, %62, %63, %64, %65, %66, %67, %68, %69, %70, %71}, {%92, %93, %94, %95}, %112, 0, 1, 1, 0;\n"
      "wgmma.mma_async.sync.aligned.m64n72k16.f32.bf16.bf16 {%36, %37, %38, %39, %40, %41, %42, %43, %44, %45, %46, %47, %48, %49, %50, %51, %52, %53, %54, %55, %56, %57, %58, %59, %60, %61, %62, %63, %64, %65, %66, %67, %68, %69, %70, %71}, {%96, %97, %98, %99}, dx1, 1, 1, 1, 0;\n"
      "wgmma.mma_async.sync.aligned.m64n72k16.f32.bf16.bf16 {%36, %37, %38, %39, %40, %41, %42, %43, %44, %45, %46, %47, %48, %49, %50, %51, %52, %53, %54, %55, %56, %57, %58, %59, %60, %61, %62, %63, %64, %65, %66, %67, %68, %69, %70, %71}, {%100, %101, %102, %103}, dx2, 1, 1, 1, 0;\n"
      "wgmma.mma_async.sync.aligned.m64n72k16.f32.bf16.bf16 {%36, %37, %38, %39, %40, %41, %42, %43, %44, %45, %46, %47, %48, %49, %50, %51, %52, %53, %54, %55, %56, %57, %58, %59, %60, %61, %62, %63, %64, %65, %66, %67, %68, %69, %70, %71}, {%104, %105, %106, %107}, dx3, 1, 1, 1, 0;\n"
      "wgmma.commit_group.sync.aligned;\n}\n"
      : "=f"(g[0]), "=f"(g[1]), "=f"(g[2]), "=f"(g[3]), "=f"(g[4]), "=f"(g[5]), "=f"(g[6]), "=f"(g[7]), "=f"(g[8]), "=f"(g[9]), "=f"(g[10]), "=f"(g[11]), "=f"(g[12]), "=f"(g[13]), "=f"(g[14]), "=f"(g[15]), "=f"(g[16]), "=f"(g[17]), "=f"(g[18]), "=f"(g[19]), "=f"(g[20]), "=f"(g[21]), "=f"(g[22]), "=f"(g[23]), "=f"(g[24]), "=f"(g[25]), "=f"(g[26]), "=f"(g[27]), "=f"(g[28]), "=f"(g[29]), "=f"(g[30]), "=f"(g[31]), "=f"(g[32]), "=f"(g[33]), "=f"(g[34]), "=f"(g[35]),
        "=f"(h[0]), "=f"(h[1]), "=f"(h[2]), "=f"(h[3]), "=f"(h[4]), "=f"(h[5]), "=f"(h[6]), "=f"(h[7]), "=f"(h[8]), "=f"(h[9]), "=f"(h[10]), "=f"(h[11]), "=f"(h[12]), "=f"(h[13]), "=f"(h[14]), "=f"(h[15]), "=f"(h[16]), "=f"(h[17]), "=f"(h[18]), "=f"(h[19]), "=f"(h[20]), "=f"(h[21]), "=f"(h[22]), "=f"(h[23]), "=f"(h[24]), "=f"(h[25]), "=f"(h[26]), "=f"(h[27]), "=f"(h[28]), "=f"(h[29]), "=f"(h[30]), "=f"(h[31]), "=f"(h[32]), "=f"(h[33]), "=f"(h[34]), "=f"(h[35])
      : "r"(w[0]), "r"(w[1]), "r"(w[2]), "r"(w[3]), "r"(w[4]), "r"(w[5]), "r"(w[6]), "r"(w[7]), "r"(w[8]), "r"(w[9]), "r"(w[10]), "r"(w[11]), "r"(w[12]), "r"(w[13]), "r"(w[14]), "r"(w[15]), "r"(w[16]), "r"(w[17]), "r"(w[18]), "r"(w[19]), "r"(w[20]), "r"(w[21]), "r"(w[22]), "r"(w[23]), "r"(w[24]), "r"(w[25]), "r"(w[26]), "r"(w[27]), "r"(w[28]), "r"(w[29]), "r"(w[30]), "r"(w[31]), "r"(w[32]), "r"(w[33]), "r"(w[34]), "r"(w[35]), "r"(w[36]), "r"(w[37]), "r"(w[38]), "r"(w[39]), "l"(dx), "l"(de), "l"(dh)
      : "memory");
  }
  static __device__ __forceinline__ void wait_g(float* g) {
    asm volatile("wgmma.wait_group.sync.aligned 1;\n"
      : "+f"(g[0]), "+f"(g[1]), "+f"(g[2]), "+f"(g[3]), "+f"(g[4]), "+f"(g[5]), "+f"(g[6]), "+f"(g[7]), "+f"(g[8]), "+f"(g[9]), "+f"(g[10]), "+f"(g[11]), "+f"(g[12]), "+f"(g[13]), "+f"(g[14]), "+f"(g[15]), "+f"(g[16]), "+f"(g[17]), "+f"(g[18]), "+f"(g[19]), "+f"(g[20]), "+f"(g[21]), "+f"(g[22]), "+f"(g[23]), "+f"(g[24]), "+f"(g[25]), "+f"(g[26]), "+f"(g[27]), "+f"(g[28]), "+f"(g[29]), "+f"(g[30]), "+f"(g[31]), "+f"(g[32]), "+f"(g[33]), "+f"(g[34]), "+f"(g[35])
      :: "memory");
  }
  static __device__ __forceinline__ void wait_h(float* h) {
    asm volatile("wgmma.wait_group.sync.aligned 0;\n"
      : "+f"(h[0]), "+f"(h[1]), "+f"(h[2]), "+f"(h[3]), "+f"(h[4]), "+f"(h[5]), "+f"(h[6]), "+f"(h[7]), "+f"(h[8]), "+f"(h[9]), "+f"(h[10]), "+f"(h[11]), "+f"(h[12]), "+f"(h[13]), "+f"(h[14]), "+f"(h[15]), "+f"(h[16]), "+f"(h[17]), "+f"(h[18]), "+f"(h[19]), "+f"(h[20]), "+f"(h[21]), "+f"(h[22]), "+f"(h[23]), "+f"(h[24]), "+f"(h[25]), "+f"(h[26]), "+f"(h[27]), "+f"(h[28]), "+f"(h[29]), "+f"(h[30]), "+f"(h[31]), "+f"(h[32]), "+f"(h[33]), "+f"(h[34]), "+f"(h[35])
      :: "memory");
  }
};
template<> struct TileMMA<10> {
  static __device__ __forceinline__ void issue(float* g, float* h, const uint32_t* w, uint64_t dx, uint64_t de, uint64_t dh, uint64_t dc) {
    asm volatile(
      "{\n.reg .b64 dx1, dx2, dx3;\n"
      "add.s64 dx1, %120, 2;\nadd.s64 dx2, %120, 4;\nadd.s64 dx3, %120, 6;\n"
      "wgmma.fence.sync.aligned;\n"
      "wgmma.mma_async.sync.aligned.m64n80k16.f32.bf16.bf16 {%0, %1, %2, %3, %4, %5, %6, %7, %8, %9, %10, %11, %12, %13, %14, %15, %16, %17, %18, %19, %20, %21, %22, %23, %24, %25, %26, %27, %28, %29, %30, %31, %32, %33, %34, %35, %36, %37, %38, %39}, {%116, %117, %118, %119}, %122, 0, 1, 1, 0;\n"
      "wgmma.mma_async.sync.aligned.m64n80k16.f32.bf16.bf16 {%0, %1, %2, %3, %4, %5, %6, %7, %8, %9, %10, %11, %12, %13, %14, %15, %16, %17, %18, %19, %20, %21, %22, %23, %24, %25, %26, %27, %28, %29, %30, %31, %32, %33, %34, %35, %36, %37, %38, %39}, {%96, %97, %98, %99}, %121, 1, 1, 1, 0;\n"
      "wgmma.mma_async.sync.aligned.m64n80k16.f32.bf16.bf16 {%0, %1, %2, %3, %4, %5, %6, %7, %8, %9, %10, %11, %12, %13, %14, %15, %16, %17, %18, %19, %20, %21, %22, %23, %24, %25, %26, %27, %28, %29, %30, %31, %32, %33, %34, %35, %36, %37, %38, %39}, {%80, %81, %82, %83}, %120, 1, 1, 1, 0;\n"
      "wgmma.mma_async.sync.aligned.m64n80k16.f32.bf16.bf16 {%0, %1, %2, %3, %4, %5, %6, %7, %8, %9, %10, %11, %12, %13, %14, %15, %16, %17, %18, %19, %20, %21, %22, %23, %24, %25, %26, %27, %28, %29, %30, %31, %32, %33, %34, %35, %36, %37, %38, %39}, {%84, %85, %86, %87}, dx1, 1, 1, 1, 0;\n"
      "wgmma.mma_async.sync.aligned.m64n80k16.f32.bf16.bf16 {%0, %1, %2, %3, %4, %5, %6, %7, %8, %9, %10, %11, %12, %13, %14, %15, %16, %17, %18, %19, %20, %21, %22, %23, %24, %25, %26, %27, %28, %29, %30, %31, %32, %33, %34, %35, %36, %37, %38, %39}, {%88, %89, %90, %91}, dx2, 1, 1, 1, 0;\n"
      "wgmma.mma_async.sync.aligned.m64n80k16.f32.bf16.bf16 {%0, %1, %2, %3, %4, %5, %6, %7, %8, %9, %10, %11, %12, %13, %14, %15, %16, %17, %18, %19, %20, %21, %22, %23, %24, %25, %26, %27, %28, %29, %30, %31, %32, %33, %34, %35, %36, %37, %38, %39}, {%92, %93, %94, %95}, dx3, 1, 1, 1, 0;\n"
      "wgmma.commit_group.sync.aligned;\n"
      "wgmma.mma_async.sync.aligned.m64n80k16.f32.bf16.bf16 {%40, %41, %42, %43, %44, %45, %46, %47, %48, %49, %50, %51, %52, %53, %54, %55, %56, %57, %58, %59, %60, %61, %62, %63, %64, %65, %66, %67, %68, %69, %70, %71, %72, %73, %74, %75, %76, %77, %78, %79}, {%100, %101, %102, %103}, %120, 0, 1, 1, 0;\n"
      "wgmma.mma_async.sync.aligned.m64n80k16.f32.bf16.bf16 {%40, %41, %42, %43, %44, %45, %46, %47, %48, %49, %50, %51, %52, %53, %54, %55, %56, %57, %58, %59, %60, %61, %62, %63, %64, %65, %66, %67, %68, %69, %70, %71, %72, %73, %74, %75, %76, %77, %78, %79}, {%104, %105, %106, %107}, dx1, 1, 1, 1, 0;\n"
      "wgmma.mma_async.sync.aligned.m64n80k16.f32.bf16.bf16 {%40, %41, %42, %43, %44, %45, %46, %47, %48, %49, %50, %51, %52, %53, %54, %55, %56, %57, %58, %59, %60, %61, %62, %63, %64, %65, %66, %67, %68, %69, %70, %71, %72, %73, %74, %75, %76, %77, %78, %79}, {%108, %109, %110, %111}, dx2, 1, 1, 1, 0;\n"
      "wgmma.mma_async.sync.aligned.m64n80k16.f32.bf16.bf16 {%40, %41, %42, %43, %44, %45, %46, %47, %48, %49, %50, %51, %52, %53, %54, %55, %56, %57, %58, %59, %60, %61, %62, %63, %64, %65, %66, %67, %68, %69, %70, %71, %72, %73, %74, %75, %76, %77, %78, %79}, {%112, %113, %114, %115}, dx3, 1, 1, 1, 0;\n"
      "wgmma.commit_group.sync.aligned;\n}\n"
      : "=f"(g[0]), "=f"(g[1]), "=f"(g[2]), "=f"(g[3]), "=f"(g[4]), "=f"(g[5]), "=f"(g[6]), "=f"(g[7]), "=f"(g[8]), "=f"(g[9]), "=f"(g[10]), "=f"(g[11]), "=f"(g[12]), "=f"(g[13]), "=f"(g[14]), "=f"(g[15]), "=f"(g[16]), "=f"(g[17]), "=f"(g[18]), "=f"(g[19]), "=f"(g[20]), "=f"(g[21]), "=f"(g[22]), "=f"(g[23]), "=f"(g[24]), "=f"(g[25]), "=f"(g[26]), "=f"(g[27]), "=f"(g[28]), "=f"(g[29]), "=f"(g[30]), "=f"(g[31]), "=f"(g[32]), "=f"(g[33]), "=f"(g[34]), "=f"(g[35]), "=f"(g[36]), "=f"(g[37]), "=f"(g[38]), "=f"(g[39]),
        "=f"(h[0]), "=f"(h[1]), "=f"(h[2]), "=f"(h[3]), "=f"(h[4]), "=f"(h[5]), "=f"(h[6]), "=f"(h[7]), "=f"(h[8]), "=f"(h[9]), "=f"(h[10]), "=f"(h[11]), "=f"(h[12]), "=f"(h[13]), "=f"(h[14]), "=f"(h[15]), "=f"(h[16]), "=f"(h[17]), "=f"(h[18]), "=f"(h[19]), "=f"(h[20]), "=f"(h[21]), "=f"(h[22]), "=f"(h[23]), "=f"(h[24]), "=f"(h[25]), "=f"(h[26]), "=f"(h[27]), "=f"(h[28]), "=f"(h[29]), "=f"(h[30]), "=f"(h[31]), "=f"(h[32]), "=f"(h[33]), "=f"(h[34]), "=f"(h[35]), "=f"(h[36]), "=f"(h[37]), "=f"(h[38]), "=f"(h[39])
      : "r"(w[0]), "r"(w[1]), "r"(w[2]), "r"(w[3]), "r"(w[4]), "r"(w[5]), "r"(w[6]), "r"(w[7]), "r"(w[8]), "r"(w[9]), "r"(w[10]), "r"(w[11]), "r"(w[12]), "r"(w[13]), "r"(w[14]), "r"(w[15]), "r"(w[16]), "r"(w[17]), "r"(w[18]), "r"(w[19]), "r"(w[20]), "r"(w[21]), "r"(w[22]), "r"(w[23]), "r"(w[24]), "r"(w[25]), "r"(w[26]), "r"(w[27]), "r"(w[28]), "r"(w[29]), "r"(w[30]), "r"(w[31]), "r"(w[32]), "r"(w[33]), "r"(w[34]), "r"(w[35]), "r"(w[36]), "r"(w[37]), "r"(w[38]), "r"(w[39]), "l"(dx), "l"(de), "l"(dh)
      : "memory");
  }
  static __device__ __forceinline__ void wait_g(float* g) {
    asm volatile("wgmma.wait_group.sync.aligned 1;\n"
      : "+f"(g[0]), "+f"(g[1]), "+f"(g[2]), "+f"(g[3]), "+f"(g[4]), "+f"(g[5]), "+f"(g[6]), "+f"(g[7]), "+f"(g[8]), "+f"(g[9]), "+f"(g[10]), "+f"(g[11]), "+f"(g[12]), "+f"(g[13]), "+f"(g[14]), "+f"(g[15]), "+f"(g[16]), "+f"(g[17]), "+f"(g[18]), "+f"(g[19]), "+f"(g[20]), "+f"(g[21]), "+f"(g[22]), "+f"(g[23]), "+f"(g[24]), "+f"(g[25]), "+f"(g[26]), "+f"(g[27]), "+f"(g[28]), "+f"(g[29]), "+f"(g[30]), "+f"(g[31]), "+f"(g[32]), "+f"(g[33]), "+f"(g[34]), "+f"(g[35]), "+f"(g[36]), "+f"(g[37]), "+f"(g[38]), "+f"(g[39])
      :: "memory");
  }
  static __device__ __forceinline__ void wait_h(float* h) {
    asm volatile("wgmma.wait_group.sync.aligned 0;\n"
      : "+f"(h[0]), "+f"(h[1]), "+f"(h[2]), "+f"(h[3]), "+f"(h[4]), "+f"(h[5]), "+f"(h[6]), "+f"(h[7]), "+f"(h[8]), "+f"(h[9]), "+f"(h[10]), "+f"(h[11]), "+f"(h[12]), "+f"(h[13]), "+f"(h[14]), "+f"(h[15]), "+f"(h[16]), "+f"(h[17]), "+f"(h[18]), "+f"(h[19]), "+f"(h[20]), "+f"(h[21]), "+f"(h[22]), "+f"(h[23]), "+f"(h[24]), "+f"(h[25]), "+f"(h[26]), "+f"(h[27]), "+f"(h[28]), "+f"(h[29]), "+f"(h[30]), "+f"(h[31]), "+f"(h[32]), "+f"(h[33]), "+f"(h[34]), "+f"(h[35]), "+f"(h[36]), "+f"(h[37]), "+f"(h[38]), "+f"(h[39])
      :: "memory");
  }
};
template<> struct TileMMA<11> {
  static __device__ __forceinline__ void issue(float* g, float* h, const uint32_t* w, uint64_t dx, uint64_t de, uint64_t dh, uint64_t dc) {
    asm volatile(
      "{\n.reg .b64 dx1, dx2, dx3;\n"
      "add.s64 dx1, %124, 2;\nadd.s64 dx2, %124, 4;\nadd.s64 dx3, %124, 6;\n"
      "wgmma.fence.sync.aligned;\n"
      "wgmma.mma_async.sync.aligned.m64n88k16.f32.bf16.bf16 {%0, %1, %2, %3, %4, %5, %6, %7, %8, %9, %10, %11, %12, %13, %14, %15, %16, %17, %18, %19, %20, %21, %22, %23, %24, %25, %26, %27, %28, %29, %30, %31, %32, %33, %34, %35, %36, %37, %38, %39, %40, %41, %42, %43}, {%120, %121, %122, %123}, %126, 0, 1, 1, 0;\n"
      "wgmma.mma_async.sync.aligned.m64n88k16.f32.bf16.bf16 {%0, %1, %2, %3, %4, %5, %6, %7, %8, %9, %10, %11, %12, %13, %14, %15, %16, %17, %18, %19, %20, %21, %22, %23, %24, %25, %26, %27, %28, %29, %30, %31, %32, %33, %34, %35, %36, %37, %38, %39, %40, %41, %42, %43}, %127, %125, 1, 1, 1, 0, 0;\n"
      "wgmma.mma_async.sync.aligned.m64n88k16.f32.bf16.bf16 {%0, %1, %2, %3, %4, %5, %6, %7, %8, %9, %10, %11, %12, %13, %14, %15, %16, %17, %18, %19, %20, %21, %22, %23, %24, %25, %26, %27, %28, %29, %30, %31, %32, %33, %34, %35, %36, %37, %38, %39, %40, %41, %42, %43}, {%88, %89, %90, %91}, %124, 1, 1, 1, 0;\n"
      "wgmma.mma_async.sync.aligned.m64n88k16.f32.bf16.bf16 {%0, %1, %2, %3, %4, %5, %6, %7, %8, %9, %10, %11, %12, %13, %14, %15, %16, %17, %18, %19, %20, %21, %22, %23, %24, %25, %26, %27, %28, %29, %30, %31, %32, %33, %34, %35, %36, %37, %38, %39, %40, %41, %42, %43}, {%92, %93, %94, %95}, dx1, 1, 1, 1, 0;\n"
      "wgmma.mma_async.sync.aligned.m64n88k16.f32.bf16.bf16 {%0, %1, %2, %3, %4, %5, %6, %7, %8, %9, %10, %11, %12, %13, %14, %15, %16, %17, %18, %19, %20, %21, %22, %23, %24, %25, %26, %27, %28, %29, %30, %31, %32, %33, %34, %35, %36, %37, %38, %39, %40, %41, %42, %43}, {%96, %97, %98, %99}, dx2, 1, 1, 1, 0;\n"
      "wgmma.mma_async.sync.aligned.m64n88k16.f32.bf16.bf16 {%0, %1, %2, %3, %4, %5, %6, %7, %8, %9, %10, %11, %12, %13, %14, %15, %16, %17, %18, %19, %20, %21, %22, %23, %24, %25, %26, %27, %28, %29, %30, %31, %32, %33, %34, %35, %36, %37, %38, %39, %40, %41, %42, %43}, {%100, %101, %102, %103}, dx3, 1, 1, 1, 0;\n"
      "wgmma.commit_group.sync.aligned;\n"
      "wgmma.mma_async.sync.aligned.m64n88k16.f32.bf16.bf16 {%44, %45, %46, %47, %48, %49, %50, %51, %52, %53, %54, %55, %56, %57, %58, %59, %60, %61, %62, %63, %64, %65, %66, %67, %68, %69, %70, %71, %72, %73, %74, %75, %76, %77, %78, %79, %80, %81, %82, %83, %84, %85, %86, %87}, {%104, %105, %106, %107}, %124, 0, 1, 1, 0;\n"
      "wgmma.mma_async.sync.aligned.m64n88k16.f32.bf16.bf16 {%44, %45, %46, %47, %48, %49, %50, %51, %52, %53, %54, %55, %56, %57, %58, %59, %60, %61, %62, %63, %64, %65, %66, %67, %68, %69, %70, %71, %72, %73, %74, %75, %76, %77, %78, %79, %80, %81, %82, %83, %84, %85, %86, %87}, {%108, %109, %110, %111}, dx1, 1, 1, 1, 0;\n"
      "wgmma.mma_async.sync.aligned.m64n88k16.f32.bf16.bf16 {%44, %45, %46, %47, %48, %49, %50, %51, %52, %53, %54, %55, %56, %57, %58, %59, %60, %61, %62, %63, %64, %65, %66, %67, %68, %69, %70, %71, %72, %73, %74, %75, %76, %77, %78, %79, %80, %81, %82, %83, %84, %85, %86, %87}, {%112, %113, %114, %115}, dx2, 1, 1, 1, 0;\n"
      "wgmma.mma_async.sync.aligned.m64n88k16.f32.bf16.bf16 {%44, %45, %46, %47, %48, %49, %50, %51, %52, %53, %54, %55, %56, %57, %58, %59, %60, %61, %62, %63, %64, %65, %66, %67, %68, %69, %70, %71, %72, %73, %74, %75, %76, %77, %78, %79, %80, %81, %82, %83, %84, %85, %86, %87}, {%116, %117, %118, %119}, dx3, 1, 1, 1, 0;\n"
      "wgmma.commit_group.sync.aligned;\n}\n"
      : "=f"(g[0]), "=f"(g[1]), "=f"(g[2]), "=f"(g[3]), "=f"(g[4]), "=f"(g[5]), "=f"(g[6]), "=f"(g[7]), "=f"(g[8]), "=f"(g[9]), "=f"(g[10]), "=f"(g[11]), "=f"(g[12]), "=f"(g[13]), "=f"(g[14]), "=f"(g[15]), "=f"(g[16]), "=f"(g[17]), "=f"(g[18]), "=f"(g[19]), "=f"(g[20]), "=f"(g[21]), "=f"(g[22]), "=f"(g[23]), "=f"(g[24]), "=f"(g[25]), "=f"(g[26]), "=f"(g[27]), "=f"(g[28]), "=f"(g[29]), "=f"(g[30]), "=f"(g[31]), "=f"(g[32]), "=f"(g[33]), "=f"(g[34]), "=f"(g[35]), "=f"(g[36]), "=f"(g[37]), "=f"(g[38]), "=f"(g[39]), "=f"(g[40]), "=f"(g[41]), "=f"(g[42]), "=f"(g[43]),
        "=f"(h[0]), "=f"(h[1]), "=f"(h[2]), "=f"(h[3]), "=f"(h[4]), "=f"(h[5]), "=f"(h[6]), "=f"(h[7]), "=f"(h[8]), "=f"(h[9]), "=f"(h[10]), "=f"(h[11]), "=f"(h[12]), "=f"(h[13]), "=f"(h[14]), "=f"(h[15]), "=f"(h[16]), "=f"(h[17]), "=f"(h[18]), "=f"(h[19]), "=f"(h[20]), "=f"(h[21]), "=f"(h[22]), "=f"(h[23]), "=f"(h[24]), "=f"(h[25]), "=f"(h[26]), "=f"(h[27]), "=f"(h[28]), "=f"(h[29]), "=f"(h[30]), "=f"(h[31]), "=f"(h[32]), "=f"(h[33]), "=f"(h[34]), "=f"(h[35]), "=f"(h[36]), "=f"(h[37]), "=f"(h[38]), "=f"(h[39]), "=f"(h[40]), "=f"(h[41]), "=f"(h[42]), "=f"(h[43])
      : "r"(w[0]), "r"(w[1]), "r"(w[2]), "r"(w[3]), "r"(w[4]), "r"(w[5]), "r"(w[6]), "r"(w[7]), "r"(w[8]), "r"(w[9]), "r"(w[10]), "r"(w[11]), "r"(w[12]), "r"(w[13]), "r"(w[14]), "r"(w[15]), "r"(w[20]), "r"(w[21]), "r"(w[22]), "r"(w[23]), "r"(w[24]), "r"(w[25]), "r"(w[26]), "r"(w[27]), "r"(w[28]), "r"(w[29]), "r"(w[30]), "r"(w[31]), "r"(w[32]), "r"(w[33]), "r"(w[34]), "r"(w[35]), "r"(w[36]), "r"(w[37]), "r"(w[38]), "r"(w[39]), "l"(dx), "l"(de), "l"(dh), "l"(dc)
      : "memory");
  }
  static __device__ __forceinline__ void wait_g(float* g) {
    asm volatile("wgmma.wait_group.sync.aligned 1;\n"
      : "+f"(g[0]), "+f"(g[1]), "+f"(g[2]), "+f"(g[3]), "+f"(g[4]), "+f"(g[5]), "+f"(g[6]), "+f"(g[7]), "+f"(g[8]), "+f"(g[9]), "+f"(g[10]), "+f"(g[11]), "+f"(g[12]), "+f"(g[13]), "+f"(g[14]), "+f"(g[15]), "+f"(g[16]), "+f"(g[17]), "+f"(g[18]), "+f"(g[19]), "+f"(g[20]), "+f"(g[21]), "+f"(g[22]), "+f"(g[23]), "+f"(g[24]), "+f"(g[25]), "+f"(g[26]), "+f"(g[27]), "+f"(g[28]), "+f"(g[29]), "+f"(g[30]), "+f"(g[31]), "+f"(g[32]), "+f"(g[33]), "+f"(g[34]), "+f"(g[35]), "+f"(g[36]), "+f"(g[37]), "+f"(g[38]), "+f"(g[39]), "+f"(g[40]), "+f"(g[41]), "+f"(g[42]), "+f"(g[43])
      :: "memory");
  }
  static __device__ __forceinline__ void wait_h(float* h) {
    asm volatile("wgmma.wait_group.sync.aligned 0;\n"
      : "+f"(h[0]), "+f"(h[1]), "+f"(h[2]), "+f"(h[3]), "+f"(h[4]), "+f"(h[5]), "+f"(h[6]), "+f"(h[7]), "+f"(h[8]), "+f"(h[9]), "+f"(h[10]), "+f"(h[11]), "+f"(h[12]), "+f"(h[13]), "+f"(h[14]), "+f"(h[15]), "+f"(h[16]), "+f"(h[17]), "+f"(h[18]), "+f"(h[19]), "+f"(h[20]), "+f"(h[21]), "+f"(h[22]), "+f"(h[23]), "+f"(h[24]), "+f"(h[25]), "+f"(h[26]), "+f"(h[27]), "+f"(h[28]), "+f"(h[29]), "+f"(h[30]), "+f"(h[31]), "+f"(h[32]), "+f"(h[33]), "+f"(h[34]), "+f"(h[35]), "+f"(h[36]), "+f"(h[37]), "+f"(h[38]), "+f"(h[39]), "+f"(h[40]), "+f"(h[41]), "+f"(h[42]), "+f"(h[43])
      :: "memory");
  }
};
__device__ __forceinline__ void node_mma2(float* u, float* a, const uint32_t* w, uint64_t dx) {
    asm volatile(
      "{\n.reg .b64 dx1, dx2, dx3, dy0, dy1, dy2, dy3;\n"
      "add.s64 dx1, %80, 2;\nadd.s64 dx2, %80, 4;\nadd.s64 dx3, %80, 6;\n"
      "add.s64 dy0, %80, 512;\nadd.s64 dy1, %80, 514;\nadd.s64 dy2, %80, 516;\nadd.s64 dy3, %80, 518;\n"
      "wgmma.fence.sync.aligned;\n"
      "wgmma.mma_async.sync.aligned.m64n64k16.f32.bf16.bf16 {%0, %1, %2, %3, %4, %5, %6, %7, %8, %9, %10, %11, %12, %13, %14, %15, %16, %17, %18, %19, %20, %21, %22, %23, %24, %25, %26, %27, %28, %29, %30, %31}, {%64, %65, %66, %67}, %80, 0, 1, 1, 0;\n"
      "wgmma.mma_async.sync.aligned.m64n64k16.f32.bf16.bf16 {%0, %1, %2, %3, %4, %5, %6, %7, %8, %9, %10, %11, %12, %13, %14, %15, %16, %17, %18, %19, %20, %21, %22, %23, %24, %25, %26, %27, %28, %29, %30, %31}, {%68, %69, %70, %71}, dx1, 1, 1, 1, 0;\n"
      "wgmma.mma_async.sync.aligned.m64n64k16.f32.bf16.bf16 {%0, %1, %2, %3, %4, %5, %6, %7, %8, %9, %10, %11, %12, %13, %14, %15, %16, %17, %18, %19, %20, %21, %22, %23, %24, %25, %26, %27, %28, %29, %30, %31}, {%72, %73, %74, %75}, dx2, 1, 1, 1, 0;\n"
      "wgmma.mma_async.sync.aligned.m64n64k16.f32.bf16.bf16 {%0, %1, %2, %3, %4, %5, %6, %7, %8, %9, %10, %11, %12, %13, %14, %15, %16, %17, %18, %19, %20, %21, %22, %23, %24, %25, %26, %27, %28, %29, %30, %31}, {%76, %77, %78, %79}, dx3, 1, 1, 1, 0;\n"
      "wgmma.commit_group.sync.aligned;\n"
      "wgmma.mma_async.sync.aligned.m64n64k16.f32.bf16.bf16 {%32, %33, %34, %35, %36, %37, %38, %39, %40, %41, %42, %43, %44, %45, %46, %47, %48, %49, %50, %51, %52, %53, %54, %55, %56, %57, %58, %59, %60, %61, %62, %63}, {%64, %65, %66, %67}, dy0, 0, 1, 1, 0;\n"
      "wgmma.mma_async.sync.aligned.m64n64k16.f32.bf16.bf16 {%32, %33, %34, %35, %36, %37, %38, %39, %40, %41, %42, %43, %44, %45, %46, %47, %48, %49, %50, %51, %52, %53, %54, %55, %56, %57, %58, %59, %60, %61, %62, %63}, {%68, %69, %70, %71}, dy1, 1, 1, 1, 0;\n"
      "wgmma.mma_async.sync.aligned.m64n64k16.f32.bf16.bf16 {%32, %33, %34, %35, %36, %37, %38, %39, %40, %41, %42, %43, %44, %45, %46, %47, %48, %49, %50, %51, %52, %53, %54, %55, %56, %57, %58, %59, %60, %61, %62, %63}, {%72, %73, %74, %75}, dy2, 1, 1, 1, 0;\n"
      "wgmma.mma_async.sync.aligned.m64n64k16.f32.bf16.bf16 {%32, %33, %34, %35, %36, %37, %38, %39, %40, %41, %42, %43, %44, %45, %46, %47, %48, %49, %50, %51, %52, %53, %54, %55, %56, %57, %58, %59, %60, %61, %62, %63}, {%76, %77, %78, %79}, dy3, 1, 1, 1, 0;\n"
      "wgmma.commit_group.sync.aligned;\n}\n"
      : "=f"(u[0]), "=f"(u[1]), "=f"(u[2]), "=f"(u[3]), "=f"(u[4]), "=f"(u[5]), "=f"(u[6]), "=f"(u[7]), "=f"(u[8]), "=f"(u[9]), "=f"(u[10]), "=f"(u[11]), "=f"(u[12]), "=f"(u[13]), "=f"(u[14]), "=f"(u[15]), "=f"(u[16]), "=f"(u[17]), "=f"(u[18]), "=f"(u[19]), "=f"(u[20]), "=f"(u[21]), "=f"(u[22]), "=f"(u[23]), "=f"(u[24]), "=f"(u[25]), "=f"(u[26]), "=f"(u[27]), "=f"(u[28]), "=f"(u[29]), "=f"(u[30]), "=f"(u[31]),
        "=f"(a[0]), "=f"(a[1]), "=f"(a[2]), "=f"(a[3]), "=f"(a[4]), "=f"(a[5]), "=f"(a[6]), "=f"(a[7]), "=f"(a[8]), "=f"(a[9]), "=f"(a[10]), "=f"(a[11]), "=f"(a[12]), "=f"(a[13]), "=f"(a[14]), "=f"(a[15]), "=f"(a[16]), "=f"(a[17]), "=f"(a[18]), "=f"(a[19]), "=f"(a[20]), "=f"(a[21]), "=f"(a[22]), "=f"(a[23]), "=f"(a[24]), "=f"(a[25]), "=f"(a[26]), "=f"(a[27]), "=f"(a[28]), "=f"(a[29]), "=f"(a[30]), "=f"(a[31])
      : "r"(w[0]), "r"(w[1]), "r"(w[2]), "r"(w[3]), "r"(w[4]), "r"(w[5]), "r"(w[6]), "r"(w[7]), "r"(w[8]), "r"(w[9]), "r"(w[10]), "r"(w[11]), "r"(w[12]), "r"(w[13]), "r"(w[14]), "r"(w[15]), "l"(dx)
      : "memory");
}

__device__ __forceinline__ uint32_t smem_u32(const void* p) { return (uint32_t)__cvta_generic_to_shared(p); }
__device__ __forceinline__ float ex2f(float x) { float y; asm("ex2.approx.ftz.f32 %0, %1;" : "=f"(y) : "f"(x)); return y; }
__device__ __forceinline__ float rcpf(float x) { float y; asm("rcp.approx.ftz.f32 %0, %1;" : "=f"(y) : "f"(x)); return y; }
__device__ __forceinline__ uint32_t pack_bf16(float lo, float hi) {
    uint32_t r; asm("cvt.rn.bf16x2.f32 %0, %1, %2;" : "=r"(r) : "f"(hi), "f"(lo)); return r;
}
__device__ __forceinline__ float bf_lo(uint32_t v) { return __uint_as_float(v << 16); }
__device__ __forceinline__ float bf_hi(uint32_t v) { return __uint_as_float(v & 0xFFFF0000u); }
template<int STRIDE>
__device__ __forceinline__ void cp16i(uint32_t dst, const char* base, uint32_t idx) {
    asm volatile("{\n.reg .b64 a;\nmad.wide.u32 a, %2, %3, %1;\ncp.async.cg.shared.global [%0], [a], 16;\n}\n" :: "r"(dst), "l"(base), "r"(idx), "n"(STRIDE) : "memory");
}
__device__ __forceinline__ void cp16e(uint32_t dst, const char* base, uint32_t idx, uint64_t pol) {
    asm volatile("{\n.reg .b64 a;\nmad.wide.u32 a, %2, 32, %1;\ncp.async.cg.shared.global.L2::cache_hint [%0], [a], 16, %3;\n}\n" :: "r"(dst), "l"(base), "r"(idx), "l"(pol) : "memory");
}
template<int STRIDE>
__device__ __forceinline__ void cp16z(uint32_t dst, const char* base, uint32_t idx, int k, int n, uint64_t pol) {
    if (STRIDE == 32)
        asm volatile("{\n.reg .b64 a;\n.reg .pred p;\nsetp.ge.s32 p, %3, %4;\nmad.wide.u32 a, %2, 32, %1;\ncp.async.cg.shared.global.L2::cache_hint [%0], [a], 16, p, %5;\n}\n"
                     :: "r"(dst), "l"(base), "r"(idx), "r"(k), "r"(n), "l"(pol) : "memory");
    else
        asm volatile("{\n.reg .b64 a;\n.reg .pred p;\nsetp.ge.s32 p, %3, %4;\nmad.wide.u32 a, %2, 128, %1;\ncp.async.cg.shared.global [%0], [a], 16, p;\n}\n"
                     :: "r"(dst), "l"(base), "r"(idx), "r"(k), "r"(n) : "memory");
}
template<int HI, bool Z>
__device__ __forceinline__ void cpx(uint32_t hi, uint32_t dst, uint32_t p, uint32_t lo, int k, int n) {
    if (Z) asm volatile("{\n.reg .b32 l;\n.reg .b64 a;\n.reg .pred q;\nsetp.ge.s32 q, %5, %6;\ndp2a.lo.u32.u32 l, %1, %2, %3;\nmov.b64 a, {l, %0};\ncp.async.cg.shared.global [%4], [a], 16, q;\n}\n"
                        :: "r"(hi), "r"(p), "r"(HI ? 0x8000u : 0x80u), "r"(lo), "r"(dst), "r"(k), "r"(n) : "memory");
    else asm volatile("{\n.reg .b32 l;\n.reg .b64 a;\ndp2a.lo.u32.u32 l, %1, %2, %3;\nmov.b64 a, {l, %0};\ncp.async.cg.shared.global [%4], [a], 16;\n}\n"
                      :: "r"(hi), "r"(p), "r"(HI ? 0x8000u : 0x80u), "r"(lo), "r"(dst) : "memory");
}
template<bool Z>
__device__ __forceinline__ void cpe(uint32_t hi, uint32_t dst, uint32_t idx, uint32_t lo, int k, int n, uint64_t pol) {
    if (Z) asm volatile("{\n.reg .b32 l;\n.reg .b64 a;\n.reg .pred q;\nsetp.ge.s32 q, %5, %6;\nmad.lo.u32 l, %1, 32, %2;\nmov.b64 a, {l, %0};\ncp.async.cg.shared.global.L2::cache_hint [%3], [a], 16, q, %4;\n}\n"
                        :: "r"(hi), "r"(idx), "r"(lo), "r"(dst), "l"(pol), "r"(k), "r"(n) : "memory");
    else asm volatile("{\n.reg .b32 l;\n.reg .b64 a;\nmad.lo.u32 l, %1, 32, %2;\nmov.b64 a, {l, %0};\ncp.async.cg.shared.global.L2::cache_hint [%3], [a], 16, %4;\n}\n"
                      :: "r"(hi), "r"(idx), "r"(lo), "r"(dst), "l"(pol) : "memory");
}
template<int N> __device__ __forceinline__ void cp_wait() { asm volatile("cp.async.wait_group %0;" :: "n"(N) : "memory"); }
__device__ __forceinline__ void mbar_init(uint32_t bar, int cnt) { asm volatile("mbarrier.init.shared.b64 [%0], %1;" :: "r"(bar), "r"(cnt) : "memory"); }
__device__ __forceinline__ void mbar_arrive(uint32_t bar) { asm volatile("mbarrier.arrive.shared.b64 _, [%0];" :: "r"(bar) : "memory"); }
__device__ __forceinline__ void mbar_expect(uint32_t bar, uint32_t bytes) { asm volatile("mbarrier.arrive.expect_tx.shared.b64 _, [%0], %1;" :: "r"(bar), "r"(bytes) : "memory"); }
__device__ __forceinline__ void mbar_cp_arrive(uint32_t bar) { asm volatile("cp.async.mbarrier.arrive.noinc.shared.b64 [%0];" :: "r"(bar) : "memory"); }
__device__ __forceinline__ void mbar_wait(uint32_t bar, uint32_t parity) {
    asm volatile("{\n.reg .pred p;\n.reg .u32 n;\nmbarrier.try_wait.parity.shared.b64 p, [%0], %1;\n@p bra DONE_%=;\nmov.u32 n, 0;\n"
                 "WAIT_%=:\nmbarrier.try_wait.parity.shared.b64 p, [%0], %1, 0x100000;\n@p bra DONE_%=;\n"
                 "add.u32 n, n, 1;\nsetp.lt.u32 p, n, 0x400000;\n@p bra WAIT_%=;\ntrap;\nDONE_%=:\n}\n"
                 :: "r"(bar), "r"(parity) : "memory");
}
__device__ __forceinline__ void mbar_wait_c(uint32_t bar, uint32_t parity) {
    asm volatile("{\n.reg .pred p;\nWAIT_%=:\nmbarrier.try_wait.parity.shared.b64 p, [%0], %1;\n@p bra DONE_%=;\nbra WAIT_%=;\nDONE_%=:\n}\n"
                 :: "r"(bar), "r"(parity) : "memory");
}
__device__ __forceinline__ void mbar_wait_h(uint32_t bar, uint32_t parity) {
    asm volatile("{\n.reg .pred p;\nWAIT_%=:\nmbarrier.try_wait.parity.shared.b64 p, [%0], %1, 0x100000;\n@p bra DONE_%=;\nbra WAIT_%=;\nDONE_%=:\n}\n"
                 :: "r"(bar), "r"(parity) : "memory");
}
__device__ __forceinline__ uint32_t lds32(uint32_t a) { uint32_t v; asm volatile("ld.shared.u32 %0, [%1];" : "=r"(v) : "r"(a) : "memory"); return v; }
__device__ __forceinline__ void sts32(uint32_t a, uint32_t v) { asm volatile("st.shared.u32 [%0], %1;" :: "r"(a), "r"(v) : "memory"); }
__device__ __forceinline__ uint2 lds64(uint32_t a) { uint2 v; asm volatile("ld.shared.v2.u32 {%0,%1}, [%2];" : "=r"(v.x), "=r"(v.y) : "r"(a) : "memory"); return v; }
__device__ __forceinline__ uint4 lds128(uint32_t a) { uint4 v; asm volatile("ld.shared.v4.u32 {%0,%1,%2,%3}, [%4];" : "=r"(v.x), "=r"(v.y), "=r"(v.z), "=r"(v.w) : "r"(a) : "memory"); return v; }
__device__ __forceinline__ void sts128(uint32_t a, uint4 v) { asm volatile("st.shared.v4.u32 [%0], {%1,%2,%3,%4};" :: "r"(a), "r"(v.x), "r"(v.y), "r"(v.z), "r"(v.w) : "memory"); }
__device__ __forceinline__ void ldsm4t(uint32_t* v, uint32_t a) {
    asm volatile("ldmatrix.sync.aligned.m8n8.x4.trans.shared.b16 {%0,%1,%2,%3}, [%4];" : "=r"(v[0]), "=r"(v[1]), "=r"(v[2]), "=r"(v[3]) : "r"(a) : "memory");
}
__device__ __forceinline__ void stsm4t(uint32_t a, const uint32_t* v) {
    asm volatile("stmatrix.sync.aligned.m8n8.x4.trans.shared.b16 [%0], {%1,%2,%3,%4};" :: "r"(a), "r"(v[0]), "r"(v[1]), "r"(v[2]), "r"(v[3]) : "memory");
}
__device__ __forceinline__ int atoms_inc(uint32_t a) { int v; asm volatile("atom.shared.add.u32 %0, [%1], 1;" : "=r"(v) : "r"(a) : "memory"); return v; }
__device__ __forceinline__ bool elect_one() {
    uint32_t el;
    asm volatile("{\n.reg .pred p;\nelect.sync _|p, 0xffffffff;\nselp.u32 %0, 1, 0, p;\n}" : "=r"(el));
    return el != 0;
}
__device__ __forceinline__ float tanhf_a(float x) { float y; asm("tanh.approx.f32 %0, %1;" : "=f"(y) : "f"(x)); return y; }
__device__ __forceinline__ const char* as_pair(const void* p, uint32_t scratch) {
    const char* r;
    asm volatile("st.shared.u64 [%1], %2;\nld.volatile.shared.u64 %0, [%1];" : "=l"(r) : "r"(scratch), "l"(p) : "memory");
    return r;
}
__device__ __forceinline__ void ld_unit(uint4& v, const char* p, bool ok) {
    asm volatile("{\n.reg .pred q;\nsetp.ne.u32 q, %5, 0;\n@q ld.relaxed.gpu.global.v4.u32 {%0,%1,%2,%3}, [%4];\n}"
                 : "+r"(v.x), "+r"(v.y), "+r"(v.z), "+r"(v.w) : "l"(p), "r"((uint32_t)ok) : "memory");
}
__device__ __forceinline__ void ld_unit(uint2& v, const char* p, bool ok) {
    asm volatile("{\n.reg .pred q;\nsetp.ne.u32 q, %3, 0;\n@q ld.relaxed.gpu.global.v2.u32 {%0,%1}, [%2];\n}"
                 : "+r"(v.x), "+r"(v.y) : "l"(p), "r"((uint32_t)ok) : "memory");
}
__device__ __forceinline__ void bulk_ld(uint32_t dst, const void* src, int bytes, uint32_t bar) {
    mbar_expect(bar, bytes);
    if (bytes > 0) asm volatile("cp.async.bulk.shared::cluster.global.mbarrier::complete_tx::bytes [%0], [%1], %2, [%3];" :: "r"(dst), "l"(src), "r"(bytes), "r"(bar) : "memory");
}
__device__ __forceinline__ void bulk_st(void* dst, uint32_t src, int bytes) {
    asm volatile("cp.async.bulk.global.shared::cta.bulk_group [%0], [%1], %2;" :: "l"(dst), "r"(src), "r"(bytes) : "memory");
}

__device__ __forceinline__ void finish(uint4& a, const uint4& xu, const uint4& xv) {
    asm("{\n.reg .b32 z;\nfma.rn.relu.bf16x2 z, %0, %3, %1;\nadd.rn.bf16x2 %0, z, %2;\n}" : "+r"(a.x) : "r"(xu.x), "r"(xv.x), "r"(0x3F803F80u));
    asm("{\n.reg .b32 z;\nfma.rn.relu.bf16x2 z, %0, %3, %1;\nadd.rn.bf16x2 %0, z, %2;\n}" : "+r"(a.y) : "r"(xu.y), "r"(xv.y), "r"(0x3F803F80u));
    asm("{\n.reg .b32 z;\nfma.rn.relu.bf16x2 z, %0, %3, %1;\nadd.rn.bf16x2 %0, z, %2;\n}" : "+r"(a.z) : "r"(xu.z), "r"(xv.z), "r"(0x3F803F80u));
    asm("{\n.reg .b32 z;\nfma.rn.relu.bf16x2 z, %0, %3, %1;\nadd.rn.bf16x2 %0, z, %2;\n}" : "+r"(a.w) : "r"(xu.w), "r"(xv.w), "r"(0x3F803F80u));
}

__device__ __forceinline__ void node_rows(uint32_t p, const float* a) {
    #pragma unroll
    for (int i = 0; i < 4; i++) {
        const float* u = a + 8 * i;
        const uint32_t v[4] = {pack_bf16(u[0], u[1]), pack_bf16(u[2], u[3]), pack_bf16(u[4], u[5]), pack_bf16(u[6], u[7])};
        stsm4t(p + i * 2048, v);
    }
}

constexpr float EPS2 = 2e-6f;
constexpr float TAU = 2.5e-5f;

template<bool HALF>
__device__ __forceinline__ void make_wfrag(uint32_t* f, const uint32_t* v) {
    const uint32_t v0 = v[0], v1 = v[1], v2 = v[2], v3 = v[3];
    f[0] = __byte_perm(v0, v1, 0x5410); f[1] = __byte_perm(v0, v1, 0x7632);
    f[2] = __byte_perm(v2, v3, 0x5410); f[3] = __byte_perm(v2, v3, 0x7632);
    if (HALF) {
        #pragma unroll
        for (int i = 0; i < 4; i++) asm("mul.rn.bf16x2 %0, %0, %1;" : "+r"(f[i]) : "r"(0x3F003F00u));
    }
}

template<int NP>
__device__ __forceinline__ void epi_fast(const float* g, const float* h, float m1, float m2,
                                         float& n0, float& d0, float& n1, float& d1, float& dmin)
{
    constexpr int JC = NP >= 6 ? NP - 3 : NP >= 4 ? NP - 2 : NP - 1;
    constexpr int JT = NP < 3 ? -1 : JC < NP - 1 ? JC : NP - 2;
    #pragma unroll
    for (int j = 0; j < NP; j++) {
        float t0 = tanhf_a(g[4*j+0]), t1 = tanhf_a(g[4*j+1]), t2 = tanhf_a(g[4*j+2]), t3 = tanhf_a(g[4*j+3]);
        auto add_d = [&]() {
            if (j == 0) { d0 = t0 + (2.f * (JT + 1) + EPS2); d1 = t2 + (2.f * (JT + 1) + EPS2); } else { d0 += t0; d1 += t2; }
            d0 += t1; d1 += t3;
        };
        if (j <= JT) add_d();
        if (j == NP - 1) { t0 = fmaf(t0, m1, m1); t1 = fmaf(t1, m2, m2); t2 = fmaf(t2, m1, m1); t3 = fmaf(t3, m2, m2); }
        else { t0 += 1.f; t1 += 1.f; t2 += 1.f; t3 += 1.f; }
        if (j > JT) add_d();
        if (j == 0) { n0 = t0 * h[0]; n1 = t2 * h[2]; } else { n0 = fmaf(t0, h[4*j], n0); n1 = fmaf(t2, h[4*j+2], n1); }
        n0 = fmaf(t1, h[4*j+1], n0); n1 = fmaf(t3, h[4*j+3], n1);
        if (j == JC) dmin = fminf(d0, d1);
    }
}

__device__ __noinline__ float4 epi_exact(const float4* gh, int np, int dv)
{
    float n0 = 0.f, d0 = EPS2, n1 = 0.f, d1 = EPS2;
    #pragma unroll 2
    for (int j = 0; j < np; j++) {
        const float4 g = gh[j], h = gh[NPMAX + j];
        const float ma = (2 * j < dv) ? 2.f : 0.f, mb = (2 * j + 1 < dv) ? 2.f : 0.f;
        const float e0 = ma * rcpf(1.f + ex2f(-2.f * LOG2E * g.x)), e1 = mb * rcpf(1.f + ex2f(-2.f * LOG2E * g.y));
        const float e2 = ma * rcpf(1.f + ex2f(-2.f * LOG2E * g.z)), e3 = mb * rcpf(1.f + ex2f(-2.f * LOG2E * g.w));
        d0 += e0 + e1; n0 = fmaf(e0, h.x, fmaf(e1, h.y, n0));
        d1 += e2 + e3; n1 = fmaf(e2, h.z, fmaf(e3, h.w, n1));
    }
    return make_float4(n0, d0, n1, d1);
}
template<int NP>
__device__ __forceinline__ void epi_dump(const float* g, const float* h, float4* gh) {
    #pragma unroll
    for (int i = 0; i < NP; i++) {
        gh[i] = make_float4(g[4*i], g[4*i+1], g[4*i+2], g[4*i+3]);
        gh[NPMAX + i] = make_float4(h[4*i], h[4*i+1], h[4*i+2], h[4*i+3]);
    }
}

__device__ __noinline__ void slow_bin(const __nv_bfloat16* x, const __nv_bfloat16* ea, const int* src, const int* dst,
                                      const __nv_bfloat16* wa, const __nv_bfloat16* wb, const __nv_bfloat16* wc,
                                      const __nv_bfloat16* wu, const __nv_bfloat16* wv, __nv_bfloat16* out,
                                      int E, int node0, int nn, int nthr)
{
    const int tid = threadIdx.x, lane = tid & 31;
    for (int i = tid; i < nn * 128; i += nthr) g_slow[(size_t)node0 * 128 + i] = 0.f;
    asm volatile("bar.sync 1, %0;" :: "r"(nthr) : "memory");
    for (int e0 = (tid >> 5) * 32; e0 < E; e0 += nthr) {
        int d = (e0 + lane < E) ? dst[e0 + lane] - node0 : -1;
        unsigned m = __ballot_sync(~0u, d >= 0 && d < nn);
        while (m) {
            int l = __ffs(m) - 1; m &= m - 1;
            int e = e0 + l, n = node0 + __shfl_sync(~0u, d, l), s = src[e];
            float g0 = 0, g1 = 0, h0 = 0, h1 = 0;
            for (int k = 0; k < 64; k++) {
                float xs = __bfloat162float(x[(size_t)s * 64 + k]), xd = __bfloat162float(x[(size_t)n * 64 + k]);
                uint32_t b2 = *(const uint32_t*)(wb + k * 64 + 2 * lane), v2 = *(const uint32_t*)(wv + k * 64 + 2 * lane);
                uint32_t a2 = *(const uint32_t*)(wa + k * 64 + 2 * lane);
                g0 = fmaf(xs, bf_lo(b2), fmaf(xd, bf_lo(a2), g0)); g1 = fmaf(xs, bf_hi(b2), fmaf(xd, bf_hi(a2), g1));
                h0 = fmaf(xs, bf_lo(v2), h0); h1 = fmaf(xs, bf_hi(v2), h1);
            }
            for (int k = 0; k < 16; k++) {
                float ev = __bfloat162float(ea[(size_t)e * 16 + k]);
                uint32_t c2 = *(const uint32_t*)(wc + k * 64 + 2 * lane);
                g0 = fmaf(ev, bf_lo(c2), g0); g1 = fmaf(ev, bf_hi(c2), g1);
            }
            float s0 = rcpf(1.f + ex2f(-LOG2E * g0)), s1 = rcpf(1.f + ex2f(-LOG2E * g1));
            float* acc = g_slow + (size_t)n * 128 + 4 * lane;
            atomicAdd(acc + 0, s0 * h0); atomicAdd(acc + 1, s0);
            atomicAdd(acc + 2, s1 * h1); atomicAdd(acc + 3, s1);
        }
    }
    __threadfence();
    asm volatile("bar.sync 1, %0;" :: "r"(nthr) : "memory");
    for (int i = tid; i < nn * 32; i += nthr) {
        int n = node0 + (i >> 5), cp = i & 31;
        float4 a = __ldcg((const float4*)(g_slow + (size_t)n * 128 + 4 * cp));
        float u0 = 0, u1 = 0;
        for (int k = 0; k < 64; k++) {
            float xd = __bfloat162float(x[(size_t)n * 64 + k]);
            uint32_t w2 = *(const uint32_t*)(wu + k * 64 + 2 * cp);
            u0 = fmaf(xd, bf_lo(w2), u0); u1 = fmaf(xd, bf_hi(w2), u1);
        }
        uint32_t xv = *(const uint32_t*)(x + (size_t)n * 64 + 2 * cp);
        float z0 = u0 + a.x / (a.y + 1e-6f), z1 = u1 + a.z / (a.w + 1e-6f);
        *(uint32_t*)(out + (size_t)n * 64 + 2 * cp) = pack_bf16(bf_lo(xv) + fmaxf(z0, 0.f), bf_hi(xv) + fmaxf(z1, 0.f));
    }
}

__global__ void __launch_bounds__(256) slow_kernel(const __nv_bfloat16* x, const __nv_bfloat16* ea, const int* src, const int* dst,
        const __nv_bfloat16* wa, const __nv_bfloat16* wb, const __nv_bfloat16* wc, const __nv_bfloat16* wu, const __nv_bfloat16* wv,
        __nv_bfloat16* out, int N, int E, int npb)
{
    int node0 = blockIdx.x * npb;
    slow_bin(x, ea, src, dst, wa, wb, wc, wu, wv, out, E, node0, max(0, min(npb, N - node0)), 256);
}

constexpr int XS_BYTES = NPMAX * 1024;
constexpr int ES_BYTES = NPMAX * 256;
constexpr int SM_XS = 0;
constexpr int SM_XU = SM_XS + 3 * NSTAGE * XS_BYTES;
constexpr int SM_TAB = SM_XU + NPB_MAX * 128;
constexpr int SM_ES = SM_TAB + (NPB_MAX + 2) * 128;
constexpr int SM_WC = SM_ES + 3 * NSTAGE * ES_BYTES;
constexpr int SM_OH = SM_WC + 2048;
constexpr int SM_EID = SM_OH + 256;
constexpr int SM_SRC = SM_EID + (SLOT_CAP + 32) * 4;
constexpr int SM_TINFO = SM_SRC + (SLOT_CAP + 32) * 2;
constexpr int SM_MISC = SM_TINFO + TILE_CAP * 32;
constexpr int SM_CLAIM = SM_TAB + (NPB_MAX + 1) * 128;
constexpr int SM_BARS = SM_MISC + 32 * 4;
constexpr int SM_ABAR = SM_BARS + 6 * 48;
constexpr int SM_XBAR = SM_ABAR + 10 * 8;
constexpr int SM_SBAR = SM_XBAR + 4 * 8;
constexpr int SM_GBAR = SM_SBAR + 3 * 8;
constexpr int SM_WL = SM_GBAR + 97 * 8;
constexpr int WST = 9;
constexpr int SMEM_BYTES = SM_WL + (96 + WST) * 8;
constexpr int SM_P2 = 0, SM_P1 = 6 * 384 * 16;
constexpr int SM_DEG = SM_P1 + P1B;
constexpr int SM_CNT = SM_DEG + 512 * 4;
constexpr int SM_CLS = SM_CNT + 512 * 4;
constexpr int SM_HIST = SM_CLS + NCLS * 4;
constexpr int SM_XLIST = SM_HIST + 136 * 4;
constexpr int SM_SORT = SM_XLIST + XCAP * 8;
constexpr int SM_BASE = SM_SORT + NPB_MAX * 4;
constexpr int SM_PAIR = SM_BASE + (NPB_MAX + 4) * 2;
constexpr int SM_IDX = SM_EID;
constexpr int SM_WR = SM_TAB;
static_assert(TILE_CAP <= 128 && TR >= 2 && SM_ES % 256 == 0 && NSTAGE == 2 && SM_BARS % 16 == 0 && SM_TINFO % 16 == 0 && SM_EID % 128 == 0 && SM_TAB % 1024 == 0 && SM_XU % 1024 == 0 && SM_TINFO % 8 == 0 && SM_OH % 16 == 0 && SM_SORT % 16 == 0 && SM_PAIR % 8 == 0, "align");
static_assert(P1B % 16 == 0 && P2B <= SM_P1 && NB_MAX <= 6 * 24 && SM_PAIR + 128 * 8 <= SM_XU && CH_MAX * 4 <= SM_SRC - SM_EID && SM_DEG >= 3 << 14, "alias");
static_assert(SMEM_BYTES <= 232448, "smem");
constexpr uint32_t C_BRK = 16  , C_CONT = 32, C_MORE = 64;
constexpr uint32_t ONE_F = 0x3F800000u;
constexpr int NONE = NPB_MAX;

__device__ __forceinline__ uint2 tile_info(uint32_t e) {
    const uint32_t y = (uint32_t)((int)e >> 16) & (ONE_F | 0x1FFFu);
    return make_uint2(e, (e & 0x1F000000u) ? y | 0x80000000u : y);
}
__device__ __forceinline__ bool unpad(uint32_t w1, int np, float ga, float gb, float& d0, float& d1, int& dv) {
    const int pad = (int)w1 < 0 ? (w1 >> 8) & 31 : 0;
    dv = 2 * np - 2 - pad + ((int)w1 > 127) + ((int)w1 >= (int)ONE_F);
    float t0 = TAU * 2 * np, t1 = t0;
    if (pad) {
        t0 = fmaxf(t0, d0 * (1.f / 1024)); t1 = fmaxf(t1, d1 * (1.f / 1024));
        asm volatile("tanh.approx.f32 %0, %0;\ntanh.approx.f32 %1, %1;" : "+f"(ga), "+f"(gb));
        d0 -= pad * (1.f + ga); d1 -= pad * (1.f + gb);
    }
    if (dv == 0) { d0 = d1 = EPS2; t0 = t1 = 0.f; }
    return __any_sync(~0u, d0 < t0 || d1 < t1);
}
__device__ __forceinline__ uint64_t desc_sw128(uint32_t a) {
    return (uint64_t)((a & 0x3FFFF) >> 4) | ((uint64_t)1 << 16) | ((uint64_t)64 << 32) | ((uint64_t)1 << 62);
}

__device__ __forceinline__ uint32_t sel(bool c, uint32_t a, uint32_t b) {
    uint32_t r; asm("{\n.reg .pred p;\nsetp.ne.u32 p, %1, 0;\nselp.b32 %0, %2, %3, p;\n}" : "=r"(r) : "r"((uint32_t)c), "r"(a), "r"(b)); return r;
}
__device__ __forceinline__ void tile_entry(uint8_t* smem, uint32_t sv, int dg, int mn, int t, int tl, int np, int done, uint32_t flags, int next) {
    const uint32_t nd = sv & 0xFFFF, w0 = nd * 128 + ((nd & 7) << 4);
    const int dv = min(max(dg - done, 0), 2 * np), r = 2 * np - dv;
    const bool gen = mn - done < 2 * np - 2;
    const uint32_t w1 = (uint32_t)np | flags | sel(gen || flags, C_BRK, 0u) | sel(r < 2, 0x8000u >> (8 * r), (r - 2) << 8);
    *(uint2*)(smem + SM_TINFO + tl * 32 + t * 8) = make_uint2(sel(dv, (sv >> 16) + done, 0) | (sel(gen, 13 + (np > 5) + (np > 8), np) << 16) | (next << 20) | ((uint32_t)dv << 27), w0 | sel(np, w1 << 16, 0u));
}
__device__ __noinline__ void tiles_many(uint8_t* smem, uint32_t sv, int dg, int mn, int id, int left, unsigned sm) {
    int* misc = (int*)(smem + SM_MISC);
    int nt = (left + NPMAX - 1) / NPMAX, tl = id >> 2, done = 0, nx = 0;
    if ((id & 3) == 0) { nx = atomicAdd(&misc[5], nt - 1); if (nx + nt - 1 > TILE_CAP) misc[1] = 1; }
    nx = __shfl_sync(sm, nx, id & 28);
    if (nx + nt - 1 > TILE_CAP) left = 0;
    uint32_t cont = 0;
    #pragma unroll 1
    while (left > 0) {
        const int np = (left + nt - 1) / nt;
        left -= np; nt--;
        tile_entry(smem, sv, dg, mn, id & 3, tl, np, done, cont | (left > 0 ? C_MORE : 0u), left > 0 ? nx : 0);
        tl = nx++; cont = C_CONT; done += 2 * np;
    }
}
__device__ __forceinline__ void tables(uint8_t* smem, uint32_t sbase, int id0, int ngroups) {
    const int t = id0 & 3;
    uint4 s4[3];
    uint32_t me[3], sv[3];
    #pragma unroll
    for (int k = 0; k < 3; k++) { s4[k] = lds128(sbase + SM_SORT + (id0 & ~3) * 4 + k * 512); me[k] = lds32(sbase + SM_SORT + id0 * 4 + k * 512); }
    #pragma unroll
    for (int k = 0; k < 3; k++) asm volatile("ld.shared.u16 %0, [%1];" : "=r"(sv[k]) : "r"(sbase + SM_BASE + (me[k] & 0xFFFF) * 2) : "memory");
    int mn[3], left[3];
    uint32_t more = 0;
    #pragma unroll
    for (int k = 0; k < 3; k++) {
        const int g = (id0 >> 2) + 32 * k, nx = ngroups + 4 + g;
        sv[k] = sv[k] << 16 | (me[k] & 0xFFFF);
        mn[k] = min(min(s4[k].x, s4[k].y), min(s4[k].z, s4[k].w)) >> 16;
        left[k] = ((max(max(s4[k].x, s4[k].y), max(s4[k].z, s4[k].w)) >> 16) + 1) >> 1;
        const bool two = left[k] > NPMAX;
        more |= two << k;
        tile_entry(smem, sv[k], me[k] >> 16, mn[k], t, sel(g >= ngroups + 4, ngroups, g), sel(two, min((left[k] + 1) >> 1, NPMAX), sel(left[k], max(left[k], NPMIN), 0)), 0, sel(two, C_MORE, 0u), sel(two, nx & 127, 0));
    }
    #pragma unroll 1
    for (int id = id0; __any_sync(~0u, more); id += 128) {
        const int nx = ngroups + 4 + (id >> 2);
        const bool odd = left[0] > 2 * NPMAX || ((more & 1) && nx >= TILE_CAP - TILE_X);
        const unsigned sm = __ballot_sync(~0u, odd);
        if (__builtin_expect(odd, 0)) tiles_many(smem, sv[0], me[0] >> 16, mn[0], id, left[0], sm);
        else if (more & 1) tile_entry(smem, sv[0], me[0] >> 16, mn[0], t, nx, left[0] >> 1, (left[0] + 1) & ~1, C_CONT, 0);
        __syncwarp();
        more >>= 1;
        sv[0] = sv[1]; sv[1] = sv[2]; me[0] = me[1]; me[1] = me[2]; mn[0] = mn[1]; mn[1] = mn[2]; left[0] = left[1]; left[1] = left[2];
    }
}
__device__ __forceinline__ uint32_t to_list(uint32_t sbase, uint32_t e, uint32_t bin) {
    uint32_t j; asm volatile("atom.shared.inc.u32 %0, [%1], 0x7fffffff;" : "=r"(j) : "r"(sbase + SM_MISC + 8) : "memory");
    j = min(j, 63u);
    sts32(sbase + SM_P1 + j * 4, e | ((j < 63 ? bin : 255u) << 16));
    return j;
}

template<bool LO32>
__global__ void __launch_bounds__(THREADS, 1)
gcn_kernel(const int* __restrict__ dst, unsigned* gbar, char* gs, const int* __restrict__ src, int E, int ch, int N, int npb, uint32_t magic,
           const __nv_bfloat16* __restrict__ x, const __nv_bfloat16* __restrict__ ea,
           const __nv_bfloat16* __restrict__ wa, const __nv_bfloat16* __restrict__ wb, const __nv_bfloat16* __restrict__ wc,
           const __nv_bfloat16* __restrict__ wu, const __nv_bfloat16* __restrict__ wv,
           __nv_bfloat16* out, int4 wrow, const __grid_constant__ CUtensorMap tm2, const __grid_constant__ CUtensorMap tmw,
           const __grid_constant__ CUtensorMap tmc, const __grid_constant__ CUtensorMap tmx)
{
    extern __shared__ __align__(1024) uint8_t smem[];
    int* cls = (int*)(smem + SM_CLS);
    int* misc = (int*)(smem + SM_MISC);
    uint32_t* xlist = (uint32_t*)(smem + SM_XLIST);
    WG0(); WS(0); ZS(0);
    const uint32_t sbase = smem_u32(smem);
    const int tid = threadIdx.x, lane = tid & 31;
    const int b = blockIdx.x, nb = gridDim.x;
    const int cnt = max(0, min(ch, E - b * ch));
    const int node0 = b * npb;
    auto src_ld = [&](int v) { bulk_ld(sbase + SM_XU + v * 8192, src + b * ch + v * 2048, min(max(cnt * 4 - v * 8192, 0), 8192), sbase + SM_SBAR + v * 8); };
    auto dst_ld = [&](int v) { bulk_ld(sbase + SM_IDX + v * 8192, dst + b * ch + v * 2048, min(max(cnt * 4 - v * 8192, 0), 8192), sbase + SM_ABAR + v * 8); };
    auto box_ld = [&](uint32_t dst, const CUtensorMap* tm, int col, int row, uint32_t bar) {
        asm volatile("cp.async.bulk.tensor.2d.shared::cluster.global.mbarrier::complete_tx::bytes [%0], [%1, {%3, %4}], [%2];"
            :: "r"(dst), "l"((uint64_t)tm), "r"(bar), "r"(col), "r"(row) : "memory");
    };
    auto w_ld = [&]() {
        mbar_expect(sbase + SM_ABAR + 24, 272 * 128);
        box_ld(sbase + SM_WR, &tmw, 0, wrow.y, sbase + SM_ABAR + 24); box_ld(sbase + SM_WR + 64 * 128, &tmc, 0, 0, sbase + SM_ABAR + 24);
        box_ld(sbase + SM_WR + 80 * 128, &tmw, 0, wrow.w, sbase + SM_ABAR + 24); box_ld(sbase + SM_WR + 144 * 128, &tmw, 0, wrow.x, sbase + SM_ABAR + 24);
        box_ld(sbase + SM_WR + 208 * 128, &tmw, 0, wrow.z, sbase + SM_ABAR + 24);
    };
    auto x_ld = [&](int k) {
        mbar_expect(sbase + SM_XBAR + k * 8, 16384);
        box_ld(sbase + SM_XU + k * 16384, &tmx, 0, node0 + 128 * k, sbase + SM_XBAR + k * 8);
    };
    uint32_t tag = 0;
    if (tid < 32) asm volatile("ld.relaxed.gpu.global.u32 %0, [%1];" : "=r"(tag) : "l"(gbar));
    if (tid >> 5 == 11) {
        if (elect_one()) {
            mbar_init(sbase + SM_ABAR, 1);
            asm volatile("fence.mbarrier_init.release.cluster;" ::: "memory");
            dst_ld(0);
        }
    }
    if (tid >= 384) {
        if (elect_one()) {
            const int v = (tid >> 5) & 3;
            if (v) mbar_init(sbase + SM_ABAR + v * 8, 1);
            asm volatile("fence.mbarrier_init.release.cluster;" ::: "memory");
            if (v == 1) dst_ld(v);
            if (v == 3) {
                mbar_init(sbase + SM_ABAR + 40, 1); mbar_init(sbase + SM_GBAR + 96 * 8, 32); mbar_init(sbase + SM_ABAR + 72, 384); mbar_init(sbase + SM_XBAR + 24, 512);
            }
            #pragma unroll 1
            for (int j = 0; j < 3; j++) {
                #pragma unroll
                for (int i = 0; i < 8; i++) mbar_init(sbase + SM_GBAR + (v * 24 + j * 8 + i) * 8, 32);
                if (j == 1 && v == 2) dst_ld(v);
            }
            if (tid < 480) {
                #pragma unroll
                for (int i = 0; i < 2; i++) { mbar_init(sbase + SM_BARS + (v * 2 + i) * 48, 64); mbar_init(sbase + SM_BARS + (v * 2 + i) * 48 + 8, 128); }
                mbar_init(sbase + SM_ABAR + 48 + v * 8, 128); mbar_init(sbase + SM_XBAR + v * 8, 1); mbar_init(sbase + SM_SBAR + v * 8, 1);
            }
            asm volatile("fence.mbarrier_init.release.cluster;" ::: "memory");
        }
    }
    if (tid >= 128 && tid < 132) asm volatile("prefetch.tensormap [%0];" :: "l"((uint64_t)(tid == 128 ? &tmw : tid == 129 ? &tmc : tid == 130 ? &tm2 : &tmx)) : "memory");
    const int warp = (int)__reduce_max_sync(~0u, (unsigned)tid >> 5);
    const int wg = warp >> 2, w = warp & 3;
    const int q = lane >> 2, t = lane & 3;
    const int ch0 = 16 * w + 2 * q;
    const int nn = max(0, min(npb, N - node0));
    if (sbase & 1023) __trap();

    sts32(sbase + (tid < NPB_MAX ? SM_DEG : SM_CNT) + tid * 4, tid < NPB_MAX ? 0 : 0xC0000000u);
    if (tid < NCLS + NB_MAX) cls[tid] = tid < NCLS ? 0 : (tid - NCLS) * CE + 64;
    else if (wg == 2) {
        if (w < 2) {
            *(uint32_t*)(smem + SM_OH + (tid & 63) * 4) = t != (q >> 1) ? 0u : (w == 0 ? 0x00003F00u : 0x3F000000u);
        } else if (w == 2) *(uint32_t*)(smem + SM_TAB + NPB_MAX * 128 + lane * 4) = 0u;
        else misc[lane] = lane == 5 ? TILE_CAP - TILE_X : 0;
    }
    if (warp == 13 && lane < WST * 2) sts32(sbase + SM_WL + 768 + lane * 4, NONE * 0x10001u);
    if (warp == 14) sts32(sbase + SM_TINFO + 96 * 32 + lane * 4, 0);
    if (warp == 15) sts32(sbase + SM_CLAIM + lane * 4, lane == 0 ? 3 : 0x40000000);
    if (wg < 3) {
        #pragma unroll 1
        for (int i = tid; i < P2B / 32; i += 384) { sts128(sbase + SM_P2 + i * 16, make_uint4(0, 0, 0, 0)); sts128(sbase + SM_P2 + P2B / 2 + i * 16, make_uint4(0, 0, 0, 0)); }
    }
    if (tid == 0) sts32(sbase + SM_PAIR, tag);
    if (wg < 3) { asm volatile("bar.sync 1, 384;" ::: "memory"); tag = lds32(sbase + SM_PAIR); }
    tag = (tag & 1) | 2;
    if (wg < 3) {
        const uint32_t d0 = ((NPB_MAX + ((2 * lane) & 15) + 16 * (b & 1)) * 4 | (tag << 14)) * 0x10001u, d1 = d0 + 0x40004u;
        #pragma unroll
        for (int i = 0; i < 3; i++) if (i < 2 || tid + 768 < P1B / 16) sts128(sbase + SM_P1 + (tid + 384 * i) * 16, make_uint4(d0, d0, d1, d1));
    }
    if (warp == 15 && elect_one()) w_ld();
    WS(1); ZS(1);
    __syncthreads();
    if (wg == 3) tag = (lds32(sbase + SM_PAIR) & 1) | 2;

    uint32_t ent[EPT];
    #pragma unroll
    for (int v = 0; v < EPT / 4; v++) {
        mbar_wait_c(sbase + SM_ABAR + v * 8, 0);
        if (v == 0) ZS(2);
        if (((v == 0 && (warp == 13 || warp == 14)) || (v == 1 && warp == 15)) && elect_one()) src_ld(warp - 13);
        const uint32_t off = v * (THREADS * 4) + tid * 4;
        if (off < (uint32_t)cnt) {
            const uint32_t ia = sbase + SM_IDX + off * 4;
            const uint4 u = lds128(ia);
            uint32_t dv[4] = {u.x, u.y, u.z, u.w}, ps[4], ck[4];
            uint32_t* en = ent + 4 * v;
            #pragma unroll
            for (int k = 0; k < 4; k++) {
                dv[k] = min(dv[k], (uint32_t)(nb * npb - 1));
                ps[k] = __umulhi(dv[k], magic); en[k] = atoms_inc(sbase + SM_HIST + ps[k] * 4);
            }
            #pragma unroll
            for (int k = 0; k < 4; k++) {
                dv[k] = (dv[k] - ps[k] * npb) * 4 + (tag << 14);
                ck[k] = en[k] - ps[k] * CE;
                en[k] ^= ps[k] * 4 & 60;
            }
            if (__builtin_expect(max(max(ck[0], ck[1]), max(ck[2], ck[3])) >= 64 + CE, 0)) {
                #pragma unroll
                for (int k = 0; k < 4; k++) if (ck[k] >= 64 + CE) en[k] = to_list(sbase, dv[k], ps[k]);
            }
            #pragma unroll
            for (int k = 0; k < 4; k++)
                asm volatile("{\n.reg .pred p;\nsetp.ge.u32 p, %2, 64;\n@p st.shared.u16 [%0], %1;\n}" :: "r"(sbase + SM_P1 + 128 + en[k] * 2), "r"(dv[k]), "r"(en[k]) : "memory");
        }
    }
    WS(5); ZS(3);
    __syncthreads();
    auto send = [&](int o, uint32_t a, int bytes) {
        if (warp == 14 && elect_one()) {
            asm volatile("fence.proxy.async.shared::cta;" ::: "memory");
            bulk_st(gs + b * (P1B + P2B) + o, a, bytes);
            asm volatile("cp.async.bulk.commit_group;" ::: "memory");
        }
    };
    send(0, sbase + SM_P1, 256 + nb * (CE * 2));
    #pragma unroll
    for (int v = 0; v < EPT / 4; v++) {
        mbar_wait_c(sbase + SM_SBAR + v * 8, 0);
        const uint32_t off = v * (THREADS * 4) + tid * 4;
        if (off < (uint32_t)cnt) {
            const uint4 sv = lds128(sbase + SM_XU + off * 4);
            const uint32_t ss[4] = {sv.x, sv.y, sv.z, sv.w};
            #pragma unroll
            for (int k = 0; k < 4; k++) sts32(sbase + SM_P2 + ent[4*v+k] * 4, (ss[k] & 0xFFFF) | (((off + k) << 19) + (tag << 16)));
        }
    }
    WS(7); ZS(4);
    __syncthreads();
    send(P1B, sbase + SM_P2, 256 + nb * (CE * 4));
    WSL(8);

    const int ngroups = (nn + 3) >> 2;
    if (wg == 3) {
        asm volatile("setmaxnreg.dec.sync.aligned.u32 56;");
        WS(2);
        const char* const ga = as_pair((const char*)x + (w < 3 ? 0 : (size_t)node0 * 128) + (lane & 7) * 16, sbase + SM_PAIR + (tid & 127) * 8);
        const char* const gb = as_pair(w < 3 ? (const char*)ea + (lane & 1) * 16 : (const char*)out + (size_t)node0 * 128 + (lane & 7) * 16, sbase + SM_PAIR + (tid & 127) * 8);
        WS(3);
        const uint32_t dm = ((NPB_MAX + lane) * 4 | (tag << 14)) * 0x10001u;
        const uint32_t db = sbase + SM_DEG - (tag << 14);
        const char* gl = gs + ((tid & 127) >> 2) * (P1B + P2B) + t * 16;
        uint4 rl[5];
        #pragma unroll
        for (int i = 0; i < 5; i++) rl[i].w = ((tid & 127) >> 2) + 32 * i < nb ? 0 : dm;
        auto p2_ld = [&]() {
            mbar_expect(sbase + SM_ABAR + 40, nb * (CE * 4));
            box_ld(sbase + SM_P2, &tm2, P1B / 4 + 64 + b * CE, 0, sbase + SM_ABAR + 40);
        };
        asm volatile("cp.async.bulk.wait_group.read 0;" ::: "memory");
        asm volatile("bar.sync 6, 128;" ::: "memory");
        WSL(12);
        uint32_t spins = 0;
        #pragma unroll 1
        for (int r = 0;; r++) {
            #pragma unroll
            for (int i = 0; i < 5; i++) rl[i].x = rl[i].y = rl[i].z = dm;
            while (true) {
                #pragma unroll
                for (int i = 0; i < 5; i++) ld_unit(rl[i], gl + i * (32 * (P1B + P2B)), (rl[i].w ^ dm) & 0xC000);
                if (spins == 0) asm volatile("bar.sync 5, 512;" ::: "memory");
                if (++spins > (1u << 22)) __trap();
                if (!__any_sync(~0u, ((rl[0].w ^ dm) | (rl[1].w ^ dm) | (rl[2].w ^ dm) | (rl[3].w ^ dm) | (rl[4].w ^ dm)) & 0xC000)) break;
            }
            WS(4);
            uint32_t own = 0;
            #pragma unroll
            for (int i = 0; i < 5; i++) {
                const uint32_t bb = b << 16;
                own |= (min(min(rl[i].x ^ bb, rl[i].y ^ bb), min(rl[i].z ^ bb, rl[i].w ^ bb)) < 0x10000u) << i;
            }
            while (own != 0) {
                const int i = __ffs(own) - 1; own &= own - 1;
                const uint4 u = i == 0 ? rl[0] : i == 1 ? rl[1] : i == 2 ? rl[2] : i == 3 ? rl[3] : rl[4];
                const uint32_t e[4] = {u.x ^ (b << 16), u.y ^ (b << 16), u.z ^ (b << 16), u.w ^ (b << 16)};
                const uint32_t s = (((tid & 127) >> 2) + 32 * i << 16) + (4 * r + t << 26);
                int n;
                asm volatile("atom.shared.add.u32 %0, [%1], %2;" : "=r"(n) : "r"(sbase + SM_MISC), "r"((e[0] < 0x10000u) + (e[1] < 0x10000u) + (e[2] < 0x10000u) + (e[3] < 0x10000u)) : "memory");
                #pragma unroll
                for (int k = 0; k < 4; k++) asm volatile("red.shared.add.u32 [%0], 1;" :: "r"(db + min(e[k], dm & 0xFFFF)) : "memory");
                if (n + 4 > XCAP) { misc[1] = 1; n = 0; }
                #pragma unroll
                for (int k = 0; k < 4; k++) if (e[k] < 0x10000u) xlist[n++] = e[k] | (s + (k << 24));
            }
            __syncwarp();
            if (__builtin_expect(!__any_sync(~0u, t == 3 && min(min(min(rl[0].w, rl[1].w), min(rl[2].w, rl[3].w)), rl[4].w) < 0x1000000u), 1)) break;
            if (r == 3) { misc[1] = 1; break; }
            #pragma unroll
            for (int i = 0; i < 5; i++) rl[i].w = __shfl_sync(~0u, rl[i].w, lane | 3) < 0x1000000u ? 0 : dm;
            gl += 64;
        }
        WS(11); ZS(5);
        asm volatile("bar.sync 7, 512;" ::: "memory");
        auto rest_ld = [&]() {
            if (w == 2 && elect_one()) {
                p2_ld(); x_ld(2);
            }
            __syncwarp();
        };
        WS(9);
        {
            int dg[3], cl[3], cr[3];
            #pragma unroll
            for (int k = 0; k < 3; k++) dg[k] = lds32(sbase + SM_DEG + ((tid & 127) + 128 * k) * 4);
            const uint2 m01 = lds64(sbase + SM_MISC);
            const int xi = (tid + 96) & 127, nx = m01.y ? 0 : m01.x;
            const uint32_t xe = xlist[xi];
            #pragma unroll
            for (int k = 0; k < 3; k++) {
                cl[k] = NCLS - 1 - (dg[k] <= 40 ? dg[k] : min(41 + ((dg[k] - 41) >> 3), NCLS - 1));
                cr[k] = atoms_inc(sbase + ((tid & 127) + 128 * k < nn ? SM_CLS + cl[k] * 4 : SM_DEG + NPB_MAX * 4));
            }
            rest_ld(); ZS(6);
            asm volatile("bar.sync 6, 128;" ::: "memory");
            WS(13);
            const uint2 c = lds64(sbase + SM_CLS + lane * 8);
            uint32_t inc = c.x + c.y;
            #pragma unroll
            for (int o = 1; o < 32; o <<= 1) { const uint32_t y = __shfl_up_sync(~0u, inc, o); if (lane >= o) inc += y; }
            inc = (inc - c.x - c.y) | (inc - c.y) << 16;
            #pragma unroll
            for (int k = 0; k < 3; k++) {
                const int id = (tid & 127) + 128 * k;
                const uint32_t e = __shfl_sync(~0u, inc, cl[k] >> 1);
                const uint32_t pos = id < nn ? (cl[k] & 1 ? e >> 16 : e & 0xFFFF) + cr[k] : id, nd = id < nn ? id : NONE;
                sts32(sbase + SM_SORT + pos * 4, nd | min(dg[k], 65535) << 16);
                asm volatile("st.shared.u16 [%0], %1;" :: "r"(sbase + SM_WL + pos * 2), "r"(nd) : "memory");
            }
            if (tid == 511) misc[4] = (nn - c.y + 3) >> 2;
            asm volatile("bar.sync 4, 512;" ::: "memory");
            WS(14);
            uint32_t xs = 0x80000000u, xv = tag << 16;
            auto x_get = [&]() { asm volatile("ld.relaxed.gpu.global.u32 %0, [%1];" : "=r"(xv) : "l"(gs + ((xe >> 16) & 0xFF) * (P1B + P2B) + P1B + (xe >> 24) * 4) : "memory"); };
            if (xi < nx) {
                asm volatile("atom.shared.add.u32 %0, [%1], 4;" : "=r"(xs) : "r"(db + (SM_CNT - SM_DEG) + (xe & 0xFFFF)) : "memory");
                x_get();
            }
            ZS(7);
            tables(smem, sbase, (tid + 32) & 127, ngroups);
            __syncwarp();
            while (__any_sync(~0u, ((xv >> 16) & 3) != tag)) { if (((xv >> 16) & 3) != tag) x_get(); if (++spins > (1u << 22)) __trap(); }
            if (xs < 4 * SLOT_CAP) {
                sts32(sbase + SM_EID + xs, ((xe >> 16) & 0xFF) * ch + (xv >> 19));
                asm volatile("st.shared.u16 [%0], %1;" :: "r"(sbase + SM_SRC + (xs >> 1)), "r"(xv) : "memory");
            }
            mbar_arrive(sbase + SM_XBAR + 24);
            asm volatile("bar.sync 6, 128;" ::: "memory");
        }
        WS(10); ZS(8);
        WGD();
        const int r4 = lane >> 3, c8 = lane & 7;
        const uint32_t sb = __reduce_or_sync(~0u, sbase);
        if (w < 3) {
            const char* gx = ga; const char* ge = gb;
            const uint32_t gx0 = (uint32_t)(uint64_t)gx, ge0 = (uint32_t)(uint64_t)ge, hi = (uint64_t)gx >> 32, he = (uint64_t)ge >> 32;
            const int s = (lane >> 1) & 3;
            const uint32_t xs0 = sb + SM_XS + w * NSTAGE * XS_BYTES;
            const uint32_t es0 = sb + SM_ES + w * NSTAGE * ES_BYTES + r4 * 64 + (((lane ^ (r4 >> 1)) & 1) << 4) + (s >> 1) * 256 + (s & 1) * 32;
            const uint32_t bars = sb + SM_BARS + w * 96;
            const uint32_t xoffA = (2 * r4) * 128 + ((c8 ^ (2 * r4)) << 4), xoffB = (2 * r4 + 1) * 128 + ((c8 ^ (2 * r4 + 1)) << 4);
            uint64_t pol;
            asm volatile("createpolicy.fractional.L2::evict_first.b64 %0, 1.0;" : "=l"(pol));
            uint32_t first = 1;
            WS(15);
            uint32_t ph = 1, cur = w;
            uint32_t hist = 96 * 0x010101u;
            auto done3 = [&]() { mbar_arrive(sb + SM_GBAR + ((hist >> 16) & 0xFF) * 8); };
            const uint32_t ca = sb + SM_CLAIM + lane * 4, pa = sb + SM_TINFO + r4 * 8;
            const uint2 p0 = lds64(pa + w * 32);
            const bool go = lds32(sb + SM_MISC + 4) == 0 && nn > 0;
            uint32_t pw = go ? p0.x : 0, brk = (p0.y >> 16) & C_BRK;
            const uint32_t se0 = sb + SM_EID + s * 4, xab = xoffB - xoffA, das = 2 * (xs0 + xoffA) + XS_BYTES, des = 2 * es0 + ES_BYTES, brs = 2 * bars + 48;
            uint32_t da = xs0 + xoffA, de = es0, br = bars;
            #pragma unroll 1
            while (true) {
                const uint32_t pt = __reduce_or_sync(~0u, pw);
                uint32_t se, sx;
                asm("dp2a.lo.u32.u32 %0, %1, 4, %2;" : "=r"(se) : "r"(pw), "r"(se0));
                asm("dp2a.lo.u32.u32 %0, %1, 2, %2;" : "=r"(sx) : "r"(pw), "r"(sb + SM_SRC));
                const int dv = pw >> 27;
                const uint32_t db = da + xab;
                const uint32_t sel = (pt >> 16) & 15, nx = (pt >> 20) & 127;
                uint32_t g;
                auto claim = [&]() { asm volatile("atom.shared.add.u32 %0, [%1], %2;" : "=r"(g) : "r"(ca), "r"(nx == 0 ? 1u : 0u) : "memory"); };
                if (sel == 0) break;
                claim();
                switch (sel) {
#define CASE(L, P, GEN) case L: { \
                        uint32_t oe[(P + 1) / 2], o[P]; \
                        if (first) asm volatile("bar.sync 3, 480;" ::: "memory"); \
                        _Pragma("unroll") for (int j = 0; j < (P + 1) / 2; j++) oe[j] = lds32(se + j * 16); \
                        _Pragma("unroll") for (int j = 0; j < P; j++) o[j] = lds32(sx + j * 4); \
                        mbar_wait_h(br + 8, ph); \
                        _Pragma("unroll") for (int j = 0; j < (P + 1) / 2; j++) \
                            if (LO32) { if (!GEN && 2 * j + 2 < P) cpe<false>(he, de + j * 512, oe[j], ge0, 0, 0, pol); \
                                else if (2 * j + 1 < NPMAX || s < 2) cpe<true>(he, de + j * 512, oe[j], ge0, 4 * j + s, dv, pol); } \
                            else if (!GEN && 2 * j + 2 < P) cp16e(de + j * 512, ge, oe[j], pol); else if (2 * j + 1 < NPMAX || s < 2) cp16z<32>(de + j * 512, ge, oe[j], 4 * j + s, dv, pol); \
                        _Pragma("unroll") for (int j = 0; j < P - 1; j++) { \
                            if (LO32) { cpx<0, GEN>(hi, da + j * 1024, o[j], gx0, 2 * j, dv); cpx<1, GEN>(hi, db + j * 1024, o[j], gx0, 2 * j + 1, dv); } \
                            else if (GEN) { cp16z<128>(da + j * 1024, gx, o[j] & 0xFFFFu, 2 * j, dv, 0); cp16z<128>(db + j * 1024, gx, o[j] >> 16, 2 * j + 1, dv, 0); } \
                            else { cp16i<128>(da + j * 1024, gx, o[j] & 0xFFFFu); cp16i<128>(db + j * 1024, gx, o[j] >> 16); } } \
                        if (LO32) { cpx<0, true>(hi, da + (P - 1) * 1024, o[P - 1], gx0, 2 * P - 2, dv); cpx<1, true>(hi, db + (P - 1) * 1024, o[P - 1], gx0, 2 * P - 1, dv); } \
                        else { cp16z<128>(da + (P - 1) * 1024, gx, o[P - 1] & 0xFFFFu, 2 * P - 2, dv, 0); cp16z<128>(db + (P - 1) * 1024, gx, o[P - 1] >> 16, 2 * P - 1, dv, 0); } \
                    } break;
                    CASE(6, 6, false) CASE(7, 7, false) CASE(8, 8, false) CASE(9, 9, false) CASE(10, 10, false) CASE(11, 11, false)
                    CASE(15, NPMAX, true) CASE(14, 8, true) default: CASE(13, 5, true)
#undef CASE
                }
                first = 0;
                mbar_cp_arrive(br);
                done3();
                g = __reduce_min_sync(~0u, g);
                {
                    const uint2 e = lds64(pa + (nx == 0 ? g : nx) * 32);
                    const uint2 v = tile_info(e.y);
                    pw = e.x;
                    asm volatile("st.shared.v2.u32 [%0], {%1, %2};" :: "r"(br + 16 + r4 * 8), "r"(v.x), "r"((v.y & ~C_BRK) | brk) : "memory");
                    brk = v.y & C_BRK;
                }
                mbar_arrive(br);
                hist = (hist << 8) | (nx == 0 ? cur : 96u);
                cur = nx == 0 ? g : cur;
                ph ^= br != bars; br = brs - br; da = das - da; de = des - de;
            }
            if (first) asm volatile("bar.sync 3, 480;" ::: "memory");
            if (go) {
                mbar_wait(sb + SM_ABAR + 72, 0);
                const int g0 = 3 * max((ngroups + 2) / 3 - TR, 0) + w;
                uint32_t ra[TR], gb[TR]; uint4 xv[TR], xu[TR]; char* po[TR];
                const int gz = misc[4];
                #pragma unroll
                for (int k = 0; k < TR; k++) {
                    uint32_t nd;
                    asm volatile("ld.shared.u16 %0, [%1];" : "=r"(nd) : "r"(sb + SM_WL + (g0 + 3 * k) * 8 + r4 * 2) : "memory");
                    xv[k] = __ldg((const uint4*)(gx + (size_t)(node0 + (nd == NONE ? 0u : nd)) * 128));
                    const uint32_t ro = sb + nd * 128 + ((c8 ^ (nd & 7)) << 4);
                    xu[k] = lds128(ro + SM_XU);
                    const bool some = g0 + 3 * k < gz;
                    ra[k] = some ? ro + SM_TAB : sb + SM_MISC + 64;
                    gb[k] = some ? sb + SM_GBAR + (g0 + 3 * k) * 8 : sb + SM_ABAR + 72;
                    po[k] = nd != NONE ? (char*)out + (size_t)(node0 + nd) * 128 + c8 * 16 : nullptr;
                    asm volatile("" : "+r"(ra[k]), "+r"(gb[k]), "+l"(po[k]));
                }
                #pragma unroll 1
                for (int k = 0; k < 3; k++) {
                    mbar_wait(k < 2 ? br + 8 : sb + SM_ABAR + 48 + w * 8, k < 2 ? ph : 0);
                    done3(); hist <<= 8;
                    ph ^= br != bars; br = brs - br;
                }
                #pragma unroll
                for (int k = 0; k < TR; k++) {
                    mbar_wait_c(gb[k], 0);
                    uint4 a = lds128(ra[k]);
                    finish(a, xu[k], xv[k]);
                    if (po[k]) *(uint4*)po[k] = a;
                }
            }
            cp_wait<0>();
        } else {
            const char* gx = ga; const char* ob = gb;
            mbar_wait(sb + SM_ABAR + 72, 0);
            WS(15); ZS(9);
            if (b == 0 && lane == 0) asm volatile("red.relaxed.gpu.global.add.u32 [%0], 1;" :: "l"(gbar) : "memory");
            const int rounds = misc[1] ? 0 : max((ngroups + 2) / 3 - TR, 0);
            const int gz = misc[4], fast = __reduce_min_sync(~0u, min(rounds, gz / 3));
            uint32_t wl = sb + SM_WL + r4 * 2, gbar = sb + SM_GBAR;
            auto row_at = [&](uint32_t a) { uint32_t n; asm volatile("ld.shared.u16 %0, [%1];" : "=r"(n) : "r"(a) : "memory"); return n; };
            auto fetch = [&](uint32_t n, uint4& v) {
                asm volatile("{\n.reg .b64 p;\nmad.wide.u32 p, %5, 128, %4;\nld.global.nc.L1::no_allocate.v4.u32 {%0,%1,%2,%3}, [p];\n}"
                             : "=r"(v.x), "=r"(v.y), "=r"(v.z), "=r"(v.w) : "l"(gx), "r"(n));
            };
            auto store = [&](uint32_t n, const uint4& a) {
                asm volatile("{\n.reg .b64 p;\nmad.wide.u32 p, %1, 128, %0;\nst.global.v4.u32 [p], {%2,%3,%4,%5};\n}" :: "l"(ob), "r"(n), "r"(a.x), "r"(a.y), "r"(a.z), "r"(a.w) : "memory");
            };
            uint32_t n0[3]; uint4 x0[3];
            if (fast) {
                #pragma unroll
                for (int r = 0; r < 3; r++) { n0[r] = row_at(wl + r * 8); fetch(n0[r], x0[r]); }
            }
            #pragma unroll 1
            for (int k = 0; k < fast; k++) {
                wl += 24;
                #pragma unroll
                for (int r = 0; r < 3; r++) {
                    const uint32_t nd = n0[r], ro = sb + nd * 128 + ((c8 ^ (nd & 7)) << 4);
                    const uint4 xu = lds128(ro + SM_XU);
                    n0[r] = row_at(wl + r * 8);
                    mbar_wait(gbar + r * 8, 0);
                    uint4 a = lds128(ro + SM_TAB);
                    finish(a, xu, x0[r]);
                    fetch(n0[r], x0[r]);
                    store(nd, a);
                }
                gbar += 24;
            }
            #pragma unroll 1
            for (int g = 3 * fast; g < 3 * rounds; g++) {
                const uint32_t nd = row_at(sb + SM_WL + r4 * 2 + g * 8), ro = sb + nd * 128 + ((c8 ^ (nd & 7)) << 4);
                uint4 xv, a = make_uint4(0, 0, 0, 0);
                fetch(nd, xv);
                if (g < gz) { mbar_wait(sb + SM_GBAR + g * 8, 0); a = lds128(ro + SM_TAB); }
                finish(a, lds128(ro + SM_XU), xv);
                store(nd, a);
            }
        }
    } else {
        asm volatile("setmaxnreg.inc.sync.aligned.u32 152;");
        float4 lgh[2 * NPMAX];
        uint32_t wf[40], wn[16], wt[16];
        const uint32_t mo0 = sbase + SM_TAB + (8 * (lane >> 4) + (lane & 7)) * 128 + (((2 * w + ((lane >> 3) & 1)) ^ (lane & 7)) << 4);
        mbar_wait_c(sbase + SM_ABAR + 24, 0);
        {
            const uint32_t wo = sbase + SM_WR + (2 * t) * 128 + ((ch0 * 2) ^ (t * 32));
            #pragma unroll
            for (int ks = 0; ks < 9; ks++) {
                uint32_t wr[4];
                #pragma unroll
                for (int i = 0; i < 4; i++) wr[i] = lds32((wo ^ ((i & 1) * 16)) + (16 * ks + (i & 1) + 4 * (i & 2)) * 128);
                if (ks < 5) make_wfrag<true>(wf + 4 * ks, wr); else make_wfrag<false>(wf + 4 * ks, wr);
            }
            #pragma unroll
            for (int ks = 0; ks < 4; ks++) { ldsm4t(wn + 4 * ks, mo0 + (144 + 16 * ks) * 128); ldsm4t(wt + 4 * ks, mo0 + (208 + 16 * ks) * 128); }
            if (wg == 2) {
                const uint32_t a = sbase + SM_WC + (16 * w + q) * 32 + t * 4, sw = (q >> 2) << 4;
                sts32(a + sw, wf[16]); sts32(a + 256 + sw, wf[17]); sts32(a + (sw ^ 16), wf[18]); sts32(a + 256 + (sw ^ 16), wf[19]);
                asm volatile("fence.proxy.async.shared::cta;" ::: "memory");
            }
            #pragma unroll
            for (int i = 0; i < 36; i++) asm volatile("" : "+r"(wf[i]));
        }
        WS(9);
        constexpr int NU = 6;
        const uint32_t dm = ((NPB_MAX + lane) * 4 | (tag << 14)) * 0x10001u;
        const char* const g1 = gs + (tid >> 4) * (P1B + P2B) + 256 + b * (CE * 2) + (lane & 15) * 8;
        const bool last = 2 * warp + 24 * (NU - 1) < nb;
        uint2 r1[NU];
        #pragma unroll
        for (int i = 0; i < NU; i++) r1[i] = make_uint2(dm, (tid >> 4) + 24 * i < nb ? 0 : dm);
        uint32_t spins = 0;
        asm volatile("bar.sync 5, 512;" ::: "memory");
        while (true) {
            #pragma unroll
            for (int i = 0; i < NU; i++) ld_unit(r1[i], g1 + i * (24 * (P1B + P2B)), (r1[i].y ^ dm) & 0xC000);
            #pragma unroll
            for (int i = 0; i < 4; i++) sts128(mo0 + wg * 16384 + 8192 + i * 2048, make_uint4(wt[4*i], wt[4*i+1], wt[4*i+2], wt[4*i+3]));
            uint32_t bad = 0;
            #pragma unroll
            for (int i = 0; i < NU; i++) bad |= r1[i].y ^ dm;
            const bool more = __any_sync(~0u, bad & 0xC000);
            if (spins == 0) WS(2);
            if (!more) break;
            if (++spins > (1u << 22)) __trap();
        }
        WS(3);
        const uint32_t db = sbase + SM_DEG - (tag << 14);
        uint32_t rk[NU][4];
        #pragma unroll
        for (int i = 0; i < NU; i++) {
            #pragma unroll
            for (int k = 0; k < 4; k++) {
                asm("dp2a.lo.u32.u32 %0, %1, %2, %3;" : "=r"(rk[i][k]) : "r"(k < 2 ? r1[i].x : r1[i].y), "r"(k & 1 ? 0x100u : 1u), "r"(db));
                if (i < NU - 1 || last) asm volatile("red.shared.add.u32 [%0], 1;" :: "r"(rk[i][k]) : "memory");
            }
        }
        WS(10);
        asm volatile("bar.sync 7, 512;" ::: "memory");
        WS(11);
        {
            const uint32_t ev = (lds32(sbase + SM_DEG + tid * 4) + 1) & ~1u;
            uint32_t inc = ev, base = 0;
            #pragma unroll
            for (int o = 1; o < 32; o <<= 1) { const uint32_t y = __shfl_up_sync(~0u, inc, o); if (lane >= o) inc += y; }
            if (lane == 31) {
                asm volatile("atom.shared.add.u32 %0, [%1], %2;" : "=r"(base) : "r"(sbase + SM_MISC + 24), "r"(inc) : "memory");
                if (base + inc > SLOT_CAP) misc[1] = 1;
            }
            const uint32_t s0 = min(__shfl_sync(~0u, base, 31) + inc - ev, SLOT_CAP);
            sts32(sbase + SM_CNT + tid * 4, 4 * s0);
            asm volatile("st.shared.u16 [%0], %1;" :: "r"(sbase + SM_BASE + tid * 2), "r"(s0) : "memory");
        }
        asm volatile("bar.arrive 4, 512;" ::: "memory");
        asm volatile("bar.sync 1, 384;" ::: "memory");
        WS(13);
        #pragma unroll
        for (int i = 0; i < NU; i++) {
            if (i < NU - 1 || last) {
                #pragma unroll
                for (int k = 0; k < 4; k++) asm volatile("atom.shared.add.u32 %0, [%0+%1], 4;" : "+r"(rk[i][k]) : "n"(SM_CNT - SM_DEG) : "memory");
            }
        }
        WS(14);
        uint4 r2[NU];
        mbar_wait_c(sbase + SM_ABAR + 40, 0);
        WS(4);
        #pragma unroll
        for (int i = 0; i < NU; i++) r2[i] = lds128(sbase + SM_P2 + (i < NU - 1 ? tid + 384 * i : min(tid + 384 * i, P2B / 16 - 1)) * 16);
        while (true) {
            uint32_t bad = 0;
            #pragma unroll
            for (int i = 0; i < NU; i++) if (i < NU - 1 || last) bad |= (r2[i].x ^ (tag << 16)) & ~(rk[i][0] >> 14);
            if (__builtin_expect(!__any_sync(~0u, bad & 0x30000), 1)) break;
            #pragma unroll
            for (int i = 0; i < NU; i++)
                ld_unit(r2[i], g1 + (P1B + b * (CE * 2) + (lane & 15) * 8 + i * (24 * (P1B + P2B))), (i < NU - 1 || last) && ((r2[i].x ^ (tag << 16)) & ~(rk[i][0] >> 14) & 0x30000));
            if (++spins > (1u << 22)) __trap();
        }
        WS(16);
        const uint32_t sbu = __reduce_or_sync(~0u, sbase);
        auto place = [&](uint32_t s4, uint32_t v, uint32_t eb) {
            asm volatile("{\n.reg .pred p;\nsetp.lt.u32 p, %0, %5;\n@p st.shared.u32 [%1], %2;\n@p st.shared.u16 [%3], %4;\n}"
                         :: "r"(s4), "r"(sbu + SM_EID + s4), "r"(eb + (v >> 19)), "r"(sbu + SM_SRC + (s4 >> 1)), "r"(v), "n"(4 * SLOT_CAP) : "memory");
        };
        #pragma unroll
        for (int i = 0; i < NU; i++) {
            const uint32_t eb = ((tid >> 4) + 24 * i) * ch;
            if (i == 2 && warp == 10 && elect_one()) { x_ld(1); x_ld(0); }
            if (i < NU - 1 || last) { place(rk[i][0], r2[i].x, eb); place(rk[i][1], r2[i].y, eb); place(rk[i][2], r2[i].z, eb); place(rk[i][3], r2[i].w, eb); }
        }
        WS(1);
        WGD();
        asm volatile("bar.arrive 3, 480;" ::: "memory");
        {
        int lane;
        asm volatile("mov.u32 %0, %%laneid;" : "=r"(lane));
        const int q = lane >> 2, t = lane & 3, ch0 = 16 * w + 2 * q;
        const uint32_t sbase = sbu;
        { const uint2 z = lds64(sbase + SM_OH + 8); wf[37] = z.x; wf[38] = z.y; }
        const uint32_t c2 = __shfl_sync(~0u, ch0 * 2, lane), t8 = __shfl_sync(~0u, t * 8, lane);
        float g[4 * NPMAX], h[4 * NPMAX];
        float4 cyr = make_float4(0.f, 0.f, 0.f, 0.f);
        {
            const uint32_t mo = sbase + (8 * (lane >> 4) + (lane & 7)) * 128 + (((2 * w + ((lane >> 3) & 1)) ^ (lane & 7)) << 4);
            mbar_wait_c(sbase + SM_XBAR + wg * 8, 0);
            WSP(4);
            node_mma2(g, h, wn, desc_sw128(sbase + SM_XU + wg * 16384));
            TileMMA<8>::wait_g(g);
            node_rows(mo + SM_TAB + wg * 16384, g);
            TileMMA<8>::wait_h(h);
            WSP(5);
            #pragma unroll
            for (int i = 0; i < 4; i++) {
                const uint4 f = lds128(mo + SM_TAB + wg * 16384 + 8192 + i * 2048);
                wn[4*i] = f.x; wn[4*i+1] = f.y; wn[4*i+2] = f.z; wn[4*i+3] = f.w;
            }
            __syncwarp();
            node_rows(mo + SM_TAB + wg * 16384 + 8192, h);
            mbar_arrive(sbase + SM_XBAR + 24);
            WSP(2);
            node_mma2(g, h, wn, desc_sw128(sbase + SM_XU + wg * 16384));
            TileMMA<8>::wait_g(g);
            asm volatile("bar.sync %0, 128;" :: "r"(8 + wg) : "memory");
            node_rows(mo + SM_XU + wg * 16384, g);
            TileMMA<8>::wait_h(h);
            WSP(3);
            asm volatile("bar.sync %0, 128;" :: "r"(8 + wg) : "memory");
            node_rows(mo + SM_XU + wg * 16384 + 8192, h);
            mbar_arrive(sbase + SM_ABAR + 72);
            mbar_wait_c(sbase + SM_XBAR + 24, 0);
            if (__builtin_expect(lds32(sbase + SM_MISC + 4) != 0, 0)) { slow_bin(x, ea, src, dst, wa, wb, wc, wu, wv, out, E, node0, nn, 384); return; }
            WS(6);
        }
        const uint64_t wcd = __reduce_or_sync(~0u, (((sbase + SM_WC) & 0x3FFFF) >> 4) | (8u << 16)) | EDHI;
        const uint32_t bar0 = __reduce_or_sync(~0u, sbase + SM_BARS + wg * 96);
        const uint32_t xd0 = __reduce_or_sync(~0u, (((sbase + SM_XS + wg * NSTAGE * XS_BYTES) & 0x3FFFF) >> 4) | (1u << 16));
        const uint32_t ed0 = __reduce_or_sync(~0u, (((sbase + SM_ES + wg * NSTAGE * ES_BYTES) & 0x3FFFF) >> 4) | (8u << 16));
        const uint64_t ohd = __reduce_or_sync(~0u, (((sbase + SM_OH) & 0x3FFFF) >> 4) | (8u << 16));
        const uint32_t tabx = __reduce_or_sync(~0u, sbase + SM_TAB);
        const uint32_t bars = __reduce_or_sync(~0u, 2 * bar0 + 48), xds = __reduce_or_sync(~0u, 2 * xd0 + XS_BYTES / 16), eds = __reduce_or_sync(~0u, 2 * ed0 + ES_BYTES / 16);
        uint32_t bar = bar0, xd = xd0, ed = ed0, ph = 0, code, w1, ta, pta = NONE * 128 + c2;
        float pn0 = 0.f, pd0 = 1.f, pn1 = 0.f, pd1 = 1.f;
        uint2 ni = tile_info(lds32(sbase + SM_TINFO + wg * 32 + t * 8 + 4));
        auto fetch_a = [&]() {
            ta = (ni.x & 0xFFFFu) ^ c2;
            wf[36] = lds32(tabx + ta); wf[39] = lds32(tabx + ta);
            code = __reduce_or_sync(~0u, ni.y);
        };
        auto emit = [&]() { sts32(tabx + pta, pack_bf16(pn0 * rcpf(pd0), pn1 * rcpf(pd1))); };
        auto carry = [&]() {
            if (w1 & C_CONT) { pn0 += cyr.x; pd0 += cyr.y; pn1 += cyr.z; pd1 += cyr.w; }
            if (w1 & C_MORE) { cyr = make_float4(pn0, pd0 - EPS2, pn1, pd1 - EPS2); pn0 = pn1 = 0.f; pta = NONE * 128 + c2; }
        };
        auto next = [&](uint32_t fb) {
            pta = ta;
            w1 = ni.y;
            ni = lds64(fb + 16 + t8);
        };
        fetch_a();
        while (true) {
            switch (code & 15) {
                default: goto finished;
#define TILE(P) { \
                    float dmin; \
                    do { \
                        mbar_wait_c(bar, ph); \
                        TileMMA<P>::issue(g, h, wf, xd | (0x40000040ull << 32), ed | EDHI, ohd, wcd); \
                        const uint32_t eb = bar + 8; \
                        ph ^= bar != bar0; bar = bars - bar; xd = xds - xd; ed = eds - ed; \
                          \
                        asm volatile("{\n.reg .pred p;\nsetp.eq.u32 p, %0, 77;\n@p trap;\n}" :: "r"(xds) : "memory"); \
                        emit(); next(eb - 8); \
                        TileMMA<P>::wait_g(g); fetch_a(); TileMMA<P>::wait_h(h); \
                        mbar_arrive(eb); \
                        float m1; \
                        asm("set.gt.f32.f32 %0, %1, 0f0000007F;" : "=f"(m1) : "f"(__uint_as_float(w1))); \
                        epi_fast<P>(g, h, m1, __uint_as_float(w1), pn0, pd0, pn1, pd1, dmin); \
                    } while (!(__any_sync(~0u, dmin < TAU * 2 * P) | ((code & 31) != P))); \
                    if (__builtin_expect(__any_sync(~0u, (int)w1 < 0 || dmin < TAU * 2 * P), 0)) { \
                        int dv; \
                        if (unpad(w1, P, g[P > 1 ? 4 * P - 7 : 0], g[P > 1 ? 4 * P - 5 : 0], pd0, pd1, dv)) { \
                            FBT(2); \
                            epi_dump<P>(g, h, lgh); \
                            FBT(3); \
                            const float4 r = epi_exact(lgh, P, dv); \
                            pn0 = r.x; pd0 = r.y; pn1 = r.z; pd1 = r.w; \
                            if (pd0 != 77.f) FBT(4); \
                        } \
                    } \
                    if (code & C_BRK) { carry(); if (P != 11 && (code & 15) == P) goto L##P; } \
                    if (P == 11) {         \
                        const uint32_t a = tabx + (SM_WC - SM_TAB) + (c2 & 0x60) * 16 + (c2 & 0x1C) * 8 + (t8 >> 1), sw = c2 & 16; \
                        wf[16] = lds32(a + sw); wf[17] = lds32(a + 256 + sw); wf[18] = lds32(a + (sw ^ 16)); wf[19] = lds32(a + 256 + (sw ^ 16)); \
                    } }
#define CASE(P, UP, DN) case P: L##P: TILE(P) \
                    if (P > NPMIN && (code & 15) == P - 1) goto L##DN; \
                    if (P <= 6 && (code & 15) == 0) goto finished; \
                    if ((code & 15) == UP) goto L##UP; \
                    break;
                CASE(11, 11, 10) CASE(10, 11, 9) CASE(9, 10, 8) CASE(8, 9, 7) CASE(7, 8, 6) CASE(6, 7, 5) CASE(5, 6, 4) CASE(4, 5, 4)
#undef CASE
#undef TILE
            }
        }
finished:
        emit();
        mbar_arrive(sbase + SM_ABAR + 48 + wg * 8);
        }
    }
    WS(17); WG1();
}

}

extern "C" void kernel_launch(void* const* d_in, const int* in_sizes, int n_in, void* d_out, int out_size) {
    const __nv_bfloat16* x = (const __nv_bfloat16*)d_in[0];
    const __nv_bfloat16* ea = (const __nv_bfloat16*)d_in[1];
    const int* src = (const int*)d_in[2];
    const int* dst = (const int*)d_in[3];
    const __nv_bfloat16* wa = (const __nv_bfloat16*)d_in[4];
    const __nv_bfloat16* wb = (const __nv_bfloat16*)d_in[5];
    const __nv_bfloat16* wc = (const __nv_bfloat16*)d_in[6];
    const __nv_bfloat16* wu = (const __nv_bfloat16*)d_in[7];
    const __nv_bfloat16* wv = (const __nv_bfloat16*)d_in[8];
    __nv_bfloat16* out = (__nv_bfloat16*)d_out;
    int N = in_sizes[0] / 64, E = in_sizes[2];
    static int sms = 0;
    static CUtensorMap tm2;
    static bool tm_ok = false;
    typedef CUresult (*EncFn)(CUtensorMap*, CUtensorMapDataType, cuuint32_t, void*, const cuuint64_t*, const cuuint64_t*, const cuuint32_t*,
                              const cuuint32_t*, CUtensorMapInterleave, CUtensorMapSwizzle, CUtensorMapL2promotion, CUtensorMapFloatOOBfill);
    static void* fn = nullptr;
    static void* gp = nullptr; static void* gb = nullptr;
    if (!sms) {
        cudaDeviceGetAttribute(&sms, cudaDevAttrMultiProcessorCount, 0);
        cudaDriverEntryPointQueryResult qr;
        cudaGetDriverEntryPoint("cuTensorMapEncodeTiled", &fn, cudaEnableDefault, &qr);
        cudaGetSymbolAddress(&gp, g_str); cudaGetSymbolAddress(&gb, g_bar);
        if (fn && gp && gb) {
            const cuuint32_t rows = sms < NB_MAX ? sms : NB_MAX;
            cuuint64_t g2[2] = {(P1B + P2B) / 4, NB_MAX}, gs[1] = {P1B + P2B};
            cuuint32_t b2[2] = {CE, rows}, es[2] = {1, 1};
            tm_ok = ((EncFn)fn)(&tm2, CU_TENSOR_MAP_DATA_TYPE_UINT32, 2, gp, g2, gs, b2, es, CU_TENSOR_MAP_INTERLEAVE_NONE, CU_TENSOR_MAP_SWIZZLE_NONE,
                                CU_TENSOR_MAP_L2_PROMOTION_NONE, CU_TENSOR_MAP_FLOAT_OOB_FILL_NONE) == CUDA_SUCCESS;
        }
        cudaFuncSetAttribute(gcn_kernel<true>, cudaFuncAttributeMaxDynamicSharedMemorySize, SMEM_LAUNCH);
        cudaFuncSetAttribute(gcn_kernel<false>, cudaFuncAttributeMaxDynamicSharedMemorySize, SMEM_LAUNCH);
    }
    auto rows = [&](CUtensorMap* tm, const void* base, uint64_t n, uint32_t box) {
        cuuint64_t gd[2] = {64, n}, gs[1] = {128};
        cuuint32_t bx[2] = {64, box}, es[2] = {1, 1};
        return ((EncFn)fn)(tm, CU_TENSOR_MAP_DATA_TYPE_BFLOAT16, 2, (void*)base, gd, gs, bx, es, CU_TENSOR_MAP_INTERLEAVE_NONE, CU_TENSOR_MAP_SWIZZLE_128B,
                           CU_TENSOR_MAP_L2_PROMOTION_NONE, CU_TENSOR_MAP_FLOAT_OOB_FILL_NONE) == CUDA_SUCCESS;
    };
    const uintptr_t wp[4] = {(uintptr_t)wa, (uintptr_t)wb, (uintptr_t)wu, (uintptr_t)wv};
    uintptr_t w0 = wp[0], w1 = wp[0], wal = 0;
    for (int i = 1; i < 4; i++) { w0 = wp[i] < w0 ? wp[i] : w0; w1 = wp[i] > w1 ? wp[i] : w1; wal |= wp[i] - wp[0]; }
    int4 wrow = make_int4((int)((wp[0] - w0) >> 7), (int)((wp[1] - w0) >> 7), (int)((wp[2] - w0) >> 7), (int)((wp[3] - w0) >> 7));
    CUtensorMap tmw, tmc, tmx;
    const bool maps = tm_ok && N > 0 && !(wal & 127) && ((w1 - w0) >> 7) < (1u << 30) && rows(&tmw, (void*)w0, ((w1 - w0) >> 7) + 64, 64) && rows(&tmc, wc, 16, 16) && rows(&tmx, x, N, 128);
    int nb = sms < NB_MAX ? sms : NB_MAX;
    int npb = (N + nb - 1) / nb;
    int ch = (((E + nb - 1) / nb) + 3) & ~3;
    if (!maps || npb > NPB_MAX || ch > CH_MAX || (E & 3) || N > 65535 || npb < 2 || (((uintptr_t)src | (uintptr_t)dst | (uintptr_t)wa | (uintptr_t)wb | (uintptr_t)wc | (uintptr_t)wu | (uintptr_t)wv) & 15)) {
        int g = 1024, p = (N + g - 1) / g;
        slow_kernel<<<g, 256>>>(x, ea, src, dst, wa, wb, wc, wu, wv, out, N, E, p < 1 ? 1 : p);
        return;
    }
    uint32_t magic = (uint32_t)((1ull << 32) / (uint32_t)npb) + 1u;
    void* args[] = {&dst, &gb, &gp, &src, &E, &ch, &N, &npb, &magic, &x, &ea, &wa, &wb, &wc, &wu, &wv, &out, &wrow, &tm2, &tmw, &tmc, &tmx};
    const bool lo32 = ((uintptr_t)x >> 32) == (((uintptr_t)x + (size_t)N * 128 - 1) >> 32) && ((uintptr_t)ea >> 32) == (((uintptr_t)ea + (size_t)E * 32 - 1) >> 32);
    cudaLaunchCooperativeKernel(lo32 && !FORCE64 ? (const void*)gcn_kernel<true> : (const void*)gcn_kernel<false>, dim3(nb), dim3(THREADS), args, SMEM_LAUNCH, cudaStreamPerThread);
}
```

```cpp
#include <cuda_runtime.h>
#include <cuda.h>
#include <cuda_bf16.h>
#include <stdint.h>

namespace {

constexpr int N_MAX = 65536;
constexpr int NPMIN = 4;
constexpr int NPMAX = 11;
constexpr int THREADS = 512;
constexpr int EPT = 12;
constexpr int CH_MAX = THREADS * EPT;
constexpr int NB_MAX = 134;
constexpr int GAL = 128;
constexpr int CE = 64;
constexpr int P1B = (256 + NB_MAX * CE * 2 + GAL - 1) / GAL * GAL;
constexpr int P2B = (256 + NB_MAX * CE * 4 + GAL - 1) / GAL * GAL;
constexpr int NPB_MAX = 384;
constexpr int SLOT_CAP = 6784;
constexpr int TILE_CAP = 124;
constexpr int TILE_X = 8;
constexpr int NCLS = 64;
constexpr int XCAP = 128;
constexpr int NSTAGE = 2;
constexpr int TR = 2;
constexpr float LOG2E = 1.4426950408889634f;

__device__ __align__(128) uint4 g_str[NB_MAX * (P1B + P2B) / 16];
__device__ __align__(128) unsigned g_bar[32];
__device__ float g_slow[N_MAX * 128];

#define WS(k)
#define WGD()
#define ZS(k)
#define FBT(k)
#define WSP(k)
#define WSL(k)
#define WSG(k)
#define WG0()
#define WG1()
#define SMEM_LAUNCH SMEM_BYTES
#define FORCE64 0
#define EDHI ((16ull << 32) | (3ull << 62))
template<int NP> struct TileMMA;
template<> struct TileMMA<4> {
  static __device__ __forceinline__ void issue(float* g, float* h, const uint32_t* w, uint64_t dx, uint64_t de, uint64_t dh, uint64_t dc) {
    asm volatile(
      "{\n.reg .b64 dx1, dx2, dx3;\n"
      "add.s64 dx1, %72, 2;\nadd.s64 dx2, %72, 4;\nadd.s64 dx3, %72, 6;\n"
      "wgmma.fence.sync.aligned;\n"
      "wgmma.mma_async.sync.aligned.m64n32k16.f32.bf16.bf16 {%0, %1, %2, %3, %4, %5, %6, %7, %8, %9, %10, %11, %12, %13, %14, %15}, {%68, %69, %70, %71}, %74, 0, 1, 1, 0;\n"
      "wgmma.mma_async.sync.aligned.m64n32k16.f32.bf16.bf16 {%0, %1, %2, %3, %4, %5, %6, %7, %8, %9, %10, %11, %12, %13, %14, %15}, {%48, %49, %50, %51}, %73, 1, 1, 1, 0;\n"
      "wgmma.mma_async.sync.aligned.m64n32k16.f32.bf16.bf16 {%0, %1, %2, %3, %4, %5, %6, %7, %8, %9, %10, %11, %12, %13, %14, %15}, {%32, %33, %34, %35}, %72, 1, 1, 1, 0;\n"
      "wgmma.mma_async.sync.aligned.m64n32k16.f32.bf16.bf16 {%0, %1, %2, %3, %4, %5, %6, %7, %8, %9, %10, %11, %12, %13, %14, %15}, {%36, %37, %38, %39}, dx1, 1, 1, 1, 0;\n"
      "wgmma.mma_async.sync.aligned.m64n32k16.f32.bf16.bf16 {%0, %1, %2, %3, %4, %5, %6, %7, %8, %9, %10, %11, %12, %13, %14, %15}, {%40, %41, %42, %43}, dx2, 1, 1, 1, 0;\n"
      "wgmma.mma_async.sync.aligned.m64n32k16.f32.bf16.bf16 {%0, %1, %2, %3, %4, %5, %6, %7, %8, %9, %10, %11, %12, %13, %14, %15}, {%44, %45, %46, %47}, dx3, 1, 1, 1, 0;\n"
      "wgmma.commit_group.sync.aligned;\n"
      "wgmma.mma_async.sync.aligned.m64n32k16.f32.bf16.bf16 {%16, %17, %18, %19, %20, %21, %22, %23, %24, %25, %26, %27, %28, %29, %30, %31}, {%52, %53, %54, %55}, %72, 0, 1, 1, 0;\n"
      "wgmma.mma_async.sync.aligned.m64n32k16.f32.bf16.bf16 {%16, %17, %18, %19, %20, %21, %22, %23, %24, %25, %26, %27, %28, %29, %30, %31}, {%56, %57, %58, %59}, dx1, 1, 1, 1, 0;\n"
      "wgmma.mma_async.sync.aligned.m64n32k16.f32.bf16.bf16 {%16, %17, %18, %19, %20, %21, %22, %23, %24, %25, %26, %27, %28, %29, %30, %31}, {%60, %61, %62, %63}, dx2, 1, 1, 1, 0;\n"
      "wgmma.mma_async.sync.aligned.m64n32k16.f32.bf16.bf16 {%16, %17, %18, %19, %20, %21, %22, %23, %24, %25, %26, %27, %28, %29, %30, %31}, {%64, %65, %66, %67}, dx3, 1, 1, 1, 0;\n"
      "wgmma.commit_group.sync.aligned;\n}\n"
      : "=f"(g[0]), "=f"(g[1]), "=f"(g[2]), "=f"(g[3]), "=f"(g[4]), "=f"(g[5]), "=f"(g[6]), "=f"(g[7]), "=f"(g[8]), "=f"(g[9]), "=f"(g[10]), "=f"(g[11]), "=f"(g[12]), "=f"(g[13]), "=f"(g[14]), "=f"(g[15]),
        "=f"(h[0]), "=f"(h[1]), "=f"(h[2]), "=f"(h[3]), "=f"(h[4]), "=f"(h[5]), "=f"(h[6]), "=f"(h[7]), "=f"(h[8]), "=f"(h[9]), "=f"(h[10]), "=f"(h[11]), "=f"(h[12]), "=f"(h[13]), "=f"(h[14]), "=f"(h[15])
      : "r"(w[0]), "r"(w[1]), "r"(w[2]), "r"(w[3]), "r"(w[4]), "r"(w[5]), "r"(w[6]), "r"(w[7]), "r"(w[8]), "r"(w[9]), "r"(w[10]), "r"(w[11]), "r"(w[12]), "r"(w[13]), "r"(w[14]), "r"(w[15]), "r"(w[16]), "r"(w[17]), "r"(w[18]), "r"(w[19]), "r"(w[20]), "r"(w[21]), "r"(w[22]), "r"(w[23]), "r"(w[24]), "r"(w[25]), "r"(w[26]), "r"(w[27]), "r"(w[28]), "r"(w[29]), "r"(w[30]), "r"(w[31]), "r"(w[32]), "r"(w[33]), "r"(w[34]), "r"(w[35]), "r"(w[36]), "r"(w[37]), "r"(w[38]), "r"(w[39]), "l"(dx), "l"(de), "l"(dh)
      : "memory");
  }
  static __device__ __forceinline__ void wait_g(float* g) {
    asm volatile("wgmma.wait_group.sync.aligned 1;\n"
      : "+f"(g[0]), "+f"(g[1]), "+f"(g[2]), "+f"(g[3]), "+f"(g[4]), "+f"(g[5]), "+f"(g[6]), "+f"(g[7]), "+f"(g[8]), "+f"(g[9]), "+f"(g[10]), "+f"(g[11]), "+f"(g[12]), "+f"(g[13]), "+f"(g[14]), "+f"(g[15])
      :: "memory");
  }
  static __device__ __forceinline__ void wait_h(float* h) {
    asm volatile("wgmma.wait_group.sync.aligned 0;\n"
      : "+f"(h[0]), "+f"(h[1]), "+f"(h[2]), "+f"(h[3]), "+f"(h[4]), "+f"(h[5]), "+f"(h[6]), "+f"(h[7]), "+f"(h[8]), "+f"(h[9]), "+f"(h[10]), "+f"(h[11]), "+f"(h[12]), "+f"(h[13]), "+f"(h[14]), "+f"(h[15])
      :: "memory");
  }
};
template<> struct TileMMA<5> {
  static __device__ __forceinline__ void issue(float* g, float* h, const uint32_t* w, uint64_t dx, uint64_t de, uint64_t dh, uint64_t dc) {
    asm volatile(
      "{\n.reg .b64 dx1, dx2, dx3;\n"
      "add.s64 dx1, %80, 2;\nadd.s64 dx2, %80, 4;\nadd.s64 dx3, %80, 6;\n"
      "wgmma.fence.sync.aligned;\n"
      "wgmma.mma_async.sync.aligned.m64n40k16.f32.bf16.bf16 {%0, %1, %2, %3, %4, %5, %6, %7, %8, %9, %10, %11, %12, %13, %14, %15, %16, %17, %18, %19}, {%76, %77, %78, %79}, %82, 0, 1, 1, 0;\n"
      "wgmma.mma_async.sync.aligned.m64n40k16.f32.bf16.bf16 {%0, %1, %2, %3, %4, %5, %6, %7, %8, %9, %10, %11, %12, %13, %14, %15, %16, %17, %18, %19}, {%56, %57, %58, %59}, %81, 1, 1, 1, 0;\n"
      "wgmma.mma_async.sync.aligned.m64n40k16.f32.bf16.bf16 {%0, %1, %2, %3, %4, %5, %6, %7, %8, %9, %10, %11, %12, %13, %14, %15, %16, %17, %18, %19}, {%40, %41, %42, %43}, %80, 1, 1, 1, 0;\n"
      "wgmma.mma_async.sync.aligned.m64n40k16.f32.bf16.bf16 {%0, %1, %2, %3, %4, %5, %6, %7, %8, %9, %10, %11, %12, %13, %14, %15, %16, %17, %18, %19}, {%44, %45, %46, %47}, dx1, 1, 1, 1, 0;\n"
      "wgmma.mma_async.sync.aligned.m64n40k16.f32.bf16.bf16 {%0, %1, %2, %3, %4, %5, %6, %7, %8, %9, %10, %11, %12, %13, %14, %15, %16, %17, %18, %19}, {%48, %49, %50, %51}, dx2, 1, 1, 1, 0;\n"
      "wgmma.mma_async.sync.aligned.m64n40k16.f32.bf16.bf16 {%0, %1, %2, %3, %4, %5, %6, %7, %8, %9, %10, %11, %12, %13, %14, %15, %16, %17, %18, %19}, {%52, %53, %54, %55}, dx3, 1, 1, 1, 0;\n"
      "wgmma.commit_group.sync.aligned;\n"
      "wgmma.mma_async.sync.aligned.m64n40k16.f32.bf16.bf16 {%20, %21, %22, %23, %24, %25, %26, %27, %28, %29, %30, %31, %32, %33, %34, %35, %36, %37, %38, %39}, {%60, %61, %62, %63}, %80, 0, 1, 1, 0;\n"
      "wgmma.mma_async.sync.aligned.m64n40k16.f32.bf16.bf16 {%20, %21, %22, %23, %24, %25, %26, %27, %28, %29, %30, %31, %32, %33, %34, %35, %36, %37, %38, %39}, {%64, %65, %66, %67}, dx1, 1, 1, 1, 0;\n"
      "wgmma.mma_async.sync.aligned.m64n40k16.f32.bf16.bf16 {%20, %21, %22, %23, %24, %25, %26, %27, %28, %29, %30, %31, %32, %33, %34, %35, %36, %37, %38, %39}, {%68, %69, %70, %71}, dx2, 1, 1, 1, 0;\n"
      "wgmma.mma_async.sync.aligned.m64n40k16.f32.bf16.bf16 {%20, %21, %22, %23, %24, %25, %26, %27, %28, %29, %30, %31, %32, %33, %34, %35, %36, %37, %38, %39}, {%72, %73, %74, %75}, dx3, 1, 1, 1, 0;\n"
      "wgmma.commit_group.sync.aligned;\n}\n"
      : "=f"(g[0]), "=f"(g[1]), "=f"(g[2]), "=f"(g[3]), "=f"(g[4]), "=f"(g[5]), "=f"(g[6]), "=f"(g[7]), "=f"(g[8]), "=f"(g[9]), "=f"(g[10]), "=f"(g[11]), "=f"(g[12]), "=f"(g[13]), "=f"(g[14]), "=f"(g[15]), "=f"(g[16]), "=f"(g[17]), "=f"(g[18]), "=f"(g[19]),
        "=f"(h[0]), "=f"(h[1]), "=f"(h[2]), "=f"(h[3]), "=f"(h[4]), "=f"(h[5]), "=f"(h[6]), "=f"(h[7]), "=f"(h[8]), "=f"(h[9]), "=f"(h[10]), "=f"(h[11]), "=f"(h[12]), "=f"(h[13]), "=f"(h[14]), "=f"(h[15]), "=f"(h[16]), "=f"(h[17]), "=f"(h[18]), "=f"(h[19])
      : "r"(w[0]), "r"(w[1]), "r"(w[2]), "r"(w[3]), "r"(w[4]), "r"(w[5]), "r"(w[6]), "r"(w[7]), "r"(w[8]), "r"(w[9]), "r"(w[10]), "r"(w[11]), "r"(w[12]), "r"(w[13]), "r"(w[14]), "r"(w[15]), "r"(w[16]), "r"(w[17]), "r"(w[18]), "r"(w[19]), "r"(w[20]), "r"(w[21]), "r"(w[22]), "r"(w[23]), "r"(w[24]), "r"(w[25]), "r"(w[26]), "r"(w[27]), "r"(w[28]), "r"(w[29]), "r"(w[30]), "r"(w[31]), "r"(w[32]), "r"(w[33]), "r"(w[34]), "r"(w[35]), "r"(w[36]), "r"(w[37]), "r"(w[38]), "r"(w[39]), "l"(dx), "l"(de), "l"(dh)
      : "memory");
  }
  static __device__ __forceinline__ void wait_g(float* g) {
    asm volatile("wgmma.wait_group.sync.aligned 1;\n"
      : "+f"(g[0]), "+f"(g[1]), "+f"(g[2]), "+f"(g[3]), "+f"(g[4]), "+f"(g[5]), "+f"(g[6]), "+f"(g[7]), "+f"(g[8]), "+f"(g[9]), "+f"(g[10]), "+f"(g[11]), "+f"(g[12]), "+f"(g[13]), "+f"(g[14]), "+f"(g[15]), "+f"(g[16]), "+f"(g[17]), "+f"(g[18]), "+f"(g[19])
      :: "memory");
  }
  static __device__ __forceinline__ void wait_h(float* h) {
    asm volatile("wgmma.wait_group.sync.aligned 0;\n"
      : "+f"(h[0]), "+f"(h[1]), "+f"(h[2]), "+f"(h[3]), "+f"(h[4]), "+f"(h[5]), "+f"(h[6]), "+f"(h[7]), "+f"(h[8]), "+f"(h[9]), "+f"(h[10]), "+f"(h[11]), "+f"(h[12]), "+f"(h[13]), "+f"(h[14]), "+f"(h[15]), "+f"(h[16]), "+f"(h[17]), "+f"(h[18]), "+f"(h[19])
      :: "memory");
  }
};
template<> struct TileMMA<6> {
  static __device__ __forceinline__ void issue(float* g, float* h, const uint32_t* w, uint64_t dx, uint64_t de, uint64_t dh, uint64_t dc) {
    asm volatile(
      "{\n.reg .b64 dx1, dx2, dx3;\n"
      "add.s64 dx1, %88, 2;\nadd.s64 dx2, %88, 4;\nadd.s64 dx3, %88, 6;\n"
      "wgmma.fence.sync.aligned;\n"
      "wgmma.mma_async.sync.aligned.m64n48k16.f32.bf16.bf16 {%0, %1, %2, %3, %4, %5, %6, %7, %8, %9, %10, %11, %12, %13, %14, %15, %16, %17, %18, %19, %20, %21, %22, %23}, {%84, %85, %86, %87}, %90, 0, 1, 1, 0;\n"
      "wgmma.mma_async.sync.aligned.m64n48k16.f32.bf16.bf16 {%0, %1, %2, %3, %4, %5, %6, %7, %8, %9, %10, %11, %12, %13, %14, %15, %16, %17, %18, %19, %20, %21, %22, %23}, {%64, %65, %66, %67}, %89, 1, 1, 1, 0;\n"
      "wgmma.mma_async.sync.aligned.m64n48k16.f32.bf16.bf16 {%0, %1, %2, %3, %4, %5, %6, %7, %8, %9, %10, %11, %12, %13, %14, %15, %16, %17, %18, %19, %20, %21, %22, %23}, {%48, %49, %50, %51}, %88, 1, 1, 1, 0;\n"
      "wgmma.mma_async.sync.aligned.m64n48k16.f32.bf16.bf16 {%0, %1, %2, %3, %4, %5, %6, %7, %8, %9, %10, %11, %12, %13, %14, %15, %16, %17, %18, %19, %20, %21, %22, %23}, {%52, %53, %54, %55}, dx1, 1, 1, 1, 0;\n"
      "wgmma.mma_async.sync.aligned.m64n48k16.f32.bf16.bf16 {%0, %1, %2, %3, %4, %5, %6, %7, %8, %9, %10, %11, %12, %13, %14, %15, %16, %17, %18, %19, %20, %21, %22, %23}, {%56, %57, %58, %59}, dx2, 1, 1, 1, 0;\n"
      "wgmma.mma_async.sync.aligned.m64n48k16.f32.bf16.bf16 {%0, %1, %2, %3, %4, %5, %6, %7, %8, %9, %10, %11, %12, %13, %14, %15, %16, %17, %18, %19, %20, %21, %22, %23}, {%60, %61, %62, %63}, dx3, 1, 1, 1, 0;\n"
      "wgmma.commit_group.sync.aligned;\n"
      "wgmma.mma_async.sync.aligned.m64n48k16.f32.bf16.bf16 {%24, %25, %26, %27, %28, %29, %30, %31, %32, %33, %34, %35, %36, %37, %38, %39, %40, %41, %42, %43, %44, %45, %46, %47}, {%68, %69, %70, %71}, %88, 0, 1, 1, 0;\n"
      "wgmma.mma_async.sync.aligned.m64n48k16.f32.bf16.bf16 {%24, %25, %26, %27, %28, %29, %30, %31, %32, %33, %34, %35, %36, %37, %38, %39, %40, %41, %42, %43, %44, %45, %46, %47}, {%72, %73, %74, %75}, dx1, 1, 1, 1, 0;\n"
      "wgmma.mma_async.sync.aligned.m64n48k16.f32.bf16.bf16 {%24, %25, %26, %27, %28, %29, %30, %31, %32, %33, %34, %35, %36, %37, %38, %39, %40, %41, %42, %43, %44, %45, %46, %47}, {%76, %77, %78, %79}, dx2, 1, 1, 1, 0;\n"
      "wgmma.mma_async.sync.aligned.m64n48k16.f32.bf16.bf16 {%24, %25, %26, %27, %28, %29, %30, %31, %32, %33, %34, %35, %36, %37, %38, %39, %40, %41, %42, %43, %44, %45, %46, %47}, {%80, %81, %82, %83}, dx3, 1, 1, 1, 0;\n"
      "wgmma.commit_group.sync.aligned;\n}\n"
      : "=f"(g[0]), "=f"(g[1]), "=f"(g[2]), "=f"(g[3]), "=f"(g[4]), "=f"(g[5]), "=f"(g[6]), "=f"(g[7]), "=f"(g[8]), "=f"(g[9]), "=f"(g[10]), "=f"(g[11]), "=f"(g[12]), "=f"(g[13]), "=f"(g[14]), "=f"(g[15]), "=f"(g[16]), "=f"(g[17]), "=f"(g[18]), "=f"(g[19]), "=f"(g[20]), "=f"(g[21]), "=f"(g[22]), "=f"(g[23]),
        "=f"(h[0]), "=f"(h[1]), "=f"(h[2]), "=f"(h[3]), "=f"(h[4]), "=f"(h[5]), "=f"(h[6]), "=f"(h[7]), "=f"(h[8]), "=f"(h[9]), "=f"(h[10]), "=f"(h[11]), "=f"(h[12]), "=f"(h[13]), "=f"(h[14]), "=f"(h[15]), "=f"(h[16]), "=f"(h[17]), "=f"(h[18]), "=f"(h[19]), "=f"(h[20]), "=f"(h[21]), "=f"(h[22]), "=f"(h[23])
      : "r"(w[0]), "r"(w[1]), "r"(w[2]), "r"(w[3]), "r"(w[4]), "r"(w[5]), "r"(w[6]), "r"(w[7]), "r"(w[8]), "r"(w[9]), "r"(w[10]), "r"(w[11]), "r"(w[12]), "r"(w[13]), "r"(w[14]), "r"(w[15]), "r"(w[16]), "r"(w[17]), "r"(w[18]), "r"(w[19]), "r"(w[20]), "r"(w[21]), "r"(w[22]), "r"(w[23]), "r"(w[24]), "r"(w[25]), "r"(w[26]), "r"(w[27]), "r"(w[28]), "r"(w[29]), "r"(w[30]), "r"(w[31]), "r"(w[32]), "r"(w[33]), "r"(w[34]), "r"(w[35]), "r"(w[36]), "r"(w[37]), "r"(w[38]), "r"(w[39]), "l"(dx), "l"(de), "l"(dh)
      : "memory");
  }
  static __device__ __forceinline__ void wait_g(float* g) {
    asm volatile("wgmma.wait_group.sync.aligned 1;\n"
      : "+f"(g[0]), "+f"(g[1]), "+f"(g[2]), "+f"(g[3]), "+f"(g[4]), "+f"(g[5]), "+f"(g[6]), "+f"(g[7]), "+f"(g[8]), "+f"(g[9]), "+f"(g[10]), "+f"(g[11]), "+f"(g[12]), "+f"(g[13]), "+f"(g[14]), "+f"(g[15]), "+f"(g[16]), "+f"(g[17]), "+f"(g[18]), "+f"(g[19]), "+f"(g[20]), "+f"(g[21]), "+f"(g[22]), "+f"(g[23])
      :: "memory");
  }
  static __device__ __forceinline__ void wait_h(float* h) {
    asm volatile("wgmma.wait_group.sync.aligned 0;\n"
      : "+f"(h[0]), "+f"(h[1]), "+f"(h[2]), "+f"(h[3]), "+f"(h[4]), "+f"(h[5]), "+f"(h[6]), "+f"(h[7]), "+f"(h[8]), "+f"(h[9]), "+f"(h[10]), "+f"(h[11]), "+f"(h[12]), "+f"(h[13]), "+f"(h[14]), "+f"(h[15]), "+f"(h[16]), "+f"(h[17]), "+f"(h[18]), "+f"(h[19]), "+f"(h[20]), "+f"(h[21]), "+f"(h[22]), "+f"(h[23])
      :: "memory");
  }
};
template<> struct TileMMA<7> {
  static __device__ __forceinline__ void issue(float* g, float* h, const uint32_t* w, uint64_t dx, uint64_t de, uint64_t dh, uint64_t dc) {
    asm volatile(
      "{\n.reg .b64 dx1, dx2, dx3;\n"
      "add.s64 dx1, %96, 2;\nadd.s64 dx2, %96, 4;\nadd.s64 dx3, %96, 6;\n"
      "wgmma.fence.sync.aligned;\n"
      "wgmma.mma_async.sync.aligned.m64n56k16.f32.bf16.bf16 {%0, %1, %2, %3, %4, %5, %6, %7, %8, %9, %10, %11, %12, %13, %14, %15, %16, %17, %18, %19, %20, %21, %22, %23, %24, %25, %26, %27}, {%92, %93, %94, %95}, %98, 0, 1, 1, 0;\n"
      "wgmma.mma_async.sync.aligned.m64n56k16.f32.bf16.bf16 {%0, %1, %2, %3, %4, %5, %6, %7, %8, %9, %10, %11, %12, %13, %14, %15, %16, %17, %18, %19, %20, %21, %22, %23, %24, %25, %26, %27}, {%72, %73, %74, %75}, %97, 1, 1, 1, 0;\n"
      "wgmma.mma_async.sync.aligned.m64n56k16.f32.bf16.bf16 {%0, %1, %2, %3, %4, %5, %6, %7, %8, %9, %10, %11, %12, %13, %14, %15, %16, %17, %18, %19, %20, %21, %22, %23, %24, %25, %26, %27}, {%56, %57, %58, %59}, %96, 1, 1, 1, 0;\n"
      "wgmma.mma_async.sync.aligned.m64n56k16.f32.bf16.bf16 {%0, %1, %2, %3, %4, %5, %6, %7, %8, %9, %10, %11, %12, %13, %14, %15, %16, %17, %18, %19, %20, %21, %22, %23, %24, %25, %26, %27}, {%60, %61, %62, %63}, dx1, 1, 1, 1, 0;\n"
      "wgmma.mma_async.sync.aligned.m64n56k16.f32.bf16.bf16 {%0, %1, %2, %3, %4, %5, %6, %7, %8, %9, %10, %11, %12, %13, %14, %15, %16, %17, %18, %19, %20, %21, %22, %23, %24, %25, %26, %27}, {%64, %65, %66, %67}, dx2, 1, 1, 1, 0;\n"
      "wgmma.mma_async.sync.aligned.m64n56k16.f32.bf16.bf16 {%0, %1, %2, %3, %4, %5, %6, %7, %8, %9, %10, %11, %12, %13, %14, %15, %16, %17, %18, %19, %20, %21, %22, %23, %24, %25, %26, %27}, {%68, %69, %70, %71}, dx3, 1, 1, 1, 0;\n"
      "wgmma.commit_group.sync.aligned;\n"
      "wgmma.mma_async.sync.aligned.m64n56k16.f32.bf16.bf16 {%28, %29, %30, %31, %32, %33, %34, %35, %36, %37, %38, %39, %40, %41, %42, %43, %44, %45, %46, %47, %48, %49, %50, %51, %52, %53, %54, %55}, {%76, %77, %78, %79}, %96, 0, 1, 1, 0;\n"
      "wgmma.mma_async.sync.aligned.m64n56k16.f32.bf16.bf16 {%28, %29, %30, %31, %32, %33, %34, %35, %36, %37, %38, %39, %40, %41, %42, %43, %44, %45, %46, %47, %48, %49, %50, %51, %52, %53, %54, %55}, {%80, %81, %82, %83}, dx1, 1, 1, 1, 0;\n"
      "wgmma.mma_async.sync.aligned.m64n56k16.f32.bf16.bf16 {%28, %29, %30, %31, %32, %33, %34, %35, %36, %37, %38, %39, %40, %41, %42, %43, %44, %45, %46, %47, %48, %49, %50, %51, %52, %53, %54, %55}, {%84, %85, %86, %87}, dx2, 1, 1, 1, 0;\n"
      "wgmma.mma_async.sync.aligned.m64n56k16.f32.bf16.bf16 {%28, %29, %30, %31, %32, %33, %34, %35, %36, %37, %38, %39, %40, %41, %42, %43, %44, %45, %46, %47, %48, %49, %50, %51, %52, %53, %54, %55}, {%88, %89, %90, %91}, dx3, 1, 1, 1, 0;\n"
      "wgmma.commit_group.sync.aligned;\n}\n"
      : "=f"(g[0]), "=f"(g[1]), "=f"(g[2]), "=f"(g[3]), "=f"(g[4]), "=f"(g[5]), "=f"(g[6]), "=f"(g[7]), "=f"(g[8]), "=f"(g[9]), "=f"(g[10]), "=f"(g[11]), "=f"(g[12]), "=f"(g[13]), "=f"(g[14]), "=f"(g[15]), "=f"(g[16]), "=f"(g[17]), "=f"(g[18]), "=f"(g[19]), "=f"(g[20]), "=f"(g[21]), "=f"(g[22]), "=f"(g[23]), "=f"(g[24]), "=f"(g[25]), "=f"(g[26]), "=f"(g[27]),
        "=f"(h[0]), "=f"(h[1]), "=f"(h[2]), "=f"(h[3]), "=f"(h[4]), "=f"(h[5]), "=f"(h[6]), "=f"(h[7]), "=f"(h[8]), "=f"(h[9]), "=f"(h[10]), "=f"(h[11]), "=f"(h[12]), "=f"(h[13]), "=f"(h[14]), "=f"(h[15]), "=f"(h[16]), "=f"(h[17]), "=f"(h[18]), "=f"(h[19]), "=f"(h[20]), "=f"(h[21]), "=f"(h[22]), "=f"(h[23]), "=f"(h[24]), "=f"(h[25]), "=f"(h[26]), "=f"(h[27])
      : "r"(w[0]), "r"(w[1]), "r"(w[2]), "r"(w[3]), "r"(w[4]), "r"(w[5]), "r"(w[6]), "r"(w[7]), "r"(w[8]), "r"(w[9]), "r"(w[10]), "r"(w[11]), "r"(w[12]), "r"(w[13]), "r"(w[14]), "r"(w[15]), "r"(w[16]), "r"(w[17]), "r"(w[18]), "r"(w[19]), "r"(w[20]), "r"(w[21]), "r"(w[22]), "r"(w[23]), "r"(w[24]), "r"(w[25]), "r"(w[26]), "r"(w[27]), "r"(w[28]), "r"(w[29]), "r"(w[30]), "r"(w[31]), "r"(w[32]), "r"(w[33]), "r"(w[34]), "r"(w[35]), "r"(w[36]), "r"(w[37]), "r"(w[38]), "r"(w[39]), "l"(dx), "l"(de), "l"(dh)
      : "memory");
  }
  static __device__ __forceinline__ void wait_g(float* g) {
    asm volatile("wgmma.wait_group.sync.aligned 1;\n"
      : "+f"(g[0]), "+f"(g[1]), "+f"(g[2]), "+f"(g[3]), "+f"(g[4]), "+f"(g[5]), "+f"(g[6]), "+f"(g[7]), "+f"(g[8]), "+f"(g[9]), "+f"(g[10]), "+f"(g[11]), "+f"(g[12]), "+f"(g[13]), "+f"(g[14]), "+f"(g[15]), "+f"(g[16]), "+f"(g[17]), "+f"(g[18]), "+f"(g[19]), "+f"(g[20]), "+f"(g[21]), "+f"(g[22]), "+f"(g[23]), "+f"(g[24]), "+f"(g[25]), "+f"(g[26]), "+f"(g[27])
      :: "memory");
  }
  static __device__ __forceinline__ void wait_h(float* h) {
    asm volatile("wgmma.wait_group.sync.aligned 0;\n"
      : "+f"(h[0]), "+f"(h[1]), "+f"(h[2]), "+f"(h[3]), "+f"(h[4]), "+f"(h[5]), "+f"(h[6]), "+f"(h[7]), "+f"(h[8]), "+f"(h[9]), "+f"(h[10]), "+f"(h[11]), "+f"(h[12]), "+f"(h[13]), "+f"(h[14]), "+f"(h[15]), "+f"(h[16]), "+f"(h[17]), "+f"(h[18]), "+f"(h[19]), "+f"(h[20]), "+f"(h[21]), "+f"(h[22]), "+f"(h[23]), "+f"(h[24]), "+f"(h[25]), "+f"(h[26]), "+f"(h[27])
      :: "memory");
  }
};
template<> struct TileMMA<8> {
  static __device__ __forceinline__ void issue(float* g, float* h, const uint32_t* w, uint64_t dx, uint64_t de, uint64_t dh, uint64_t dc) {
    asm volatile(
      "{\n.reg .b64 dx1, dx2, dx3;\n"
      "add.s64 dx1, %104, 2;\nadd.s64 dx2, %104, 4;\nadd.s64 dx3, %104, 6;\n"
      "wgmma.fence.sync.aligned;\n"
      "wgmma.mma_async.sync.aligned.m64n64k16.f32.bf16.bf16 {%0, %1, %2, %3, %4, %5, %6, %7, %8, %9, %10, %11, %12, %13, %14, %15, %16, %17, %18, %19, %20, %21, %22, %23, %24, %25, %26, %27, %28, %29, %30, %31}, {%100, %101, %102, %103}, %106, 0, 1, 1, 0;\n"
      "wgmma.mma_async.sync.aligned.m64n64k16.f32.bf16.bf16 {%0, %1, %2, %3, %4, %5, %6, %7, %8, %9, %10, %11, %12, %13, %14, %15, %16, %17, %18, %19, %20, %21, %22, %23, %24, %25, %26, %27, %28, %29, %30, %31}, {%80, %81, %82, %83}, %105, 1, 1, 1, 0;\n"
      "wgmma.mma_async.sync.aligned.m64n64k16.f32.bf16.bf16 {%0, %1, %2, %3, %4, %5, %6, %7, %8, %9, %10, %11, %12, %13, %14, %15, %16, %17, %18, %19, %20, %21, %22, %23, %24, %25, %26, %27, %28, %29, %30, %31}, {%64, %65, %66, %67}, %104, 1, 1, 1, 0;\n"
      "wgmma.mma_async.sync.aligned.m64n64k16.f32.bf16.bf16 {%0, %1, %2, %3, %4, %5, %6, %7, %8, %9, %10, %11, %12, %13, %14, %15, %16, %17, %18, %19, %20, %21, %22, %23, %24, %25, %26, %27, %28, %29, %30, %31}, {%68, %69, %70, %71}, dx1, 1, 1, 1, 0;\n"
      "wgmma.mma_async.sync.aligned.m64n64k16.f32.bf16.bf16 {%0, %1, %2, %3, %4, %5, %6, %7, %8, %9, %10, %11, %12, %13, %14, %15, %16, %17, %18, %19, %20, %21, %22, %23, %24, %25, %26, %27, %28, %29, %30, %31}, {%72, %73, %74, %75}, dx2, 1, 1, 1, 0;\n"
      "wgmma.mma_async.sync.aligned.m64n64k16.f32.bf16.bf16 {%0, %1, %2, %3, %4, %5, %6, %7, %8, %9, %10, %11, %12, %13, %14, %15, %16, %17, %18, %19, %20, %21, %22, %23, %24, %25, %26, %27, %28, %29, %30, %31}, {%76, %77, %78, %79}, dx3, 1, 1, 1, 0;\n"
      "wgmma.commit_group.sync.aligned;\n"
      "wgmma.mma_async.sync.aligned.m64n64k16.f32.bf16.bf16 {%32, %33, %34, %35, %36, %37, %38, %39, %40, %41, %42, %43, %44, %45, %46, %47, %48, %49, %50, %51, %52, %53, %54, %55, %56, %57, %58, %59, %60, %61, %62, %63}, {%84, %85, %86, %87}, %104, 0, 1, 1, 0;\n"
      "wgmma.mma_async.sync.aligned.m64n64k16.f32.bf16.bf16 {%32, %33, %34, %35, %36, %37, %38, %39, %40, %41, %42, %43, %44, %45, %46, %47, %48, %49, %50, %51, %52, %53, %54, %55, %56, %57, %58, %59, %60, %61, %62, %63}, {%88, %89, %90, %91}, dx1, 1, 1, 1, 0;\n"
      "wgmma.mma_async.sync.aligned.m64n64k16.f32.bf16.bf16 {%32, %33, %34, %35, %36, %37, %38, %39, %40, %41, %42, %43, %44, %45, %46, %47, %48, %49, %50, %51, %52, %53, %54, %55, %56, %57, %58, %59, %60, %61, %62, %63}, {%92, %93, %94, %95}, dx2, 1, 1, 1, 0;\n"
      "wgmma.mma_async.sync.aligned.m64n64k16.f32.bf16.bf16 {%32, %33, %34, %35, %36, %37, %38, %39, %40, %41, %42, %43, %44, %45, %46, %47, %48, %49, %50, %51, %52, %53, %54, %55, %56, %57, %58, %59, %60, %61, %62, %63}, {%96, %97, %98, %99}, dx3, 1, 1, 1, 0;\n"
      "wgmma.commit_group.sync.aligned;\n}\n"
      : "=f"(g[0]), "=f"(g[1]), "=f"(g[2]), "=f"(g[3]), "=f"(g[4]), "=f"(g[5]), "=f"(g[6]), "=f"(g[7]), "=f"(g[8]), "=f"(g[9]), "=f"(g[10]), "=f"(g[11]), "=f"(g[12]), "=f"(g[13]), "=f"(g[14]), "=f"(g[15]), "=f"(g[16]), "=f"(g[17]), "=f"(g[18]), "=f"(g[19]), "=f"(g[20]), "=f"(g[21]), "=f"(g[22]), "=f"(g[23]), "=f"(g[24]), "=f"(g[25]), "=f"(g[26]), "=f"(g[27]), "=f"(g[28]), "=f"(g[29]), "=f"(g[30]), "=f"(g[31]),
        "=f"(h[0]), "=f"(h[1]), "=f"(h[2]), "=f"(h[3]), "=f"(h[4]), "=f"(h[5]), "=f"(h[6]), "=f"(h[7]), "=f"(h[8]), "=f"(h[9]), "=f"(h[10]), "=f"(h[11]), "=f"(h[12]), "=f"(h[13]), "=f"(h[14]), "=f"(h[15]), "=f"(h[16]), "=f"(h[17]), "=f"(h[18]), "=f"(h[19]), "=f"(h[20]), "=f"(h[21]), "=f"(h[22]), "=f"(h[23]), "=f"(h[24]), "=f"(h[25]), "=f"(h[26]), "=f"(h[27]), "=f"(h[28]), "=f"(h[29]), "=f"(h[30]), "=f"(h[31])
      : "r"(w[0]), "r"(w[1]), "r"(w[2]), "r"(w[3]), "r"(w[4]), "r"(w[5]), "r"(w[6]), "r"(w[7]), "r"(w[8]), "r"(w[9]), "r"(w[10]), "r"(w[11]), "r"(w[12]), "r"(w[13]), "r"(w[14]), "r"(w[15]), "r"(w[16]), "r"(w[17]), "r"(w[18]), "r"(w[19]), "r"(w[20]), "r"(w[21]), "r"(w[22]), "r"(w[23]), "r"(w[24]), "r"(w[25]), "r"(w[26]), "r"(w[27]), "r"(w[28]), "r"(w[29]), "r"(w[30]), "r"(w[31]), "r"(w[32]), "r"(w[33]), "r"(w[34]), "r"(w[35]), "r"(w[36]), "r"(w[37]), "r"(w[38]), "r"(w[39]), "l"(dx), "l"(de), "l"(dh)
      : "memory");
  }
  static __device__ __forceinline__ void wait_g(float* g) {
    asm volatile("wgmma.wait_group.sync.aligned 1;\n"
      : "+f"(g[0]), "+f"(g[1]), "+f"(g[2]), "+f"(g[3]), "+f"(g[4]), "+f"(g[5]), "+f"(g[6]), "+f"(g[7]), "+f"(g[8]), "+f"(g[9]), "+f"(g[10]), "+f"(g[11]), "+f"(g[12]), "+f"(g[13]), "+f"(g[14]), "+f"(g[15]), "+f"(g[16]), "+f"(g[17]), "+f"(g[18]), "+f"(g[19]), "+f"(g[20]), "+f"(g[21]), "+f"(g[22]), "+f"(g[23]), "+f"(g[24]), "+f"(g[25]), "+f"(g[26]), "+f"(g[27]), "+f"(g[28]), "+f"(g[29]), "+f"(g[30]), "+f"(g[31])
      :: "memory");
  }
  static __device__ __forceinline__ void wait_h(float* h) {
    asm volatile("wgmma.wait_group.sync.aligned 0;\n"
      : "+f"(h[0]), "+f"(h[1]), "+f"(h[2]), "+f"(h[3]), "+f"(h[4]), "+f"(h[5]), "+f"(h[6]), "+f"(h[7]), "+f"(h[8]), "+f"(h[9]), "+f"(h[10]), "+f"(h[11]), "+f"(h[12]), "+f"(h[13]), "+f"(h[14]), "+f"(h[15]), "+f"(h[16]), "+f"(h[17]), "+f"(h[18]), "+f"(h[19]), "+f"(h[20]), "+f"(h[21]), "+f"(h[22]), "+f"(h[23]), "+f"(h[24]), "+f"(h[25]), "+f"(h[26]), "+f"(h[27]), "+f"(h[28]), "+f"(h[29]), "+f"(h[30]), "+f"(h[31])
      :: "memory");
  }
};
template<> struct TileMMA<9> {
  static __device__ __forceinline__ void issue(float* g, float* h, const uint32_t* w, uint64_t dx, uint64_t de, uint64_t dh, uint64_t dc) {
    asm volatile(
      "{\n.reg .b64 dx1, dx2, dx3;\n"
      "add.s64 dx1, %112, 2;\nadd.s64 dx2, %112, 4;\nadd.s64 dx3, %112, 6;\n"
      "wgmma.fence.sync.aligned;\n"
      "wgmma.mma_async.sync.aligned.m64n72k16.f32.bf16.bf16 {%0, %1, %2, %3, %4, %5, %6, %7, %8, %9, %10, %11, %12, %13, %14, %15, %16, %17, %18, %19, %20, %21, %22, %23, %24, %25, %26, %27, %28, %29, %30, %31, %32, %33, %34, %35}, {%108, %109, %110, %111}, %114, 0, 1, 1, 0;\n"
      "wgmma.mma_async.sync.aligned.m64n72k16.f32.bf16.bf16 {%0, %1, %2, %3, %4, %5, %6, %7, %8, %9, %10, %11, %12, %13, %14, %15, %16, %17, %18, %19, %20, %21, %22, %23, %24, %25, %26, %27, %28, %29, %30, %31, %32, %33, %34, %35}, {%88, %89, %90, %91}, %113, 1, 1, 1, 0;\n"
      "wgmma.mma_async.sync.aligned.m64n72k16.f32.bf16.bf16 {%0, %1, %2, %3, %4, %5, %6, %7, %8, %9, %10, %11, %12, %13, %14, %15, %16, %17, %18, %19, %20, %21, %22, %23, %24, %25, %26, %27, %28, %29, %30, %31, %32, %33, %34, %35}, {%72, %73, %74, %75}, %112, 1, 1, 1, 0;\n"
      "wgmma.mma_async.sync.aligned.m64n72k16.f32.bf16.bf16 {%0, %1, %2, %3, %4, %5, %6, %7, %8, %9, %10, %11, %12, %13, %14, %15, %16, %17, %18, %19, %20, %21, %22, %23, %24, %25, %26, %27, %28, %29, %30, %31, %32, %33, %34, %35}, {%76, %77, %78, %79}, dx1, 1, 1, 1, 0;\n"
      "wgmma.mma_async.sync.aligned.m64n72k16.f32.bf16.bf16 {%0, %1, %2, %3, %4, %5, %6, %7, %8, %9, %10, %11, %12, %13, %14, %15, %16, %17, %18, %19, %20, %21, %22, %23, %24, %25, %26, %27, %28, %29, %30, %31, %32, %33, %34, %35}, {%80, %81, %82, %83}, dx2, 1, 1, 1, 0;\n"
      "wgmma.mma_async.sync.aligned.m64n72k16.f32.bf16.bf16 {%0, %1, %2, %3, %4, %5, %6, %7, %8, %9, %10, %11, %12, %13, %14, %15, %16, %17, %18, %19, %20, %21, %22, %23, %24, %25, %26, %27, %28, %29, %30, %31, %32, %33, %34, %35}, {%84, %85, %86, %87}, dx3, 1, 1, 1, 0;\n"
      "wgmma.commit_group.sync.aligned;\n"
      "wgmma.mma_async.sync.aligned.m64n72k16.f32.bf16.bf16 {%36, %37, %38, %39, %40, %41, %42, %43, %44, %45, %46, %47, %48, %49, %50, %51, %52, %53, %54, %55, %56, %57, %58, %59, %60, %61, %62, %63, %64, %65, %66, %67, %68, %69, %70, %71}, {%92, %93, %94, %95}, %112, 0, 1, 1, 0;\n"
      "wgmma.mma_async.sync.aligned.m64n72k16.f32.bf16.bf16 {%36, %37, %38, %39, %40, %41, %42, %43, %44, %45, %46, %47, %48, %49, %50, %51, %52, %53, %54, %55, %56, %57, %58, %59, %60, %61, %62, %63, %64, %65, %66, %67, %68, %69, %70, %71}, {%96, %97, %98, %99}, dx1, 1, 1, 1, 0;\n"
      "wgmma.mma_async.sync.aligned.m64n72k16.f32.bf16.bf16 {%36, %37, %38, %39, %40, %41, %42, %43, %44, %45, %46, %47, %48, %49, %50, %51, %52, %53, %54, %55, %56, %57, %58, %59, %60, %61, %62, %63, %64, %65, %66, %67, %68, %69, %70, %71}, {%100, %101, %102, %103}, dx2, 1, 1, 1, 0;\n"
      "wgmma.mma_async.sync.aligned.m64n72k16.f32.bf16.bf16 {%36, %37, %38, %39, %40, %41, %42, %43, %44, %45, %46, %47, %48, %49, %50, %51, %52, %53, %54, %55, %56, %57, %58, %59, %60, %61, %62, %63, %64, %65, %66, %67, %68, %69, %70, %71}, {%104, %105, %106, %107}, dx3, 1, 1, 1, 0;\n"
      "wgmma.commit_group.sync.aligned;\n}\n"
      : "=f"(g[0]), "=f"(g[1]), "=f"(g[2]), "=f"(g[3]), "=f"(g[4]), "=f"(g[5]), "=f"(g[6]), "=f"(g[7]), "=f"(g[8]), "=f"(g[9]), "=f"(g[10]), "=f"(g[11]), "=f"(g[12]), "=f"(g[13]), "=f"(g[14]), "=f"(g[15]), "=f"(g[16]), "=f"(g[17]), "=f"(g[18]), "=f"(g[19]), "=f"(g[20]), "=f"(g[21]), "=f"(g[22]), "=f"(g[23]), "=f"(g[24]), "=f"(g[25]), "=f"(g[26]), "=f"(g[27]), "=f"(g[28]), "=f"(g[29]), "=f"(g[30]), "=f"(g[31]), "=f"(g[32]), "=f"(g[33]), "=f"(g[34]), "=f"(g[35]),
        "=f"(h[0]), "=f"(h[1]), "=f"(h[2]), "=f"(h[3]), "=f"(h[4]), "=f"(h[5]), "=f"(h[6]), "=f"(h[7]), "=f"(h[8]), "=f"(h[9]), "=f"(h[10]), "=f"(h[11]), "=f"(h[12]), "=f"(h[13]), "=f"(h[14]), "=f"(h[15]), "=f"(h[16]), "=f"(h[17]), "=f"(h[18]), "=f"(h[19]), "=f"(h[20]), "=f"(h[21]), "=f"(h[22]), "=f"(h[23]), "=f"(h[24]), "=f"(h[25]), "=f"(h[26]), "=f"(h[27]), "=f"(h[28]), "=f"(h[29]), "=f"(h[30]), "=f"(h[31]), "=f"(h[32]), "=f"(h[33]), "=f"(h[34]), "=f"(h[35])
      : "r"(w[0]), "r"(w[1]), "r"(w[2]), "r"(w[3]), "r"(w[4]), "r"(w[5]), "r"(w[6]), "r"(w[7]), "r"(w[8]), "r"(w[9]), "r"(w[10]), "r"(w[11]), "r"(w[12]), "r"(w[13]), "r"(w[14]), "r"(w[15]), "r"(w[16]), "r"(w[17]), "r"(w[18]), "r"(w[19]), "r"(w[20]), "r"(w[21]), "r"(w[22]), "r"(w[23]), "r"(w[24]), "r"(w[25]), "r"(w[26]), "r"(w[27]), "r"(w[28]), "r"(w[29]), "r"(w[30]), "r"(w[31]), "r"(w[32]), "r"(w[33]), "r"(w[34]), "r"(w[35]), "r"(w[36]), "r"(w[37]), "r"(w[38]), "r"(w[39]), "l"(dx), "l"(de), "l"(dh)
      : "memory");
  }
  static __device__ __forceinline__ void wait_g(float* g) {
    asm volatile("wgmma.wait_group.sync.aligned 1;\n"
      : "+f"(g[0]), "+f"(g[1]), "+f"(g[2]), "+f"(g[3]), "+f"(g[4]), "+f"(g[5]), "+f"(g[6]), "+f"(g[7]), "+f"(g[8]), "+f"(g[9]), "+f"(g[10]), "+f"(g[11]), "+f"(g[12]), "+f"(g[13]), "+f"(g[14]), "+f"(g[15]), "+f"(g[16]), "+f"(g[17]), "+f"(g[18]), "+f"(g[19]), "+f"(g[20]), "+f"(g[21]), "+f"(g[22]), "+f"(g[23]), "+f"(g[24]), "+f"(g[25]), "+f"(g[26]), "+f"(g[27]), "+f"(g[28]), "+f"(g[29]), "+f"(g[30]), "+f"(g[31]), "+f"(g[32]), "+f"(g[33]), "+f"(g[34]), "+f"(g[35])
      :: "memory");
  }
  static __device__ __forceinline__ void wait_h(float* h) {
    asm volatile("wgmma.wait_group.sync.aligned 0;\n"
      : "+f"(h[0]), "+f"(h[1]), "+f"(h[2]), "+f"(h[3]), "+f"(h[4]), "+f"(h[5]), "+f"(h[6]), "+f"(h[7]), "+f"(h[8]), "+f"(h[9]), "+f"(h[10]), "+f"(h[11]), "+f"(h[12]), "+f"(h[13]), "+f"(h[14]), "+f"(h[15]), "+f"(h[16]), "+f"(h[17]), "+f"(h[18]), "+f"(h[19]), "+f"(h[20]), "+f"(h[21]), "+f"(h[22]), "+f"(h[23]), "+f"(h[24]), "+f"(h[25]), "+f"(h[26]), "+f"(h[27]), "+f"(h[28]), "+f"(h[29]), "+f"(h[30]), "+f"(h[31]), "+f"(h[32]), "+f"(h[33]), "+f"(h[34]), "+f"(h[35])
      :: "memory");
  }
};
template<> struct TileMMA<10> {
  static __device__ __forceinline__ void issue(float* g, float* h, const uint32_t* w, uint64_t dx, uint64_t de, uint64_t dh, uint64_t dc) {
    asm volatile(
      "{\n.reg .b64 dx1, dx2, dx3;\n"
      "add.s64 dx1, %120, 2;\nadd.s64 dx2, %120, 4;\nadd.s64 dx3, %120, 6;\n"
      "wgmma.fence.sync.aligned;\n"
      "wgmma.mma_async.sync.aligned.m64n80k16.f32.bf16.bf16 {%0, %1, %2, %3, %4, %5, %6, %7, %8, %9, %10, %11, %12, %13, %14, %15, %16, %17, %18, %19, %20, %21, %22, %23, %24, %25, %26, %27, %28, %29, %30, %31, %32, %33, %34, %35, %36, %37, %38, %39}, {%116, %117, %118, %119}, %122, 0, 1, 1, 0;\n"
      "wgmma.mma_async.sync.aligned.m64n80k16.f32.bf16.bf16 {%0, %1, %2, %3, %4, %5, %6, %7, %8, %9, %10, %11, %12, %13, %14, %15, %16, %17, %18, %19, %20, %21, %22, %23, %24, %25, %26, %27, %28, %29, %30, %31, %32, %33, %34, %35, %36, %37, %38, %39}, {%96, %97, %98, %99}, %121, 1, 1, 1, 0;\n"
      "wgmma.mma_async.sync.aligned.m64n80k16.f32.bf16.bf16 {%0, %1, %2, %3, %4, %5, %6, %7, %8, %9, %10, %11, %12, %13, %14, %15, %16, %17, %18, %19, %20, %21, %22, %23, %24, %25, %26, %27, %28, %29, %30, %31, %32, %33, %34, %35, %36, %37, %38, %39}, {%80, %81, %82, %83}, %120, 1, 1, 1, 0;\n"
      "wgmma.mma_async.sync.aligned.m64n80k16.f32.bf16.bf16 {%0, %1, %2, %3, %4, %5, %6, %7, %8, %9, %10, %11, %12, %13, %14, %15, %16, %17, %18, %19, %20, %21, %22, %23, %24, %25, %26, %27, %28, %29, %30, %31, %32, %33, %34, %35, %36, %37, %38, %39}, {%84, %85, %86, %87}, dx1, 1, 1, 1, 0;\n"
      "wgmma.mma_async.sync.aligned.m64n80k16.f32.bf16.bf16 {%0, %1, %2, %3, %4, %5, %6, %7, %8, %9, %10, %11, %12, %13, %14, %15, %16, %17, %18, %19, %20, %21, %22, %23, %24, %25, %26, %27, %28, %29, %30, %31, %32, %33, %34, %35, %36, %37, %38, %39}, {%88, %89, %90, %91}, dx2, 1, 1, 1, 0;\n"
      "wgmma.mma_async.sync.aligned.m64n80k16.f32.bf16.bf16 {%0, %1, %2, %3, %4, %5, %6, %7, %8, %9, %10, %11, %12, %13, %14, %15, %16, %17, %18, %19, %20, %21, %22, %23, %24, %25, %26, %27, %28, %29, %30, %31, %32, %33, %34, %35, %36, %37, %38, %39}, {%92, %93, %94, %95}, dx3, 1, 1, 1, 0;\n"
      "wgmma.commit_group.sync.aligned;\n"
      "wgmma.mma_async.sync.aligned.m64n80k16.f32.bf16.bf16 {%40, %41, %42, %43, %44, %45, %46, %47, %48, %49, %50, %51, %52, %53, %54, %55, %56, %57, %58, %59, %60, %61, %62, %63, %64, %65, %66, %67, %68, %69, %70, %71, %72, %73, %74, %75, %76, %77, %78, %79}, {%100, %101, %102, %103}, %120, 0, 1, 1, 0;\n"
      "wgmma.mma_async.sync.aligned.m64n80k16.f32.bf16.bf16 {%40, %41, %42, %43, %44, %45, %46, %47, %48, %49, %50, %51, %52, %53, %54, %55, %56, %57, %58, %59, %60, %61, %62, %63, %64, %65, %66, %67, %68, %69, %70, %71, %72, %73, %74, %75, %76, %77, %78, %79}, {%104, %105, %106, %107}, dx1, 1, 1, 1, 0;\n"
      "wgmma.mma_async.sync.aligned.m64n80k16.f32.bf16.bf16 {%40, %41, %42, %43, %44, %45, %46, %47, %48, %49, %50, %51, %52, %53, %54, %55, %56, %57, %58, %59, %60, %61, %62, %63, %64, %65, %66, %67, %68, %69, %70, %71, %72, %73, %74, %75, %76, %77, %78, %79}, {%108, %109, %110, %111}, dx2, 1, 1, 1, 0;\n"
      "wgmma.mma_async.sync.aligned.m64n80k16.f32.bf16.bf16 {%40, %41, %42, %43, %44, %45, %46, %47, %48, %49, %50, %51, %52, %53, %54, %55, %56, %57, %58, %59, %60, %61, %62, %63, %64, %65, %66, %67, %68, %69, %70, %71, %72, %73, %74, %75, %76, %77, %78, %79}, {%112, %113, %114, %115}, dx3, 1, 1, 1, 0;\n"
      "wgmma.commit_group.sync.aligned;\n}\n"
      : "=f"(g[0]), "=f"(g[1]), "=f"(g[2]), "=f"(g[3]), "=f"(g[4]), "=f"(g[5]), "=f"(g[6]), "=f"(g[7]), "=f"(g[8]), "=f"(g[9]), "=f"(g[10]), "=f"(g[11]), "=f"(g[12]), "=f"(g[13]), "=f"(g[14]), "=f"(g[15]), "=f"(g[16]), "=f"(g[17]), "=f"(g[18]), "=f"(g[19]), "=f"(g[20]), "=f"(g[21]), "=f"(g[22]), "=f"(g[23]), "=f"(g[24]), "=f"(g[25]), "=f"(g[26]), "=f"(g[27]), "=f"(g[28]), "=f"(g[29]), "=f"(g[30]), "=f"(g[31]), "=f"(g[32]), "=f"(g[33]), "=f"(g[34]), "=f"(g[35]), "=f"(g[36]), "=f"(g[37]), "=f"(g[38]), "=f"(g[39]),
        "=f"(h[0]), "=f"(h[1]), "=f"(h[2]), "=f"(h[3]), "=f"(h[4]), "=f"(h[5]), "=f"(h[6]), "=f"(h[7]), "=f"(h[8]), "=f"(h[9]), "=f"(h[10]), "=f"(h[11]), "=f"(h[12]), "=f"(h[13]), "=f"(h[14]), "=f"(h[15]), "=f"(h[16]), "=f"(h[17]), "=f"(h[18]), "=f"(h[19]), "=f"(h[20]), "=f"(h[21]), "=f"(h[22]), "=f"(h[23]), "=f"(h[24]), "=f"(h[25]), "=f"(h[26]), "=f"(h[27]), "=f"(h[28]), "=f"(h[29]), "=f"(h[30]), "=f"(h[31]), "=f"(h[32]), "=f"(h[33]), "=f"(h[34]), "=f"(h[35]), "=f"(h[36]), "=f"(h[37]), "=f"(h[38]), "=f"(h[39])
      : "r"(w[0]), "r"(w[1]), "r"(w[2]), "r"(w[3]), "r"(w[4]), "r"(w[5]), "r"(w[6]), "r"(w[7]), "r"(w[8]), "r"(w[9]), "r"(w[10]), "r"(w[11]), "r"(w[12]), "r"(w[13]), "r"(w[14]), "r"(w[15]), "r"(w[16]), "r"(w[17]), "r"(w[18]), "r"(w[19]), "r"(w[20]), "r"(w[21]), "r"(w[22]), "r"(w[23]), "r"(w[24]), "r"(w[25]), "r"(w[26]), "r"(w[27]), "r"(w[28]), "r"(w[29]), "r"(w[30]), "r"(w[31]), "r"(w[32]), "r"(w[33]), "r"(w[34]), "r"(w[35]), "r"(w[36]), "r"(w[37]), "r"(w[38]), "r"(w[39]), "l"(dx), "l"(de), "l"(dh)
      : "memory");
  }
  static __device__ __forceinline__ void wait_g(float* g) {
    asm volatile("wgmma.wait_group.sync.aligned 1;\n"
      : "+f"(g[0]), "+f"(g[1]), "+f"(g[2]), "+f"(g[3]), "+f"(g[4]), "+f"(g[5]), "+f"(g[6]), "+f"(g[7]), "+f"(g[8]), "+f"(g[9]), "+f"(g[10]), "+f"(g[11]), "+f"(g[12]), "+f"(g[13]), "+f"(g[14]), "+f"(g[15]), "+f"(g[16]), "+f"(g[17]), "+f"(g[18]), "+f"(g[19]), "+f"(g[20]), "+f"(g[21]), "+f"(g[22]), "+f"(g[23]), "+f"(g[24]), "+f"(g[25]), "+f"(g[26]), "+f"(g[27]), "+f"(g[28]), "+f"(g[29]), "+f"(g[30]), "+f"(g[31]), "+f"(g[32]), "+f"(g[33]), "+f"(g[34]), "+f"(g[35]), "+f"(g[36]), "+f"(g[37]), "+f"(g[38]), "+f"(g[39])
      :: "memory");
  }
  static __device__ __forceinline__ void wait_h(float* h) {
    asm volatile("wgmma.wait_group.sync.aligned 0;\n"
      : "+f"(h[0]), "+f"(h[1]), "+f"(h[2]), "+f"(h[3]), "+f"(h[4]), "+f"(h[5]), "+f"(h[6]), "+f"(h[7]), "+f"(h[8]), "+f"(h[9]), "+f"(h[10]), "+f"(h[11]), "+f"(h[12]), "+f"(h[13]), "+f"(h[14]), "+f"(h[15]), "+f"(h[16]), "+f"(h[17]), "+f"(h[18]), "+f"(h[19]), "+f"(h[20]), "+f"(h[21]), "+f"(h[22]), "+f"(h[23]), "+f"(h[24]), "+f"(h[25]), "+f"(h[26]), "+f"(h[27]), "+f"(h[28]), "+f"(h[29]), "+f"(h[30]), "+f"(h[31]), "+f"(h[32]), "+f"(h[33]), "+f"(h[34]), "+f"(h[35]), "+f"(h[36]), "+f"(h[37]), "+f"(h[38]), "+f"(h[39])
      :: "memory");
  }
};
template<> struct TileMMA<11> {
  static __device__ __forceinline__ void issue(float* g, float* h, const uint32_t* w, uint64_t dx, uint64_t de, uint64_t dh, uint64_t dc) {
    asm volatile(
      "{\n.reg .b64 dx1, dx2, dx3;\n"
      "add.s64 dx1, %124, 2;\nadd.s64 dx2, %124, 4;\nadd.s64 dx3, %124, 6;\n"
      "wgmma.fence.sync.aligned;\n"
      "wgmma.mma_async.sync.aligned.m64n88k16.f32.bf16.bf16 {%0, %1, %2, %3, %4, %5, %6, %7, %8, %9, %10, %11, %12, %13, %14, %15, %16, %17, %18, %19, %20, %21, %22, %23, %24, %25, %26, %27, %28, %29, %30, %31, %32, %33, %34, %35, %36, %37, %38, %39, %40, %41, %42, %43}, {%120, %121, %122, %123}, %126, 0, 1, 1, 0;\n"
      "wgmma.mma_async.sync.aligned.m64n88k16.f32.bf16.bf16 {%0, %1, %2, %3, %4, %5, %6, %7, %8, %9, %10, %11, %12, %13, %14, %15, %16, %17, %18, %19, %20, %21, %22, %23, %24, %25, %26, %27, %28, %29, %30, %31, %32, %33, %34, %35, %36, %37, %38, %39, %40, %41, %42, %43}, %127, %125, 1, 1, 1, 0, 0;\n"
      "wgmma.mma_async.sync.aligned.m64n88k16.f32.bf16.bf16 {%0, %1, %2, %3, %4, %5, %6, %7, %8, %9, %10, %11, %12, %13, %14, %15, %16, %17, %18, %19, %20, %21, %22, %23, %24, %25, %26, %27, %28, %29, %30, %31, %32, %33, %34, %35, %36, %37, %38, %39, %40, %41, %42, %43}, {%88, %89, %90, %91}, %124, 1, 1, 1, 0;\n"
      "wgmma.mma_async.sync.aligned.m64n88k16.f32.bf16.bf16 {%0, %1, %2, %3, %4, %5, %6, %7, %8, %9, %10, %11, %12, %13, %14, %15, %16, %17, %18, %19, %20, %21, %22, %23, %24, %25, %26, %27, %28, %29, %30, %31, %32, %33, %34, %35, %36, %37, %38, %39, %40, %41, %42, %43}, {%92, %93, %94, %95}, dx1, 1, 1, 1, 0;\n"
      "wgmma.mma_async.sync.aligned.m64n88k16.f32.bf16.bf16 {%0, %1, %2, %3, %4, %5, %6, %7, %8, %9, %10, %11, %12, %13, %14, %15, %16, %17, %18, %19, %20, %21, %22, %23, %24, %25, %26, %27, %28, %29, %30, %31, %32, %33, %34, %35, %36, %37, %38, %39, %40, %41, %42, %43}, {%96, %97, %98, %99}, dx2, 1, 1, 1, 0;\n"
      "wgmma.mma_async.sync.aligned.m64n88k16.f32.bf16.bf16 {%0, %1, %2, %3, %4, %5, %6, %7, %8, %9, %10, %11, %12, %13, %14, %15, %16, %17, %18, %19, %20, %21, %22, %23, %24, %25, %26, %27, %28, %29, %30, %31, %32, %33, %34, %35, %36, %37, %38, %39, %40, %41, %42, %43}, {%100, %101, %102, %103}, dx3, 1, 1, 1, 0;\n"
      "wgmma.commit_group.sync.aligned;\n"
      "wgmma.mma_async.sync.aligned.m64n88k16.f32.bf16.bf16 {%44, %45, %46, %47, %48, %49, %50, %51, %52, %53, %54, %55, %56, %57, %58, %59, %60, %61, %62, %63, %64, %65, %66, %67, %68, %69, %70, %71, %72, %73, %74, %75, %76, %77, %78, %79, %80, %81, %82, %83, %84, %85, %86, %87}, {%104, %105, %106, %107}, %124, 0, 1, 1, 0;\n"
      "wgmma.mma_async.sync.aligned.m64n88k16.f32.bf16.bf16 {%44, %45, %46, %47, %48, %49, %50, %51, %52, %53, %54, %55, %56, %57, %58, %59, %60, %61, %62, %63, %64, %65, %66, %67, %68, %69, %70, %71, %72, %73, %74, %75, %76, %77, %78, %79, %80, %81, %82, %83, %84, %85, %86, %87}, {%108, %109, %110, %111}, dx1, 1, 1, 1, 0;\n"
      "wgmma.mma_async.sync.aligned.m64n88k16.f32.bf16.bf16 {%44, %45, %46, %47, %48, %49, %50, %51, %52, %53, %54, %55, %56, %57, %58, %59, %60, %61, %62, %63, %64, %65, %66, %67, %68, %69, %70, %71, %72, %73, %74, %75, %76, %77, %78, %79, %80, %81, %82, %83, %84, %85, %86, %87}, {%112, %113, %114, %115}, dx2, 1, 1, 1, 0;\n"
      "wgmma.mma_async.sync.aligned.m64n88k16.f32.bf16.bf16 {%44, %45, %46, %47, %48, %49, %50, %51, %52, %53, %54, %55, %56, %57, %58, %59, %60, %61, %62, %63, %64, %65, %66, %67, %68, %69, %70, %71, %72, %73, %74, %75, %76, %77, %78, %79, %80, %81, %82, %83, %84, %85, %86, %87}, {%116, %117, %118, %119}, dx3, 1, 1, 1, 0;\n"
      "wgmma.commit_group.sync.aligned;\n}\n"
      : "=f"(g[0]), "=f"(g[1]), "=f"(g[2]), "=f"(g[3]), "=f"(g[4]), "=f"(g[5]), "=f"(g[6]), "=f"(g[7]), "=f"(g[8]), "=f"(g[9]), "=f"(g[10]), "=f"(g[11]), "=f"(g[12]), "=f"(g[13]), "=f"(g[14]), "=f"(g[15]), "=f"(g[16]), "=f"(g[17]), "=f"(g[18]), "=f"(g[19]), "=f"(g[20]), "=f"(g[21]), "=f"(g[22]), "=f"(g[23]), "=f"(g[24]), "=f"(g[25]), "=f"(g[26]), "=f"(g[27]), "=f"(g[28]), "=f"(g[29]), "=f"(g[30]), "=f"(g[31]), "=f"(g[32]), "=f"(g[33]), "=f"(g[34]), "=f"(g[35]), "=f"(g[36]), "=f"(g[37]), "=f"(g[38]), "=f"(g[39]), "=f"(g[40]), "=f"(g[41]), "=f"(g[42]), "=f"(g[43]),
        "=f"(h[0]), "=f"(h[1]), "=f"(h[2]), "=f"(h[3]), "=f"(h[4]), "=f"(h[5]), "=f"(h[6]), "=f"(h[7]), "=f"(h[8]), "=f"(h[9]), "=f"(h[10]), "=f"(h[11]), "=f"(h[12]), "=f"(h[13]), "=f"(h[14]), "=f"(h[15]), "=f"(h[16]), "=f"(h[17]), "=f"(h[18]), "=f"(h[19]), "=f"(h[20]), "=f"(h[21]), "=f"(h[22]), "=f"(h[23]), "=f"(h[24]), "=f"(h[25]), "=f"(h[26]), "=f"(h[27]), "=f"(h[28]), "=f"(h[29]), "=f"(h[30]), "=f"(h[31]), "=f"(h[32]), "=f"(h[33]), "=f"(h[34]), "=f"(h[35]), "=f"(h[36]), "=f"(h[37]), "=f"(h[38]), "=f"(h[39]), "=f"(h[40]), "=f"(h[41]), "=f"(h[42]), "=f"(h[43])
      : "r"(w[0]), "r"(w[1]), "r"(w[2]), "r"(w[3]), "r"(w[4]), "r"(w[5]), "r"(w[6]), "r"(w[7]), "r"(w[8]), "r"(w[9]), "r"(w[10]), "r"(w[11]), "r"(w[12]), "r"(w[13]), "r"(w[14]), "r"(w[15]), "r"(w[20]), "r"(w[21]), "r"(w[22]), "r"(w[23]), "r"(w[24]), "r"(w[25]), "r"(w[26]), "r"(w[27]), "r"(w[28]), "r"(w[29]), "r"(w[30]), "r"(w[31]), "r"(w[32]), "r"(w[33]), "r"(w[34]), "r"(w[35]), "r"(w[36]), "r"(w[37]), "r"(w[38]), "r"(w[39]), "l"(dx), "l"(de), "l"(dh), "l"(dc)
      : "memory");
  }
  static __device__ __forceinline__ void wait_g(float* g) {
    asm volatile("wgmma.wait_group.sync.aligned 1;\n"
      : "+f"(g[0]), "+f"(g[1]), "+f"(g[2]), "+f"(g[3]), "+f"(g[4]), "+f"(g[5]), "+f"(g[6]), "+f"(g[7]), "+f"(g[8]), "+f"(g[9]), "+f"(g[10]), "+f"(g[11]), "+f"(g[12]), "+f"(g[13]), "+f"(g[14]), "+f"(g[15]), "+f"(g[16]), "+f"(g[17]), "+f"(g[18]), "+f"(g[19]), "+f"(g[20]), "+f"(g[21]), "+f"(g[22]), "+f"(g[23]), "+f"(g[24]), "+f"(g[25]), "+f"(g[26]), "+f"(g[27]), "+f"(g[28]), "+f"(g[29]), "+f"(g[30]), "+f"(g[31]), "+f"(g[32]), "+f"(g[33]), "+f"(g[34]), "+f"(g[35]), "+f"(g[36]), "+f"(g[37]), "+f"(g[38]), "+f"(g[39]), "+f"(g[40]), "+f"(g[41]), "+f"(g[42]), "+f"(g[43])
      :: "memory");
  }
  static __device__ __forceinline__ void wait_h(float* h) {
    asm volatile("wgmma.wait_group.sync.aligned 0;\n"
      : "+f"(h[0]), "+f"(h[1]), "+f"(h[2]), "+f"(h[3]), "+f"(h[4]), "+f"(h[5]), "+f"(h[6]), "+f"(h[7]), "+f"(h[8]), "+f"(h[9]), "+f"(h[10]), "+f"(h[11]), "+f"(h[12]), "+f"(h[13]), "+f"(h[14]), "+f"(h[15]), "+f"(h[16]), "+f"(h[17]), "+f"(h[18]), "+f"(h[19]), "+f"(h[20]), "+f"(h[21]), "+f"(h[22]), "+f"(h[23]), "+f"(h[24]), "+f"(h[25]), "+f"(h[26]), "+f"(h[27]), "+f"(h[28]), "+f"(h[29]), "+f"(h[30]), "+f"(h[31]), "+f"(h[32]), "+f"(h[33]), "+f"(h[34]), "+f"(h[35]), "+f"(h[36]), "+f"(h[37]), "+f"(h[38]), "+f"(h[39]), "+f"(h[40]), "+f"(h[41]), "+f"(h[42]), "+f"(h[43])
      :: "memory");
  }
};
__device__ __forceinline__ void node_mma2(float* u, float* a, const uint32_t* w, uint64_t dx) {
    asm volatile(
      "{\n.reg .b64 dx1, dx2, dx3, dy0, dy1, dy2, dy3;\n"
      "add.s64 dx1, %80, 2;\nadd.s64 dx2, %80, 4;\nadd.s64 dx3, %80, 6;\n"
      "add.s64 dy0, %80, 512;\nadd.s64 dy1, %80, 514;\nadd.s64 dy2, %80, 516;\nadd.s64 dy3, %80, 518;\n"
      "wgmma.fence.sync.aligned;\n"
      "wgmma.mma_async.sync.aligned.m64n64k16.f32.bf16.bf16 {%0, %1, %2, %3, %4, %5, %6, %7, %8, %9, %10, %11, %12, %13, %14, %15, %16, %17, %18, %19, %20, %21, %22, %23, %24, %25, %26, %27, %28, %29, %30, %31}, {%64, %65, %66, %67}, %80, 0, 1, 1, 0;\n"
      "wgmma.mma_async.sync.aligned.m64n64k16.f32.bf16.bf16 {%0, %1, %2, %3, %4, %5, %6, %7, %8, %9, %10, %11, %12, %13, %14, %15, %16, %17, %18, %19, %20, %21, %22, %23, %24, %25, %26, %27, %28, %29, %30, %31}, {%68, %69, %70, %71}, dx1, 1, 1, 1, 0;\n"
      "wgmma.mma_async.sync.aligned.m64n64k16.f32.bf16.bf16 {%0, %1, %2, %3, %4, %5, %6, %7, %8, %9, %10, %11, %12, %13, %14, %15, %16, %17, %18, %19, %20, %21, %22, %23, %24, %25, %26, %27, %28, %29, %30, %31}, {%72, %73, %74, %75}, dx2, 1, 1, 1, 0;\n"
      "wgmma.mma_async.sync.aligned.m64n64k16.f32.bf16.bf16 {%0, %1, %2, %3, %4, %5, %6, %7, %8, %9, %10, %11, %12, %13, %14, %15, %16, %17, %18, %19, %20, %21, %22, %23, %24, %25, %26, %27, %28, %29, %30, %31}, {%76, %77, %78, %79}, dx3, 1, 1, 1, 0;\n"
      "wgmma.commit_group.sync.aligned;\n"
      "wgmma.mma_async.sync.aligned.m64n64k16.f32.bf16.bf16 {%32, %33, %34, %35, %36, %37, %38, %39, %40, %41, %42, %43, %44, %45, %46, %47, %48, %49, %50, %51, %52, %53, %54, %55, %56, %57, %58, %59, %60, %61, %62, %63}, {%64, %65, %66, %67}, dy0, 0, 1, 1, 0;\n"
      "wgmma.mma_async.sync.aligned.m64n64k16.f32.bf16.bf16 {%32, %33, %34, %35, %36, %37, %38, %39, %40, %41, %42, %43, %44, %45, %46, %47, %48, %49, %50, %51, %52, %53, %54, %55, %56, %57, %58, %59, %60, %61, %62, %63}, {%68, %69, %70, %71}, dy1, 1, 1, 1, 0;\n"
      "wgmma.mma_async.sync.aligned.m64n64k16.f32.bf16.bf16 {%32, %33, %34, %35, %36, %37, %38, %39, %40, %41, %42, %43, %44, %45, %46, %47, %48, %49, %50, %51, %52, %53, %54, %55, %56, %57, %58, %59, %60, %61, %62, %63}, {%72, %73, %74, %75}, dy2, 1, 1, 1, 0;\n"
      "wgmma.mma_async.sync.aligned.m64n64k16.f32.bf16.bf16 {%32, %33, %34, %35, %36, %37, %38, %39, %40, %41, %42, %43, %44, %45, %46, %47, %48, %49, %50, %51, %52, %53, %54, %55, %56, %57, %58, %59, %60, %61, %62, %63}, {%76, %77, %78, %79}, dy3, 1, 1, 1, 0;\n"
      "wgmma.commit_group.sync.aligned;\n}\n"
      : "=f"(u[0]), "=f"(u[1]), "=f"(u[2]), "=f"(u[3]), "=f"(u[4]), "=f"(u[5]), "=f"(u[6]), "=f"(u[7]), "=f"(u[8]), "=f"(u[9]), "=f"(u[10]), "=f"(u[11]), "=f"(u[12]), "=f"(u[13]), "=f"(u[14]), "=f"(u[15]), "=f"(u[16]), "=f"(u[17]), "=f"(u[18]), "=f"(u[19]), "=f"(u[20]), "=f"(u[21]), "=f"(u[22]), "=f"(u[23]), "=f"(u[24]), "=f"(u[25]), "=f"(u[26]), "=f"(u[27]), "=f"(u[28]), "=f"(u[29]), "=f"(u[30]), "=f"(u[31]),
        "=f"(a[0]), "=f"(a[1]), "=f"(a[2]), "=f"(a[3]), "=f"(a[4]), "=f"(a[5]), "=f"(a[6]), "=f"(a[7]), "=f"(a[8]), "=f"(a[9]), "=f"(a[10]), "=f"(a[11]), "=f"(a[12]), "=f"(a[13]), "=f"(a[14]), "=f"(a[15]), "=f"(a[16]), "=f"(a[17]), "=f"(a[18]), "=f"(a[19]), "=f"(a[20]), "=f"(a[21]), "=f"(a[22]), "=f"(a[23]), "=f"(a[24]), "=f"(a[25]), "=f"(a[26]), "=f"(a[27]), "=f"(a[28]), "=f"(a[29]), "=f"(a[30]), "=f"(a[31])
      : "r"(w[0]), "r"(w[1]), "r"(w[2]), "r"(w[3]), "r"(w[4]), "r"(w[5]), "r"(w[6]), "r"(w[7]), "r"(w[8]), "r"(w[9]), "r"(w[10]), "r"(w[11]), "r"(w[12]), "r"(w[13]), "r"(w[14]), "r"(w[15]), "l"(dx)
      : "memory");
}

__device__ __forceinline__ uint32_t smem_u32(const void* p) { return (uint32_t)__cvta_generic_to_shared(p); }
__device__ __forceinline__ float ex2f(float x) { float y; asm("ex2.approx.ftz.f32 %0, %1;" : "=f"(y) : "f"(x)); return y; }
__device__ __forceinline__ float rcpf(float x) { float y; asm("rcp.approx.ftz.f32 %0, %1;" : "=f"(y) : "f"(x)); return y; }
__device__ __forceinline__ uint32_t pack_bf16(float lo, float hi) {
    uint32_t r; asm("cvt.rn.bf16x2.f32 %0, %1, %2;" : "=r"(r) : "f"(hi), "f"(lo)); return r;
}
__device__ __forceinline__ float bf_lo(uint32_t v) { return __uint_as_float(v << 16); }
__device__ __forceinline__ float bf_hi(uint32_t v) { return __uint_as_float(v & 0xFFFF0000u); }
template<int STRIDE>
__device__ __forceinline__ void cp16i(uint32_t dst, const char* base, uint32_t idx) {
    asm volatile("{\n.reg .b64 a;\nmad.wide.u32 a, %2, %3, %1;\ncp.async.cg.shared.global [%0], [a], 16;\n}\n" :: "r"(dst), "l"(base), "r"(idx), "n"(STRIDE) : "memory");
}
__device__ __forceinline__ void cp16e(uint32_t dst, const char* base, uint32_t idx, uint64_t pol) {
    asm volatile("{\n.reg .b64 a;\nmad.wide.u32 a, %2, 32, %1;\ncp.async.cg.shared.global.L2::cache_hint [%0], [a], 16, %3;\n}\n" :: "r"(dst), "l"(base), "r"(idx), "l"(pol) : "memory");
}
template<int STRIDE>
__device__ __forceinline__ void cp16z(uint32_t dst, const char* base, uint32_t idx, int k, int n, uint64_t pol) {
    if (STRIDE == 32)
        asm volatile("{\n.reg .b64 a;\n.reg .pred p;\nsetp.ge.s32 p, %3, %4;\nmad.wide.u32 a, %2, 32, %1;\ncp.async.cg.shared.global.L2::cache_hint [%0], [a], 16, p, %5;\n}\n"
                     :: "r"(dst), "l"(base), "r"(idx), "r"(k), "r"(n), "l"(pol) : "memory");
    else
        asm volatile("{\n.reg .b64 a;\n.reg .pred p;\nsetp.ge.s32 p, %3, %4;\nmad.wide.u32 a, %2, 128, %1;\ncp.async.cg.shared.global [%0], [a], 16, p;\n}\n"
                     :: "r"(dst), "l"(base), "r"(idx), "r"(k), "r"(n) : "memory");
}
template<int HI, bool Z>
__device__ __forceinline__ void cpx(uint32_t hi, uint32_t dst, uint32_t p, uint32_t lo, int k, int n) {
    if (Z) asm volatile("{\n.reg .b32 l;\n.reg .b64 a;\n.reg .pred q;\nsetp.ge.s32 q, %5, %6;\ndp2a.lo.u32.u32 l, %1, %2, %3;\nmov.b64 a, {l, %0};\ncp.async.cg.shared.global [%4], [a], 16, q;\n}\n"
                        :: "r"(hi), "r"(p), "r"(HI ? 0x8000u : 0x80u), "r"(lo), "r"(dst), "r"(k), "r"(n) : "memory");
    else asm volatile("{\n.reg .b32 l;\n.reg .b64 a;\ndp2a.lo.u32.u32 l, %1, %2, %3;\nmov.b64 a, {l, %0};\ncp.async.cg.shared.global [%4], [a], 16;\n}\n"
                      :: "r"(hi), "r"(p), "r"(HI ? 0x8000u : 0x80u), "r"(lo), "r"(dst) : "memory");
}
template<bool Z>
__device__ __forceinline__ void cpe(uint32_t hi, uint32_t dst, uint32_t idx, uint32_t lo, int k, int n, uint64_t pol) {
    if (Z) asm volatile("{\n.reg .b32 l;\n.reg .b64 a;\n.reg .pred q;\nsetp.ge.s32 q, %5, %6;\nmad.lo.u32 l, %1, 32, %2;\nmov.b64 a, {l, %0};\ncp.async.cg.shared.global.L2::cache_hint [%3], [a], 16, q, %4;\n}\n"
                        :: "r"(hi), "r"(idx), "r"(lo), "r"(dst), "l"(pol), "r"(k), "r"(n) : "memory");
    else asm volatile("{\n.reg .b32 l;\n.reg .b64 a;\nmad.lo.u32 l, %1, 32, %2;\nmov.b64 a, {l, %0};\ncp.async.cg.shared.global.L2::cache_hint [%3], [a], 16, %4;\n}\n"
                      :: "r"(hi), "r"(idx), "r"(lo), "r"(dst), "l"(pol) : "memory");
}
template<int N> __device__ __forceinline__ void cp_wait() { asm volatile("cp.async.wait_group %0;" :: "n"(N) : "memory"); }
__device__ __forceinline__ void mbar_init(uint32_t bar, int cnt) { asm volatile("mbarrier.init.shared.b64 [%0], %1;" :: "r"(bar), "r"(cnt) : "memory"); }
__device__ __forceinline__ void mbar_arrive(uint32_t bar) { asm volatile("mbarrier.arrive.shared.b64 _, [%0];" :: "r"(bar) : "memory"); }
__device__ __forceinline__ void mbar_expect(uint32_t bar, uint32_t bytes) { asm volatile("mbarrier.arrive.expect_tx.shared.b64 _, [%0], %1;" :: "r"(bar), "r"(bytes) : "memory"); }
__device__ __forceinline__ void mbar_cp_arrive(uint32_t bar) { asm volatile("cp.async.mbarrier.arrive.noinc.shared.b64 [%0];" :: "r"(bar) : "memory"); }
__device__ __forceinline__ void mbar_wait(uint32_t bar, uint32_t parity) {
    asm volatile("{\n.reg .pred p;\n.reg .u32 n;\nmbarrier.try_wait.parity.shared.b64 p, [%0], %1;\n@p bra DONE_%=;\nmov.u32 n, 0;\n"
                 "WAIT_%=:\nmbarrier.try_wait.parity.shared.b64 p, [%0], %1, 0x100000;\n@p bra DONE_%=;\n"
                 "add.u32 n, n, 1;\nsetp.lt.u32 p, n, 0x400000;\n@p bra WAIT_%=;\ntrap;\nDONE_%=:\n}\n"
                 :: "r"(bar), "r"(parity) : "memory");
}
__device__ __forceinline__ void mbar_wait_c(uint32_t bar, uint32_t parity) {
    asm volatile("{\n.reg .pred p;\nWAIT_%=:\nmbarrier.try_wait.parity.shared.b64 p, [%0], %1;\n@p bra DONE_%=;\nbra WAIT_%=;\nDONE_%=:\n}\n"
                 :: "r"(bar), "r"(parity) : "memory");
}
__device__ __forceinline__ void mbar_wait_h(uint32_t bar, uint32_t parity) {
    asm volatile("{\n.reg .pred p;\nWAIT_%=:\nmbarrier.try_wait.parity.shared.b64 p, [%0], %1, 0x100000;\n@p bra DONE_%=;\nbra WAIT_%=;\nDONE_%=:\n}\n"
                 :: "r"(bar), "r"(parity) : "memory");
}
__device__ __forceinline__ uint32_t lds32(uint32_t a) { uint32_t v; asm volatile("ld.shared.u32 %0, [%1];" : "=r"(v) : "r"(a) : "memory"); return v; }
__device__ __forceinline__ void sts32(uint32_t a, uint32_t v) { asm volatile("st.shared.u32 [%0], %1;" :: "r"(a), "r"(v) : "memory"); }
__device__ __forceinline__ uint2 lds64(uint32_t a) { uint2 v; asm volatile("ld.shared.v2.u32 {%0,%1}, [%2];" : "=r"(v.x), "=r"(v.y) : "r"(a) : "memory"); return v; }
__device__ __forceinline__ uint4 lds128(uint32_t a) { uint4 v; asm volatile("ld.shared.v4.u32 {%0,%1,%2,%3}, [%4];" : "=r"(v.x), "=r"(v.y), "=r"(v.z), "=r"(v.w) : "r"(a) : "memory"); return v; }
__device__ __forceinline__ void sts128(uint32_t a, uint4 v) { asm volatile("st.shared.v4.u32 [%0], {%1,%2,%3,%4};" :: "r"(a), "r"(v.x), "r"(v.y), "r"(v.z), "r"(v.w) : "memory"); }
__device__ __forceinline__ void ldsm4t(uint32_t* v, uint32_t a) {
    asm volatile("ldmatrix.sync.aligned.m8n8.x4.trans.shared.b16 {%0,%1,%2,%3}, [%4];" : "=r"(v[0]), "=r"(v[1]), "=r"(v[2]), "=r"(v[3]) : "r"(a) : "memory");
}
__device__ __forceinline__ void stsm4t(uint32_t a, const uint32_t* v) {
    asm volatile("stmatrix.sync.aligned.m8n8.x4.trans.shared.b16 [%0], {%1,%2,%3,%4};" :: "r"(a), "r"(v[0]), "r"(v[1]), "r"(v[2]), "r"(v[3]) : "memory");
}
__device__ __forceinline__ int atoms_inc(uint32_t a) { int v; asm volatile("atom.shared.add.u32 %0, [%1], 1;" : "=r"(v) : "r"(a) : "memory"); return v; }
__device__ __forceinline__ bool elect_one() {
    uint32_t el;
    asm volatile("{\n.reg .pred p;\nelect.sync _|p, 0xffffffff;\nselp.u32 %0, 1, 0, p;\n}" : "=r"(el));
    return el != 0;
}
__device__ __forceinline__ float tanhf_a(float x) { float y; asm("tanh.approx.f32 %0, %1;" : "=f"(y) : "f"(x)); return y; }
__device__ __forceinline__ const char* as_pair(const void* p, uint32_t scratch) {
    const char* r;
    asm volatile("st.shared.u64 [%1], %2;\nld.volatile.shared.u64 %0, [%1];" : "=l"(r) : "r"(scratch), "l"(p) : "memory");
    return r;
}
__device__ __forceinline__ void ld_unit(uint4& v, const char* p, bool ok) {
    asm volatile("{\n.reg .pred q;\nsetp.ne.u32 q, %5, 0;\n@q ld.relaxed.gpu.global.v4.u32 {%0,%1,%2,%3}, [%4];\n}"
                 : "+r"(v.x), "+r"(v.y), "+r"(v.z), "+r"(v.w) : "l"(p), "r"((uint32_t)ok) : "memory");
}
__device__ __forceinline__ void ld_unit(uint2& v, const char* p, bool ok) {
    asm volatile("{\n.reg .pred q;\nsetp.ne.u32 q, %3, 0;\n@q ld.relaxed.gpu.global.v2.u32 {%0,%1}, [%2];\n}"
                 : "+r"(v.x), "+r"(v.y) : "l"(p), "r"((uint32_t)ok) : "memory");
}
__device__ __forceinline__ void bulk_ld(uint32_t dst, const void* src, int bytes, uint32_t bar) {
    mbar_expect(bar, bytes);
    if (bytes > 0) asm volatile("cp.async.bulk.shared::cluster.global.mbarrier::complete_tx::bytes [%0], [%1], %2, [%3];" :: "r"(dst), "l"(src), "r"(bytes), "r"(bar) : "memory");
}
__device__ __forceinline__ void bulk_st(void* dst, uint32_t src, int bytes) {
    asm volatile("cp.async.bulk.global.shared::cta.bulk_group [%0], [%1], %2;" :: "l"(dst), "r"(src), "r"(bytes) : "memory");
}

__device__ __forceinline__ void finish(uint4& a, const uint4& xu, const uint4& xv) {
    asm("{\n.reg .b32 z;\nfma.rn.relu.bf16x2 z, %0, %3, %1;\nadd.rn.bf16x2 %0, z, %2;\n}" : "+r"(a.x) : "r"(xu.x), "r"(xv.x), "r"(0x3F803F80u));
    asm("{\n.reg .b32 z;\nfma.rn.relu.bf16x2 z, %0, %3, %1;\nadd.rn.bf16x2 %0, z, %2;\n}" : "+r"(a.y) : "r"(xu.y), "r"(xv.y), "r"(0x3F803F80u));
    asm("{\n.reg .b32 z;\nfma.rn.relu.bf16x2 z, %0, %3, %1;\nadd.rn.bf16x2 %0, z, %2;\n}" : "+r"(a.z) : "r"(xu.z), "r"(xv.z), "r"(0x3F803F80u));
    asm("{\n.reg .b32 z;\nfma.rn.relu.bf16x2 z, %0, %3, %1;\nadd.rn.bf16x2 %0, z, %2;\n}" : "+r"(a.w) : "r"(xu.w), "r"(xv.w), "r"(0x3F803F80u));
}

__device__ __forceinline__ void node_rows(uint32_t p, const float* a) {
    #pragma unroll
    for (int i = 0; i < 4; i++) {
        const float* u = a + 8 * i;
        const uint32_t v[4] = {pack_bf16(u[0], u[1]), pack_bf16(u[2], u[3]), pack_bf16(u[4], u[5]), pack_bf16(u[6], u[7])};
        stsm4t(p + i * 2048, v);
    }
}

constexpr int LOCK_OFF = 64732;
constexpr float EPS2 = 2e-6f;
constexpr float TAU = 2.5e-5f;

template<bool HALF>
__device__ __forceinline__ void make_wfrag(uint32_t* f, const uint32_t* v) {
    const uint32_t v0 = v[0], v1 = v[1], v2 = v[2], v3 = v[3];
    f[0] = __byte_perm(v0, v1, 0x5410); f[1] = __byte_perm(v0, v1, 0x7632);
    f[2] = __byte_perm(v2, v3, 0x5410); f[3] = __byte_perm(v2, v3, 0x7632);
    if (HALF) {
        #pragma unroll
        for (int i = 0; i < 4; i++) asm("mul.rn.bf16x2 %0, %0, %1;" : "+r"(f[i]) : "r"(0x3F003F00u));
    }
}

template<int NP>
__device__ __forceinline__ void epi_fast(const float* g, const float* h, float m1, float m2,
                                         float& n0, float& d0, float& n1, float& d1, float& dmin)
{
    constexpr int JC = NP >= 6 ? NP - 3 : NP >= 4 ? NP - 2 : NP - 1;
    constexpr int JT = NP < 3 ? -1 : JC < NP - 1 ? JC : NP - 2;
    #pragma unroll
    for (int j = 0; j < NP; j++) {
        float t0 = tanhf_a(g[4*j+0]), t1 = tanhf_a(g[4*j+1]), t2 = tanhf_a(g[4*j+2]), t3 = tanhf_a(g[4*j+3]);
        auto add_d = [&]() {
            if (j == 0) { d0 = t0 + (2.f * (JT + 1) + EPS2); d1 = t2 + (2.f * (JT + 1) + EPS2); } else { d0 += t0; d1 += t2; }
            d0 += t1; d1 += t3;
        };
        if (j <= JT) add_d();
        if (j == NP - 1) { t0 = fmaf(t0, m1, m1); t1 = fmaf(t1, m2, m2); t2 = fmaf(t2, m1, m1); t3 = fmaf(t3, m2, m2); }
        else { t0 += 1.f; t1 += 1.f; t2 += 1.f; t3 += 1.f; }
        if (j > JT) add_d();
        if (j == 0) { n0 = t0 * h[0]; n1 = t2 * h[2]; } else { n0 = fmaf(t0, h[4*j], n0); n1 = fmaf(t2, h[4*j+2], n1); }
        n0 = fmaf(t1, h[4*j+1], n0); n1 = fmaf(t3, h[4*j+3], n1);
        if (j == JC) dmin = fminf(d0, d1);
    }
}

__device__ __noinline__ float4 epi_exact(const float4* gh, int np, int dv)
{
    float n0 = 0.f, d0 = EPS2, n1 = 0.f, d1 = EPS2;
    #pragma unroll 2
    for (int j = 0; j < np; j++) {
        const float4 g = gh[j], h = gh[NPMAX + j];
        const float ma = (2 * j < dv) ? 2.f : 0.f, mb = (2 * j + 1 < dv) ? 2.f : 0.f;
        const float e0 = ma * rcpf(1.f + ex2f(-2.f * LOG2E * g.x)), e1 = mb * rcpf(1.f + ex2f(-2.f * LOG2E * g.y));
        const float e2 = ma * rcpf(1.f + ex2f(-2.f * LOG2E * g.z)), e3 = mb * rcpf(1.f + ex2f(-2.f * LOG2E * g.w));
        d0 += e0 + e1; n0 = fmaf(e0, h.x, fmaf(e1, h.y, n0));
        d1 += e2 + e3; n1 = fmaf(e2, h.z, fmaf(e3, h.w, n1));
    }
    return make_float4(n0, d0, n1, d1);
}
__device__ __noinline__ float4 epi_single(uint32_t spare, int dv)
{
    __syncwarp();
    uint32_t lane; asm volatile("mov.u32 %0, %%laneid;" : "=r"(lane));
    const int j = lane & 15;
    const uint32_t p = spare + min(j, (dv - 1) >> 1) * 16 + (lane >> 4) * 8;
    const uint2 g = lds64(p), h = lds64(p + 16 * NPMAX);
    const float e0 = (2 * j < dv ? 2.f : 0.f) * rcpf(1.f + ex2f(-2.f * LOG2E * __uint_as_float(g.x)));
    const float e1 = (2 * j + 1 < dv ? 2.f : 0.f) * rcpf(1.f + ex2f(-2.f * LOG2E * __uint_as_float(g.y)));
    float d = e0 + e1, n = fmaf(e0, __uint_as_float(h.x), e1 * __uint_as_float(h.y));
    #pragma unroll
    for (int o = 8; o; o >>= 1) { n += __shfl_xor_sync(~0u, n, o); d += __shfl_xor_sync(~0u, d, o); }
    d += EPS2;
    sts32(spare + LOCK_OFF, 0);
    return make_float4(__shfl_sync(~0u, n, 0), __shfl_sync(~0u, d, 0), __shfl_sync(~0u, n, 16), __shfl_sync(~0u, d, 16));
}
template<int NP>
__device__ __forceinline__ void epi_dump(const float* g, const float* h, float4* gh) {
    #pragma unroll
    for (int i = 0; i < NP; i++) {
        gh[i] = make_float4(g[4*i], g[4*i+1], g[4*i+2], g[4*i+3]);
        gh[NPMAX + i] = make_float4(h[4*i], h[4*i+1], h[4*i+2], h[4*i+3]);
    }
}

__device__ __noinline__ void slow_bin(const __nv_bfloat16* x, const __nv_bfloat16* ea, const int* src, const int* dst,
                                      const __nv_bfloat16* wa, const __nv_bfloat16* wb, const __nv_bfloat16* wc,
                                      const __nv_bfloat16* wu, const __nv_bfloat16* wv, __nv_bfloat16* out,
                                      int E, int node0, int nn, int nthr)
{
    const int tid = threadIdx.x, lane = tid & 31;
    for (int i = tid; i < nn * 128; i += nthr) g_slow[(size_t)node0 * 128 + i] = 0.f;
    asm volatile("bar.sync 1, %0;" :: "r"(nthr) : "memory");
    for (int e0 = (tid >> 5) * 32; e0 < E; e0 += nthr) {
        int d = (e0 + lane < E) ? dst[e0 + lane] - node0 : -1;
        unsigned m = __ballot_sync(~0u, d >= 0 && d < nn);
        while (m) {
            int l = __ffs(m) - 1; m &= m - 1;
            int e = e0 + l, n = node0 + __shfl_sync(~0u, d, l), s = src[e];
            float g0 = 0, g1 = 0, h0 = 0, h1 = 0;
            for (int k = 0; k < 64; k++) {
                float xs = __bfloat162float(x[(size_t)s * 64 + k]), xd = __bfloat162float(x[(size_t)n * 64 + k]);
                uint32_t b2 = *(const uint32_t*)(wb + k * 64 + 2 * lane), v2 = *(const uint32_t*)(wv + k * 64 + 2 * lane);
                uint32_t a2 = *(const uint32_t*)(wa + k * 64 + 2 * lane);
                g0 = fmaf(xs, bf_lo(b2), fmaf(xd, bf_lo(a2), g0)); g1 = fmaf(xs, bf_hi(b2), fmaf(xd, bf_hi(a2), g1));
                h0 = fmaf(xs, bf_lo(v2), h0); h1 = fmaf(xs, bf_hi(v2), h1);
            }
            for (int k = 0; k < 16; k++) {
                float ev = __bfloat162float(ea[(size_t)e * 16 + k]);
                uint32_t c2 = *(const uint32_t*)(wc + k * 64 + 2 * lane);
                g0 = fmaf(ev, bf_lo(c2), g0); g1 = fmaf(ev, bf_hi(c2), g1);
            }
            float s0 = rcpf(1.f + ex2f(-LOG2E * g0)), s1 = rcpf(1.f + ex2f(-LOG2E * g1));
            float* acc = g_slow + (size_t)n * 128 + 4 * lane;
            atomicAdd(acc + 0, s0 * h0); atomicAdd(acc + 1, s0);
            atomicAdd(acc + 2, s1 * h1); atomicAdd(acc + 3, s1);
        }
    }
    __threadfence();
    asm volatile("bar.sync 1, %0;" :: "r"(nthr) : "memory");
    for (int i = tid; i < nn * 32; i += nthr) {
        int n = node0 + (i >> 5), cp = i & 31;
        float4 a = __ldcg((const float4*)(g_slow + (size_t)n * 128 + 4 * cp));
        float u0 = 0, u1 = 0;
        for (int k = 0; k < 64; k++) {
            float xd = __bfloat162float(x[(size_t)n * 64 + k]);
            uint32_t w2 = *(const uint32_t*)(wu + k * 64 + 2 * cp);
            u0 = fmaf(xd, bf_lo(w2), u0); u1 = fmaf(xd, bf_hi(w2), u1);
        }
        uint32_t xv = *(const uint32_t*)(x + (size_t)n * 64 + 2 * cp);
        float z0 = u0 + a.x / (a.y + 1e-6f), z1 = u1 + a.z / (a.w + 1e-6f);
        *(uint32_t*)(out + (size_t)n * 64 + 2 * cp) = pack_bf16(bf_lo(xv) + fmaxf(z0, 0.f), bf_hi(xv) + fmaxf(z1, 0.f));
    }
}

__global__ void __launch_bounds__(256) slow_kernel(const __nv_bfloat16* x, const __nv_bfloat16* ea, const int* src, const int* dst,
        const __nv_bfloat16* wa, const __nv_bfloat16* wb, const __nv_bfloat16* wc, const __nv_bfloat16* wu, const __nv_bfloat16* wv,
        __nv_bfloat16* out, int N, int E, int npb)
{
    int node0 = blockIdx.x * npb;
    slow_bin(x, ea, src, dst, wa, wb, wc, wu, wv, out, E, node0, max(0, min(npb, N - node0)), 256);
}

constexpr int XS_BYTES = NPMAX * 1024;
constexpr int ES_BYTES = NPMAX * 256;
constexpr int SM_XS = 0;
constexpr int SM_XU = SM_XS + 3 * NSTAGE * XS_BYTES;
constexpr int SM_TAB = SM_XU + NPB_MAX * 128;
constexpr int SM_ES = SM_TAB + (NPB_MAX + 2) * 128;
constexpr int SM_WC = SM_ES + 3 * NSTAGE * ES_BYTES;
constexpr int SM_OH = SM_WC + 2048;
constexpr int SM_EID = SM_OH + 256;
constexpr int SM_SRC = SM_EID + (SLOT_CAP + 32) * 4;
constexpr int SM_TINFO = SM_SRC + (SLOT_CAP + 32) * 2;
constexpr int SM_MISC = SM_TINFO + TILE_CAP * 32;
constexpr int SM_CLAIM = SM_TAB + (NPB_MAX + 1) * 128;
constexpr int SM_BARS = SM_MISC + 32 * 4;
constexpr int SM_ABAR = SM_BARS + 6 * 48;
constexpr int SM_XBAR = SM_ABAR + 10 * 8;
constexpr int SM_SBAR = SM_XBAR + 4 * 8;
constexpr int SM_GBAR = SM_SBAR + 3 * 8;
constexpr int SM_WL = SM_GBAR + 97 * 8;
constexpr int WST = 9;
constexpr int SMEM_BYTES = SM_WL + (96 + WST) * 8;
constexpr int SM_P2 = 0, SM_P1 = 6 * 384 * 16;
constexpr int SM_DEG = SM_P1 + P1B;
constexpr int SM_CNT = SM_DEG + 512 * 4;
constexpr int SM_CLS = SM_CNT + 512 * 4;
constexpr int SM_HIST = SM_CLS + NCLS * 4;
constexpr int SM_XLIST = SM_HIST + 136 * 4;
constexpr int SM_SORT = SM_XLIST + XCAP * 8;
constexpr int SM_BASE = SM_SORT + NPB_MAX * 4;
constexpr int SM_PAIR = SM_BASE + (NPB_MAX + 4) * 2;
constexpr int SM_IDX = SM_EID;
constexpr int SM_WR = SM_TAB;
static_assert(TILE_CAP <= 128 && TR >= 2 && SM_ES % 256 == 0 && NSTAGE == 2 && SM_BARS % 16 == 0 && SM_TINFO % 16 == 0 && SM_EID % 128 == 0 && SM_TAB % 1024 == 0 && SM_XU % 1024 == 0 && SM_TINFO % 8 == 0 && SM_OH % 16 == 0 && SM_SORT % 16 == 0 && SM_XLIST % 16 == 0 && SM_PAIR % 8 == 0, "align");
static_assert(P1B % 16 == 0 && P2B <= SM_P1 && NB_MAX <= 6 * 24 && SM_PAIR + 128 * 8 <= SM_XU && CH_MAX * 4 <= SM_SRC - SM_EID && SM_DEG >= 3 << 14, "alias");
static_assert(SMEM_BYTES <= 232448 && SM_TAB + (NPB_MAX - 3) * 128 + LOCK_OFF == SM_MISC + 28 && 32 * NPMAX <= 384, "smem");
constexpr uint32_t C_BRK = 16  , C_CONT = 32, C_MORE = 64;
constexpr uint32_t ONE_F = 0x3F800000u;
constexpr int NONE = NPB_MAX;

__device__ __forceinline__ uint2 tile_info(uint32_t e) {
    const uint32_t y = (uint32_t)((int)e >> 16) & (ONE_F | 0x1FFFu);
    return make_uint2(e, (e & 0x1F000000u) ? y | 0x80000000u : y);
}
__device__ __forceinline__ bool unpad(uint32_t w1, int np, float ga, float gb, float& d0, float& d1, int& dv) {
    const int pad = (int)w1 < 0 ? (w1 >> 8) & 31 : 0;
    dv = 2 * np - 2 - pad + ((int)w1 > 127) + ((int)w1 >= (int)ONE_F);
    float t0 = TAU * 2 * np, t1 = t0;
    if (pad) {
        t0 = fmaxf(t0, d0 * (1.f / 1024)); t1 = fmaxf(t1, d1 * (1.f / 1024));
        asm volatile("tanh.approx.f32 %0, %0;\ntanh.approx.f32 %1, %1;" : "+f"(ga), "+f"(gb));
        d0 -= pad * (1.f + ga); d1 -= pad * (1.f + gb);
    }
    if (dv == 0) { d0 = d1 = EPS2; t0 = t1 = 0.f; }
    return d0 < t0 || d1 < t1;
}
__device__ __forceinline__ uint64_t desc_sw128(uint32_t a) {
    return (uint64_t)((a & 0x3FFFF) >> 4) | ((uint64_t)1 << 16) | ((uint64_t)64 << 32) | ((uint64_t)1 << 62);
}

__device__ __forceinline__ uint32_t sel(bool c, uint32_t a, uint32_t b) {
    uint32_t r; asm("{\n.reg .pred p;\nsetp.ne.u32 p, %1, 0;\nselp.b32 %0, %2, %3, p;\n}" : "=r"(r) : "r"((uint32_t)c), "r"(a), "r"(b)); return r;
}
__device__ __forceinline__ void tile_entry(uint8_t* smem, uint32_t sv, int dg, int mn, int t, int tl, int np, int done, uint32_t flags, int next) {
    const uint32_t nd = sv & 0xFFFF, w0 = nd * 128 + ((nd & 7) << 4);
    const int dv = min(max(dg - done, 0), 2 * np), r = 2 * np - dv;
    const bool gen = mn - done < 2 * np - 2;
    const uint32_t w1 = (uint32_t)np | flags | sel(gen || flags, C_BRK, 0u) | sel(r < 2, 0x8000u >> (8 * r), (r - 2) << 8);
    *(uint2*)(smem + SM_TINFO + tl * 32 + t * 8) = make_uint2(sel(dv, (sv >> 16) + done, 0) | (sel(gen, 13 + (np > 5) + (np > 8), np) << 16) | (next << 20) | ((uint32_t)dv << 27), w0 | sel(np, w1 << 16, 0u));
}
__device__ __noinline__ void tiles_many(uint8_t* smem, uint32_t sv, int dg, int mn, int id, int left, unsigned sm) {
    int* misc = (int*)(smem + SM_MISC);
    int nt = (left + NPMAX - 1) / NPMAX, tl = id >> 2, done = 0, nx = 0;
    if ((id & 3) == 0) { nx = atomicAdd(&misc[5], nt - 1); if (nx + nt - 1 > TILE_CAP) misc[1] = 1; }
    nx = __shfl_sync(sm, nx, id & 28);
    if (nx + nt - 1 > TILE_CAP) left = 0;
    uint32_t cont = 0;
    #pragma unroll 1
    while (left > 0) {
        const int np = (left + nt - 1) / nt;
        left -= np; nt--;
        tile_entry(smem, sv, dg, mn, id & 3, tl, np, done, cont | (left > 0 ? C_MORE : 0u), left > 0 ? nx : 0);
        tl = nx++; cont = C_CONT; done += 2 * np;
    }
}
__device__ __forceinline__ void tables(uint8_t* smem, uint32_t sbase, int id0, int ngroups) {
    const int t = id0 & 3;
    uint4 s4[3];
    uint32_t me[3], sv[3];
    #pragma unroll
    for (int k = 0; k < 3; k++) { s4[k] = lds128(sbase + SM_SORT + (id0 & ~3) * 4 + k * 512); me[k] = lds32(sbase + SM_SORT + id0 * 4 + k * 512); }
    #pragma unroll
    for (int k = 0; k < 3; k++) asm volatile("ld.shared.u16 %0, [%1];" : "=r"(sv[k]) : "r"(sbase + SM_BASE + (me[k] & 0xFFFF) * 2) : "memory");
    int mn[3], left[3];
    uint32_t more = 0;
    #pragma unroll
    for (int k = 0; k < 3; k++) {
        const int g = (id0 >> 2) + 32 * k, nx = ngroups + 4 + g;
        sv[k] = sv[k] << 16 | (me[k] & 0xFFFF);
        mn[k] = min(min(s4[k].x, s4[k].y), min(s4[k].z, s4[k].w)) >> 16;
        left[k] = ((max(max(s4[k].x, s4[k].y), max(s4[k].z, s4[k].w)) >> 16) + 1) >> 1;
        const bool two = left[k] > NPMAX;
        more |= two << k;
        tile_entry(smem, sv[k], me[k] >> 16, mn[k], t, sel(g >= ngroups + 4, ngroups, g), sel(two, min((left[k] + 1) >> 1, NPMAX), sel(left[k], max(left[k], NPMIN), 0)), 0, sel(two, C_MORE, 0u), sel(two, nx & 127, 0));
    }
    #pragma unroll 1
    for (int id = id0; __any_sync(~0u, more); id += 128) {
        const int nx = ngroups + 4 + (id >> 2);
        const bool odd = left[0] > 2 * NPMAX || ((more & 1) && nx >= TILE_CAP - TILE_X);
        const unsigned sm = __ballot_sync(~0u, odd);
        if (__builtin_expect(odd, 0)) tiles_many(smem, sv[0], me[0] >> 16, mn[0], id, left[0], sm);
        else if (more & 1) tile_entry(smem, sv[0], me[0] >> 16, mn[0], t, nx, left[0] >> 1, (left[0] + 1) & ~1, C_CONT, 0);
        __syncwarp();
        more >>= 1;
        sv[0] = sv[1]; sv[1] = sv[2]; me[0] = me[1]; me[1] = me[2]; mn[0] = mn[1]; mn[1] = mn[2]; left[0] = left[1]; left[1] = left[2];
    }
}
__device__ __forceinline__ uint32_t to_list(uint32_t sbase, uint32_t e, uint32_t bin) {
    uint32_t j; asm volatile("atom.shared.inc.u32 %0, [%1], 0x7fffffff;" : "=r"(j) : "r"(sbase + SM_MISC + 8) : "memory");
    j = min(j, 63u);
    sts32(sbase + SM_P1 + j * 4, e | ((j < 63 ? bin : 255u) << 16));
    return j;
}

template<bool LO32>
__global__ void __launch_bounds__(THREADS, 1)
gcn_kernel(const int* __restrict__ dst, unsigned* gbar, char* gs, const int* __restrict__ src, int E, int ch, int N, int npb, uint32_t magic,
           const __nv_bfloat16* __restrict__ x, const __nv_bfloat16* __restrict__ ea,
           const __nv_bfloat16* __restrict__ wa, const __nv_bfloat16* __restrict__ wb, const __nv_bfloat16* __restrict__ wc,
           const __nv_bfloat16* __restrict__ wu, const __nv_bfloat16* __restrict__ wv,
           __nv_bfloat16* out, int4 wrow, const __grid_constant__ CUtensorMap tm2, const __grid_constant__ CUtensorMap tmw,
           const __grid_constant__ CUtensorMap tmc, const __grid_constant__ CUtensorMap tmx)
{
    extern __shared__ __align__(1024) uint8_t smem[];
    int* cls = (int*)(smem + SM_CLS);
    int* misc = (int*)(smem + SM_MISC);
    uint32_t* xlist = (uint32_t*)(smem + SM_XLIST);
    WG0(); WS(0); ZS(0);
    const uint32_t sbase = smem_u32(smem);
    const int tid = threadIdx.x, lane = tid & 31;
    const int b = blockIdx.x, nb = gridDim.x;
    const int cnt = max(0, min(ch, E - b * ch));
    const int node0 = b * npb;
    auto src_ld = [&](int v) { bulk_ld(sbase + SM_XU + v * 8192, src + b * ch + v * 2048, min(max(cnt * 4 - v * 8192, 0), 8192), sbase + SM_SBAR + v * 8); };
    auto dst_ld = [&](int v) { bulk_ld(sbase + SM_IDX + v * 8192, dst + b * ch + v * 2048, min(max(cnt * 4 - v * 8192, 0), 8192), sbase + SM_ABAR + v * 8); };
    auto box_ld = [&](uint32_t dst, const CUtensorMap* tm, int col, int row, uint32_t bar) {
        asm volatile("cp.async.bulk.tensor.2d.shared::cluster.global.mbarrier::complete_tx::bytes [%0], [%1, {%3, %4}], [%2];"
            :: "r"(dst), "l"((uint64_t)tm), "r"(bar), "r"(col), "r"(row) : "memory");
    };
    auto w_ld = [&]() {
        mbar_expect(sbase + SM_ABAR + 24, 272 * 128);
        box_ld(sbase + SM_WR, &tmw, 0, wrow.y, sbase + SM_ABAR + 24); box_ld(sbase + SM_WR + 64 * 128, &tmc, 0, 0, sbase + SM_ABAR + 24);
        box_ld(sbase + SM_WR + 80 * 128, &tmw, 0, wrow.w, sbase + SM_ABAR + 24); box_ld(sbase + SM_WR + 144 * 128, &tmw, 0, wrow.x, sbase + SM_ABAR + 24);
        box_ld(sbase + SM_WR + 208 * 128, &tmw, 0, wrow.z, sbase + SM_ABAR + 24);
    };
    auto x_ld = [&](int k) {
        mbar_expect(sbase + SM_XBAR + k * 8, 16384);
        box_ld(sbase + SM_XU + k * 16384, &tmx, 0, node0 + 128 * k, sbase + SM_XBAR + k * 8);
    };
    uint32_t tag = 0;
    if (tid < 32) asm volatile("ld.relaxed.gpu.global.u32 %0, [%1];" : "=r"(tag) : "l"(gbar));
    if (tid >> 5 == 11) {
        if (elect_one()) {
            mbar_init(sbase + SM_ABAR, 1);
            asm volatile("fence.mbarrier_init.release.cluster;" ::: "memory");
            dst_ld(0);
        }
    }
    if (tid >= 384) {
        if (elect_one()) {
            const int v = (tid >> 5) & 3;
            if (v) mbar_init(sbase + SM_ABAR + v * 8, 1);
            asm volatile("fence.mbarrier_init.release.cluster;" ::: "memory");
            if (v == 1) dst_ld(v);
            if (v == 3) {
                mbar_init(sbase + SM_ABAR + 40, 1); mbar_init(sbase + SM_GBAR + 96 * 8, 32); mbar_init(sbase + SM_ABAR + 72, 384); mbar_init(sbase + SM_XBAR + 24, 512);
            }
            #pragma unroll 1
            for (int j = 0; j < 3; j++) {
                #pragma unroll
                for (int i = 0; i < 8; i++) mbar_init(sbase + SM_GBAR + (v * 24 + j * 8 + i) * 8, 32);
                if (j == 1 && v == 2) dst_ld(v);
            }
            if (tid < 480) {
                #pragma unroll
                for (int i = 0; i < 2; i++) { mbar_init(sbase + SM_BARS + (v * 2 + i) * 48, 64); mbar_init(sbase + SM_BARS + (v * 2 + i) * 48 + 8, 128); }
                mbar_init(sbase + SM_ABAR + 48 + v * 8, 128); mbar_init(sbase + SM_XBAR + v * 8, 1); mbar_init(sbase + SM_SBAR + v * 8, 1);
            }
            asm volatile("fence.mbarrier_init.release.cluster;" ::: "memory");
        }
    }
    if (tid >= 128 && tid < 132) asm volatile("prefetch.tensormap [%0];" :: "l"((uint64_t)(tid == 128 ? &tmw : tid == 129 ? &tmc : tid == 130 ? &tm2 : &tmx)) : "memory");
    const int warp = (int)__reduce_max_sync(~0u, (unsigned)tid >> 5);
    const int wg = warp >> 2, w = warp & 3;
    const int q = lane >> 2, t = lane & 3;
    const int ch0 = 16 * w + 2 * q;
    const int nn = max(0, min(npb, N - node0));
    if (sbase & 1023) __trap();

    sts32(sbase + (tid < NPB_MAX ? SM_DEG : SM_CNT) + tid * 4, tid < NPB_MAX ? 0 : 0xC0000000u);
    if (tid < NCLS + NB_MAX) cls[tid] = tid < NCLS ? 0 : (tid - NCLS) * CE + 64;
    else if (wg == 2) {
        if (w < 2) {
            *(uint32_t*)(smem + SM_OH + (tid & 63) * 4) = t != (q >> 1) ? 0u : (w == 0 ? 0x00003F00u : 0x3F000000u);
        } else if (w == 2) *(uint32_t*)(smem + SM_TAB + NPB_MAX * 128 + lane * 4) = 0u;
        else misc[lane] = lane == 5 ? TILE_CAP - TILE_X : lane == 7 && npb > NPB_MAX - 3;
    }
    if (warp == 13 && lane < WST * 2) sts32(sbase + SM_WL + 768 + lane * 4, NONE * 0x10001u);
    if (warp == 14) sts32(sbase + SM_TINFO + 96 * 32 + lane * 4, 0);
    if (warp == 15) sts32(sbase + SM_CLAIM + lane * 4, lane == 0 ? 3 : 0x40000000);
    if (wg < 3) {
        #pragma unroll 1
        for (int i = tid; i < P2B / 32; i += 384) { sts128(sbase + SM_P2 + i * 16, make_uint4(0, 0, 0, 0)); sts128(sbase + SM_P2 + P2B / 2 + i * 16, make_uint4(0, 0, 0, 0)); }
    }
    if (tid == 0) sts32(sbase + SM_PAIR, tag);
    if (wg < 3) { asm volatile("bar.sync 1, 384;" ::: "memory"); tag = lds32(sbase + SM_PAIR); }
    tag = (tag & 1) | 2;
    if (wg < 3) {
        const uint32_t d0 = ((NPB_MAX + ((2 * lane) & 15) + 16 * (b & 1)) * 4 | (tag << 14)) * 0x10001u, d1 = d0 + 0x40004u;
        #pragma unroll
        for (int i = 0; i < 3; i++) if (i < 2 || tid + 768 < P1B / 16) sts128(sbase + SM_P1 + (tid + 384 * i) * 16, make_uint4(d0, d0, d1, d1));
    }
    if (warp == 15 && elect_one()) w_ld();
    WS(1); ZS(1);
    __syncthreads();
    if (wg == 3) tag = (lds32(sbase + SM_PAIR) & 1) | 2;

    uint32_t ent[EPT];
    #pragma unroll
    for (int v = 0; v < EPT / 4; v++) {
        mbar_wait_c(sbase + SM_ABAR + v * 8, 0);
        if (v == 0) ZS(2);
        if (((v == 0 && (warp == 13 || warp == 14)) || (v == 1 && warp == 15)) && elect_one()) src_ld(warp - 13);
        const uint32_t off = v * (THREADS * 4) + tid * 4;
        if (off < (uint32_t)cnt) {
            const uint32_t ia = sbase + SM_IDX + off * 4;
            const uint4 u = lds128(ia);
            uint32_t dv[4] = {u.x, u.y, u.z, u.w}, ps[4], ck[4];
            uint32_t* en = ent + 4 * v;
            #pragma unroll
            for (int k = 0; k < 4; k++) {
                dv[k] = min(dv[k], (uint32_t)(nb * npb - 1));
                ps[k] = __umulhi(dv[k], magic); en[k] = atoms_inc(sbase + SM_HIST + ps[k] * 4);
            }
            #pragma unroll
            for (int k = 0; k < 4; k++) {
                dv[k] = (dv[k] - ps[k] * npb) * 4 + (tag << 14);
                ck[k] = en[k] - ps[k] * CE;
                en[k] ^= ps[k] * 4 & 60;
            }
            if (__builtin_expect(max(max(ck[0], ck[1]), max(ck[2], ck[3])) >= 64 + CE, 0)) {
                #pragma unroll
                for (int k = 0; k < 4; k++) if (ck[k] >= 64 + CE) en[k] = to_list(sbase, dv[k], ps[k]);
            }
            #pragma unroll
            for (int k = 0; k < 4; k++)
                asm volatile("{\n.reg .pred p;\nsetp.ge.u32 p, %2, 64;\n@p st.shared.u16 [%0], %1;\n}" :: "r"(sbase + SM_P1 + 128 + en[k] * 2), "r"(dv[k]), "r"(en[k]) : "memory");
        }
    }
    WS(5); ZS(3);
    __syncthreads();
    auto send = [&](int o, uint32_t a, int bytes) {
        if (warp == 14 && elect_one()) {
            asm volatile("fence.proxy.async.shared::cta;" ::: "memory");
            bulk_st(gs + b * (P1B + P2B) + o, a, bytes);
            asm volatile("cp.async.bulk.commit_group;" ::: "memory");
        }
    };
    send(0, sbase + SM_P1, 256 + nb * (CE * 2));
    #pragma unroll
    for (int v = 0; v < EPT / 4; v++) {
        mbar_wait_c(sbase + SM_SBAR + v * 8, 0);
        const uint32_t off = v * (THREADS * 4) + tid * 4;
        if (off < (uint32_t)cnt) {
            const uint4 sv = lds128(sbase + SM_XU + off * 4);
            const uint32_t ss[4] = {sv.x, sv.y, sv.z, sv.w};
            #pragma unroll
            for (int k = 0; k < 4; k++) sts32(sbase + SM_P2 + ent[4*v+k] * 4, (ss[k] & 0xFFFF) | (((off + k) << 19) + (tag << 16)));
        }
    }
    WS(7); ZS(4);
    __syncthreads();
    send(P1B, sbase + SM_P2, 256 + nb * (CE * 4));
    WSL(8);

    const int ngroups = (nn + 3) >> 2;
    if (wg == 3) {
        asm volatile("setmaxnreg.dec.sync.aligned.u32 56;");
        WS(2);
        const char* const ga = as_pair((const char*)x + (w < 3 ? 0 : (size_t)node0 * 128) + (lane & 7) * 16, sbase + SM_PAIR + (tid & 127) * 8);
        const char* const gb = as_pair(w < 3 ? (const char*)ea + (lane & 1) * 16 : (const char*)out + (size_t)node0 * 128 + (lane & 7) * 16, sbase + SM_PAIR + (tid & 127) * 8);
        WS(3);
        const uint32_t dm = ((NPB_MAX + lane) * 4 | (tag << 14)) * 0x10001u;
        const uint32_t db = sbase + SM_DEG - (tag << 14);
        const char* gl = gs + ((tid & 127) >> 2) * (P1B + P2B) + t * 16;
        uint4 rl[5];
        #pragma unroll
        for (int i = 0; i < 5; i++) rl[i].w = ((tid & 127) >> 2) + 32 * i < nb ? 0 : dm;
        auto p2_ld = [&]() {
            mbar_expect(sbase + SM_ABAR + 40, nb * (CE * 4));
            box_ld(sbase + SM_P2, &tm2, P1B / 4 + 64 + b * CE, 0, sbase + SM_ABAR + 40);
        };
        asm volatile("cp.async.bulk.wait_group.read 0;" ::: "memory");
        asm volatile("bar.sync 6, 128;" ::: "memory");
        WSL(12);
        uint32_t spins = 0;
        #pragma unroll 1
        for (int r = 0;; r++) {
            #pragma unroll
            for (int i = 0; i < 5; i++) rl[i].x = rl[i].y = rl[i].z = dm;
            while (true) {
                #pragma unroll
                for (int i = 0; i < 5; i++) ld_unit(rl[i], gl + i * (32 * (P1B + P2B)), (rl[i].w ^ dm) & 0xC000);
                if (spins == 0) asm volatile("bar.sync 5, 512;" ::: "memory");
                if (++spins > (1u << 22)) __trap();
                if (!__any_sync(~0u, ((rl[0].w ^ dm) | (rl[1].w ^ dm) | (rl[2].w ^ dm) | (rl[3].w ^ dm) | (rl[4].w ^ dm)) & 0xC000)) break;
            }
            WS(4);
            uint32_t own = 0;
            #pragma unroll
            for (int i = 0; i < 5; i++) {
                const uint32_t bb = b << 16;
                own |= (min(min(rl[i].x ^ bb, rl[i].y ^ bb), min(rl[i].z ^ bb, rl[i].w ^ bb)) < 0x10000u) << i;
            }
            while (own != 0) {
                uint32_t n; asm volatile("atom.shared.inc.u32 %0, [%1], 0x7fffffff;" : "=r"(n) : "r"(sbase + SM_MISC) : "memory");
                uint4 u = rl[4];
                #pragma unroll
                for (int i = 3; i >= 0; i--) { const bool c = (own >> i) & 1; u.x = sel(c, rl[i].x, u.x); u.y = sel(c, rl[i].y, u.y); u.z = sel(c, rl[i].z, u.z); u.w = sel(c, rl[i].w, u.w); }
                const uint32_t s = (((tid & 127) >> 2) + 32 * (__ffs(own) - 1) << 16) + (4 * r + t << 26);
                own &= own - 1;
                const uint32_t e[4] = {min(u.x ^ (b << 16), dm & 0xFFFF), min(u.y ^ (b << 16), dm & 0xFFFF), min(u.z ^ (b << 16), dm & 0xFFFF), min(u.w ^ (b << 16), dm & 0xFFFF)};
                #pragma unroll
                for (int k = 0; k < 4; k++) asm volatile("red.shared.add.u32 [%0], 1;" :: "r"(db + e[k]) : "memory");
                sts128(sbase + SM_XLIST + min(n, XCAP / 4 - 1) * 16, make_uint4(e[0] + s, e[1] + s + (1 << 24), e[2] + s + (2 << 24), e[3] + s + (3 << 24)));
            }
            __syncwarp();
            if (__builtin_expect(!__any_sync(~0u, t == 3 && min(min(min(rl[0].w, rl[1].w), min(rl[2].w, rl[3].w)), rl[4].w) < 0x1000000u), 1)) break;
            if (r == 3) { misc[1] = 1; break; }
            #pragma unroll
            for (int i = 0; i < 5; i++) rl[i].w = __shfl_sync(~0u, rl[i].w, lane | 3) < 0x1000000u ? 0 : dm;
            gl += 64;
        }
        WS(11); ZS(5);
        asm volatile("bar.sync 7, 512;" ::: "memory");
        auto rest_ld = [&]() {
            if (w == 2 && elect_one()) {
                p2_ld(); x_ld(2);
            }
            __syncwarp();
        };
        WS(9);
        {
            int dg[3], cl[3], cr[3];
            #pragma unroll
            for (int k = 0; k < 3; k++) dg[k] = lds32(sbase + SM_DEG + ((tid & 127) + 128 * k) * 4);
            const int xi = (tid + 96) & 127, nx = lds32(sbase + SM_MISC);
            const uint32_t xe = xlist[xi];
            if (nx > XCAP / 4) sts32(sbase + SM_MISC + 4, 1);
            #pragma unroll
            for (int k = 0; k < 3; k++) {
                cl[k] = NCLS - 1 - (dg[k] <= 40 ? dg[k] : min(41 + ((dg[k] - 41) >> 3), NCLS - 1));
                cr[k] = atoms_inc(sbase + ((tid & 127) + 128 * k < nn ? SM_CLS + cl[k] * 4 : SM_DEG + NPB_MAX * 4));
            }
            rest_ld(); ZS(6);
            asm volatile("bar.sync 6, 128;" ::: "memory");
            WS(13);
            const uint2 c = lds64(sbase + SM_CLS + lane * 8);
            uint32_t inc = c.x + c.y;
            #pragma unroll
            for (int o = 1; o < 32; o <<= 1) { const uint32_t y = __shfl_up_sync(~0u, inc, o); if (lane >= o) inc += y; }
            inc = (inc - c.x - c.y) | (inc - c.y) << 16;
            #pragma unroll
            for (int k = 0; k < 3; k++) {
                const int id = (tid & 127) + 128 * k;
                const uint32_t e = __shfl_sync(~0u, inc, cl[k] >> 1);
                const uint32_t pos = id < nn ? (cl[k] & 1 ? e >> 16 : e & 0xFFFF) + cr[k] : id, nd = id < nn ? id : NONE;
                sts32(sbase + SM_SORT + pos * 4, nd | min(dg[k], 65535) << 16);
                asm volatile("st.shared.u16 [%0], %1;" :: "r"(sbase + SM_WL + pos * 2), "r"(nd) : "memory");
            }
            if (tid == 511) misc[4] = (nn - c.y + 3) >> 2;
            asm volatile("bar.sync 4, 512;" ::: "memory");
            WS(14);
            uint32_t xs = 0x80000000u, xv = tag << 16;
            auto x_get = [&]() { asm volatile("ld.relaxed.gpu.global.u32 %0, [%1];" : "=r"(xv) : "l"(gs + ((xe >> 16) & 0xFF) * (P1B + P2B) + P1B + (xe >> 24) * 4) : "memory"); };
            if (xi < 4 * nx && (xe & 0x3FFF) < NPB_MAX * 4) {
                asm volatile("atom.shared.add.u32 %0, [%1], 4;" : "=r"(xs) : "r"(db + (SM_CNT - SM_DEG) + (xe & 0xFFFF)) : "memory");
                x_get();
            }
            ZS(7);
            tables(smem, sbase, (tid + 32) & 127, ngroups);
            __syncwarp();
            while (__any_sync(~0u, ((xv >> 16) & 3) != tag)) { if (((xv >> 16) & 3) != tag) x_get(); if (++spins > (1u << 22)) __trap(); }
            if (xs < 4 * SLOT_CAP) {
                sts32(sbase + SM_EID + xs, ((xe >> 16) & 0xFF) * ch + (xv >> 19));
                asm volatile("st.shared.u16 [%0], %1;" :: "r"(sbase + SM_SRC + (xs >> 1)), "r"(xv) : "memory");
            }
            mbar_arrive(sbase + SM_XBAR + 24);
            asm volatile("bar.sync 6, 128;" ::: "memory");
        }
        WS(10); ZS(8);
        WGD();
        asm volatile("setmaxnreg.dec.sync.aligned.u32 48;");
        const int r4 = lane >> 3, c8 = lane & 7;
        const uint32_t sb = __reduce_or_sync(~0u, sbase);
        if (w < 3) {
            const char* gx = ga; const char* ge = gb;
            const uint32_t gx0 = (uint32_t)(uint64_t)gx, ge0 = (uint32_t)(uint64_t)ge, hi = (uint64_t)gx >> 32, he = (uint64_t)ge >> 32;
            const int s = (lane >> 1) & 3;
            const uint32_t xs0 = sb + SM_XS + w * NSTAGE * XS_BYTES;
            const uint32_t es0 = sb + SM_ES + w * NSTAGE * ES_BYTES + r4 * 64 + (((lane ^ (r4 >> 1)) & 1) << 4) + (s >> 1) * 256 + (s & 1) * 32;
            const uint32_t bars = sb + SM_BARS + w * 96;
            const uint32_t xoffA = (2 * r4) * 128 + ((c8 ^ (2 * r4)) << 4), xoffB = (2 * r4 + 1) * 128 + ((c8 ^ (2 * r4 + 1)) << 4);
            uint64_t pol;
            asm volatile("createpolicy.fractional.L2::evict_first.b64 %0, 1.0;" : "=l"(pol));
            uint32_t first = 1;
            WS(15);
            uint32_t ph = 1, cur = w;
            uint32_t hist = 96 * 0x010101u;
            auto done3 = [&]() { mbar_arrive(sb + SM_GBAR + ((hist >> 16) & 0xFF) * 8); };
            const uint32_t ca = sb + SM_CLAIM + lane * 4, pa = sb + SM_TINFO + r4 * 8;
            const uint2 p0 = lds64(pa + w * 32);
            const bool go = lds32(sb + SM_MISC + 4) == 0 && nn > 0;
            uint32_t pw = go ? p0.x : 0, brk = (p0.y >> 16) & C_BRK;
            const uint32_t se0 = sb + SM_EID + s * 4, xab = xoffB - xoffA, das = 2 * (xs0 + xoffA) + XS_BYTES, des = 2 * es0 + ES_BYTES, brs = 2 * bars + 48;
            uint32_t da = xs0 + xoffA, de = es0, br = bars;
            #pragma unroll 1
            while (true) {
                const uint32_t pt = __reduce_or_sync(~0u, pw);
                uint32_t se, sx;
                asm("dp2a.lo.u32.u32 %0, %1, 4, %2;" : "=r"(se) : "r"(pw), "r"(se0));
                asm("dp2a.lo.u32.u32 %0, %1, 2, %2;" : "=r"(sx) : "r"(pw), "r"(sb + SM_SRC));
                const int dv = pw >> 27;
                const uint32_t db = da + xab;
                const uint32_t sel = (pt >> 16) & 15, nx = (pt >> 20) & 127;
                uint32_t g;
                auto claim = [&]() { asm volatile("atom.shared.add.u32 %0, [%1], %2;" : "=r"(g) : "r"(ca), "r"(nx == 0 ? 1u : 0u) : "memory"); };
                if (sel == 0) break;
                claim();
                switch (sel) {
#define CASE(L, P, GEN) case L: { \
                        uint32_t oe[(P + 1) / 2], o[P]; \
                        if (first) asm volatile("bar.sync 3, 480;" ::: "memory"); \
                        _Pragma("unroll") for (int j = 0; j < (P + 1) / 2; j++) oe[j] = lds32(se + j * 16); \
                        _Pragma("unroll") for (int j = 0; j < P; j++) o[j] = lds32(sx + j * 4); \
                        mbar_wait_h(br + 8, ph); \
                        _Pragma("unroll") for (int j = 0; j < (P + 1) / 2; j++) \
                            if (LO32) { if (!GEN && 2 * j + 2 < P) cpe<false>(he, de + j * 512, oe[j], ge0, 0, 0, pol); \
                                else if (2 * j + 1 < NPMAX || s < 2) cpe<true>(he, de + j * 512, oe[j], ge0, 4 * j + s, dv, pol); } \
                            else if (!GEN && 2 * j + 2 < P) cp16e(de + j * 512, ge, oe[j], pol); else if (2 * j + 1 < NPMAX || s < 2) cp16z<32>(de + j * 512, ge, oe[j], 4 * j + s, dv, pol); \
                        _Pragma("unroll") for (int j = 0; j < P - 1; j++) { \
                            if (LO32) { cpx<0, GEN>(hi, da + j * 1024, o[j], gx0, 2 * j, dv); cpx<1, GEN>(hi, db + j * 1024, o[j], gx0, 2 * j + 1, dv); } \
                            else if (GEN) { cp16z<128>(da + j * 1024, gx, o[j] & 0xFFFFu, 2 * j, dv, 0); cp16z<128>(db + j * 1024, gx, o[j] >> 16, 2 * j + 1, dv, 0); } \
                            else { cp16i<128>(da + j * 1024, gx, o[j] & 0xFFFFu); cp16i<128>(db + j * 1024, gx, o[j] >> 16); } } \
                        if (LO32) { cpx<0, true>(hi, da + (P - 1) * 1024, o[P - 1], gx0, 2 * P - 2, dv); cpx<1, true>(hi, db + (P - 1) * 1024, o[P - 1], gx0, 2 * P - 1, dv); } \
                        else { cp16z<128>(da + (P - 1) * 1024, gx, o[P - 1] & 0xFFFFu, 2 * P - 2, dv, 0); cp16z<128>(db + (P - 1) * 1024, gx, o[P - 1] >> 16, 2 * P - 1, dv, 0); } \
                    } break;
                    CASE(6, 6, false) CASE(7, 7, false) CASE(8, 8, false) CASE(9, 9, false) CASE(10, 10, false) CASE(11, 11, false)
                    CASE(15, NPMAX, true) CASE(14, 8, true) default: CASE(13, 5, true)
#undef CASE
                }
                first = 0;
                mbar_cp_arrive(br);
                done3();
                g = __reduce_min_sync(~0u, g);
                {
                    const uint2 e = lds64(pa + (nx == 0 ? g : nx) * 32);
                    const uint2 v = tile_info(e.y);
                    pw = e.x;
                    asm volatile("st.shared.v2.u32 [%0], {%1, %2};" :: "r"(br + 16 + r4 * 8), "r"(v.x), "r"((v.y & ~C_BRK) | brk) : "memory");
                    brk = v.y & C_BRK;
                }
                mbar_arrive(br);
                hist = (hist << 8) | (nx == 0 ? cur : 96u);
                cur = nx == 0 ? g : cur;
                ph ^= br != bars; br = brs - br; da = das - da; de = des - de;
            }
            if (first) asm volatile("bar.sync 3, 480;" ::: "memory");
            if (go) {
                mbar_wait(sb + SM_ABAR + 72, 0);
                const int g0 = 3 * max((ngroups + 2) / 3 - TR, 0) + w;
                uint32_t ra[TR], gb[TR]; uint4 xv[TR], xu[TR]; char* po[TR];
                const int gz = misc[4];
                #pragma unroll
                for (int k = 0; k < TR; k++) {
                    uint32_t nd;
                    asm volatile("ld.shared.u16 %0, [%1];" : "=r"(nd) : "r"(sb + SM_WL + (g0 + 3 * k) * 8 + r4 * 2) : "memory");
                    xv[k] = __ldg((const uint4*)(gx + (size_t)(node0 + (nd == NONE ? 0u : nd)) * 128));
                    const uint32_t ro = sb + nd * 128 + ((c8 ^ (nd & 7)) << 4);
                    xu[k] = lds128(ro + SM_XU);
                    const bool some = g0 + 3 * k < gz;
                    ra[k] = some ? ro + SM_TAB : sb + SM_MISC + 64;
                    gb[k] = some ? sb + SM_GBAR + (g0 + 3 * k) * 8 : sb + SM_ABAR + 72;
                    po[k] = nd != NONE ? (char*)out + (size_t)(node0 + nd) * 128 + c8 * 16 : nullptr;
                    asm volatile("" : "+r"(ra[k]), "+r"(gb[k]), "+l"(po[k]));
                }
                #pragma unroll 1
                for (int k = 0; k < 3; k++) {
                    mbar_wait(k < 2 ? br + 8 : sb + SM_ABAR + 48 + w * 8, k < 2 ? ph : 0);
                    done3(); hist <<= 8;
                    ph ^= br != bars; br = brs - br;
                }
                #pragma unroll
                for (int k = 0; k < TR; k++) {
                    mbar_wait_c(gb[k], 0);
                    uint4 a = lds128(ra[k]);
                    finish(a, xu[k], xv[k]);
                    if (po[k]) *(uint4*)po[k] = a;
                }
            }
            cp_wait<0>();
        } else {
            const char* gx = ga; const char* ob = gb;
            mbar_wait(sb + SM_ABAR + 72, 0);
            WS(15); ZS(9);
            if (b == 0 && lane == 0) asm volatile("red.relaxed.gpu.global.add.u32 [%0], 1;" :: "l"(gbar) : "memory");
            const int rounds = misc[1] ? 0 : max((ngroups + 2) / 3 - TR, 0);
            const int gz = misc[4], fast = __reduce_min_sync(~0u, min(rounds, gz / 3));
            uint32_t wl = sb + SM_WL + r4 * 2, gbar = sb + SM_GBAR;
            auto row_at = [&](uint32_t a) { uint32_t n; asm volatile("ld.shared.u16 %0, [%1];" : "=r"(n) : "r"(a) : "memory"); return n; };
            auto fetch = [&](uint32_t n, uint4& v) {
                asm volatile("{\n.reg .b64 p;\nmad.wide.u32 p, %5, 128, %4;\nld.global.nc.L1::no_allocate.v4.u32 {%0,%1,%2,%3}, [p];\n}"
                             : "=r"(v.x), "=r"(v.y), "=r"(v.z), "=r"(v.w) : "l"(gx), "r"(n));
            };
            auto store = [&](uint32_t n, const uint4& a) {
                asm volatile("{\n.reg .b64 p;\nmad.wide.u32 p, %1, 128, %0;\nst.global.v4.u32 [p], {%2,%3,%4,%5};\n}" :: "l"(ob), "r"(n), "r"(a.x), "r"(a.y), "r"(a.z), "r"(a.w) : "memory");
            };
            uint32_t n0[3]; uint4 x0[3];
            if (fast) {
                #pragma unroll
                for (int r = 0; r < 3; r++) { n0[r] = row_at(wl + r * 8); fetch(n0[r], x0[r]); }
            }
            #pragma unroll 1
            for (int k = 0; k < fast; k++) {
                wl += 24;
                #pragma unroll
                for (int r = 0; r < 3; r++) {
                    const uint32_t nd = n0[r], ro = sb + nd * 128 + ((c8 ^ (nd & 7)) << 4);
                    const uint4 xu = lds128(ro + SM_XU);
                    n0[r] = row_at(wl + r * 8);
                    mbar_wait(gbar + r * 8, 0);
                    uint4 a = lds128(ro + SM_TAB);
                    finish(a, xu, x0[r]);
                    fetch(n0[r], x0[r]);
                    store(nd, a);
                }
                gbar += 24;
            }
            #pragma unroll 1
            for (int g = 3 * fast; g < 3 * rounds; g++) {
                const uint32_t nd = row_at(sb + SM_WL + r4 * 2 + g * 8), ro = sb + nd * 128 + ((c8 ^ (nd & 7)) << 4);
                uint4 xv, a = make_uint4(0, 0, 0, 0);
                fetch(nd, xv);
                if (g < gz) { mbar_wait(sb + SM_GBAR + g * 8, 0); a = lds128(ro + SM_TAB); }
                finish(a, lds128(ro + SM_XU), xv);
                store(nd, a);
            }
        }
    } else {
        asm volatile("setmaxnreg.inc.sync.aligned.u32 152;");
        float4 lgh[2 * NPMAX];
        uint32_t wf[40], wn[16], wt[16];
        const uint32_t mo0 = sbase + SM_TAB + (8 * (lane >> 4) + (lane & 7)) * 128 + (((2 * w + ((lane >> 3) & 1)) ^ (lane & 7)) << 4);
        mbar_wait_c(sbase + SM_ABAR + 24, 0);
        {
            const uint32_t wo = sbase + SM_WR + (2 * t) * 128 + ((ch0 * 2) ^ (t * 32));
            #pragma unroll
            for (int ks = 0; ks < 9; ks++) {
                uint32_t wr[4];
                #pragma unroll
                for (int i = 0; i < 4; i++) wr[i] = lds32((wo ^ ((i & 1) * 16)) + (16 * ks + (i & 1) + 4 * (i & 2)) * 128);
                if (ks < 5) make_wfrag<true>(wf + 4 * ks, wr); else make_wfrag<false>(wf + 4 * ks, wr);
            }
            #pragma unroll
            for (int ks = 0; ks < 4; ks++) { ldsm4t(wn + 4 * ks, mo0 + (144 + 16 * ks) * 128); ldsm4t(wt + 4 * ks, mo0 + (208 + 16 * ks) * 128); }
            if (wg == 2) {
                const uint32_t a = sbase + SM_WC + (16 * w + q) * 32 + t * 4, sw = (q >> 2) << 4;
                sts32(a + sw, wf[16]); sts32(a + 256 + sw, wf[17]); sts32(a + (sw ^ 16), wf[18]); sts32(a + 256 + (sw ^ 16), wf[19]);
                asm volatile("fence.proxy.async.shared::cta;" ::: "memory");
            }
            #pragma unroll
            for (int i = 0; i < 36; i++) asm volatile("" : "+r"(wf[i]));
        }
        WS(9);
        constexpr int NU = 6;
        const uint32_t dm = ((NPB_MAX + lane) * 4 | (tag << 14)) * 0x10001u;
        const char* const g1 = gs + (tid >> 4) * (P1B + P2B) + 256 + b * (CE * 2) + (lane & 15) * 8;
        const bool last = 2 * warp + 24 * (NU - 1) < nb;
        uint2 r1[NU];
        #pragma unroll
        for (int i = 0; i < NU; i++) r1[i] = make_uint2(dm, (tid >> 4) + 24 * i < nb ? 0 : dm);
        uint32_t spins = 0;
        asm volatile("bar.sync 5, 512;" ::: "memory");
        while (true) {
            #pragma unroll
            for (int i = 0; i < NU; i++) ld_unit(r1[i], g1 + i * (24 * (P1B + P2B)), (r1[i].y ^ dm) & 0xC000);
            #pragma unroll
            for (int i = 0; i < 4; i++) sts128(mo0 + wg * 16384 + 8192 + i * 2048, make_uint4(wt[4*i], wt[4*i+1], wt[4*i+2], wt[4*i+3]));
            uint32_t bad = 0;
            #pragma unroll
            for (int i = 0; i < NU; i++) bad |= r1[i].y ^ dm;
            const bool more = __any_sync(~0u, bad & 0xC000);
            if (spins == 0) WS(2);
            if (!more) break;
            if (++spins > (1u << 22)) __trap();
        }
        WS(3);
        const uint32_t db = sbase + SM_DEG - (tag << 14);
        uint32_t rk[NU][4];
        #pragma unroll
        for (int i = 0; i < NU; i++) {
            #pragma unroll
            for (int k = 0; k < 4; k++) {
                asm("dp2a.lo.u32.u32 %0, %1, %2, %3;" : "=r"(rk[i][k]) : "r"(k < 2 ? r1[i].x : r1[i].y), "r"(k & 1 ? 0x100u : 1u), "r"(db));
                if (i < NU - 1 || last) asm volatile("red.shared.add.u32 [%0], 1;" :: "r"(rk[i][k]) : "memory");
            }
        }
        WS(10);
        asm volatile("bar.sync 7, 512;" ::: "memory");
        WS(11);
        {
            const uint32_t ev = (lds32(sbase + SM_DEG + tid * 4) + 1) & ~1u;
            uint32_t inc = ev, base = 0;
            #pragma unroll
            for (int o = 1; o < 32; o <<= 1) { const uint32_t y = __shfl_up_sync(~0u, inc, o); if (lane >= o) inc += y; }
            if (lane == 31) {
                asm volatile("atom.shared.add.u32 %0, [%1], %2;" : "=r"(base) : "r"(sbase + SM_MISC + 24), "r"(inc) : "memory");
                if (base + inc > SLOT_CAP) misc[1] = 1;
            }
            const uint32_t s0 = min(__shfl_sync(~0u, base, 31) + inc - ev, SLOT_CAP);
            sts32(sbase + SM_CNT + tid * 4, 4 * s0);
            asm volatile("st.shared.u16 [%0], %1;" :: "r"(sbase + SM_BASE + tid * 2), "r"(s0) : "memory");
        }
        asm volatile("bar.arrive 4, 512;" ::: "memory");
        asm volatile("bar.sync 1, 384;" ::: "memory");
        WS(13);
        #pragma unroll
        for (int i = 0; i < NU; i++) {
            if (i < NU - 1 || last) {
                #pragma unroll
                for (int k = 0; k < 4; k++) asm volatile("atom.shared.add.u32 %0, [%0+%1], 4;" : "+r"(rk[i][k]) : "n"(SM_CNT - SM_DEG) : "memory");
            }
        }
        WS(14);
        uint4 r2[NU];
        mbar_wait_c(sbase + SM_ABAR + 40, 0);
        WS(4);
        #pragma unroll
        for (int i = 0; i < NU; i++) r2[i] = lds128(sbase + SM_P2 + (i < NU - 1 ? tid + 384 * i : min(tid + 384 * i, P2B / 16 - 1)) * 16);
        while (true) {
            uint32_t bad = 0;
            #pragma unroll
            for (int i = 0; i < NU; i++) if (i < NU - 1 || last) bad |= (r2[i].x ^ (tag << 16)) & ~(rk[i][0] >> 14);
            if (__builtin_expect(!__any_sync(~0u, bad & 0x30000), 1)) break;
            #pragma unroll
            for (int i = 0; i < NU; i++)
                ld_unit(r2[i], g1 + (P1B + b * (CE * 2) + (lane & 15) * 8 + i * (24 * (P1B + P2B))), (i < NU - 1 || last) && ((r2[i].x ^ (tag << 16)) & ~(rk[i][0] >> 14) & 0x30000));
            if (++spins > (1u << 22)) __trap();
        }
        WS(16);
        const uint32_t sbu = __reduce_or_sync(~0u, sbase);
        auto place = [&](uint32_t s4, uint32_t v, uint32_t eb) {
            asm volatile("{\n.reg .pred p;\nsetp.lt.u32 p, %0, %5;\n@p st.shared.u32 [%1], %2;\n@p st.shared.u16 [%3], %4;\n}"
                         :: "r"(s4), "r"(sbu + SM_EID + s4), "r"(eb + (v >> 19)), "r"(sbu + SM_SRC + (s4 >> 1)), "r"(v), "n"(4 * SLOT_CAP) : "memory");
        };
        #pragma unroll
        for (int i = 0; i < NU; i++) {
            const uint32_t eb = ((tid >> 4) + 24 * i) * ch;
            if (i == 2 && warp == 10 && elect_one()) { x_ld(1); x_ld(0); }
            if (i < NU - 1 || last) { place(rk[i][0], r2[i].x, eb); place(rk[i][1], r2[i].y, eb); place(rk[i][2], r2[i].z, eb); place(rk[i][3], r2[i].w, eb); }
        }
        WS(1);
        WGD();
        asm volatile("bar.arrive 3, 480;" ::: "memory");
        {
        int lane;
        asm volatile("mov.u32 %0, %%laneid;" : "=r"(lane));
        const int q = lane >> 2, t = lane & 3, ch0 = 16 * w + 2 * q;
        const uint32_t sbase = sbu;
        { const uint2 z = lds64(sbase + SM_OH + 8); wf[37] = z.x; wf[38] = z.y; }
        const uint32_t c2 = __shfl_sync(~0u, ch0 * 2, lane), t8 = __shfl_sync(~0u, t * 8, lane);
        float g[4 * NPMAX], h[4 * NPMAX];
        float4 cyr = make_float4(0.f, 0.f, 0.f, 0.f);
        {
            const uint32_t mo = sbase + (8 * (lane >> 4) + (lane & 7)) * 128 + (((2 * w + ((lane >> 3) & 1)) ^ (lane & 7)) << 4);
            mbar_wait_c(sbase + SM_XBAR + wg * 8, 0);
            WSP(4);
            node_mma2(g, h, wn, desc_sw128(sbase + SM_XU + wg * 16384));
            TileMMA<8>::wait_g(g);
            node_rows(mo + SM_TAB + wg * 16384, g);
            TileMMA<8>::wait_h(h);
            WSP(5);
            #pragma unroll
            for (int i = 0; i < 4; i++) {
                const uint4 f = lds128(mo + SM_TAB + wg * 16384 + 8192 + i * 2048);
                wn[4*i] = f.x; wn[4*i+1] = f.y; wn[4*i+2] = f.z; wn[4*i+3] = f.w;
            }
            __syncwarp();
            node_rows(mo + SM_TAB + wg * 16384 + 8192, h);
            mbar_arrive(sbase + SM_XBAR + 24);
            WSP(2);
            node_mma2(g, h, wn, desc_sw128(sbase + SM_XU + wg * 16384));
            TileMMA<8>::wait_g(g);
            asm volatile("bar.sync %0, 128;" :: "r"(8 + wg) : "memory");
            node_rows(mo + SM_XU + wg * 16384, g);
            TileMMA<8>::wait_h(h);
            WSP(3);
            asm volatile("bar.sync %0, 128;" :: "r"(8 + wg) : "memory");
            node_rows(mo + SM_XU + wg * 16384 + 8192, h);
            mbar_arrive(sbase + SM_ABAR + 72);
            mbar_wait_c(sbase + SM_XBAR + 24, 0);
            if (__builtin_expect(lds32(sbase + SM_MISC + 4) != 0, 0)) { slow_bin(x, ea, src, dst, wa, wb, wc, wu, wv, out, E, node0, nn, 384); return; }
            WS(6);
        }
        const uint64_t wcd = __reduce_or_sync(~0u, (((sbase + SM_WC) & 0x3FFFF) >> 4) | (8u << 16)) | EDHI;
        const uint32_t bar0 = __reduce_or_sync(~0u, sbase + SM_BARS + wg * 96);
        const uint32_t xd0 = __reduce_or_sync(~0u, (((sbase + SM_XS + wg * NSTAGE * XS_BYTES) & 0x3FFFF) >> 4) | (1u << 16));
        const uint32_t ed0 = __reduce_or_sync(~0u, (((sbase + SM_ES + wg * NSTAGE * ES_BYTES) & 0x3FFFF) >> 4) | (8u << 16));
        const uint64_t ohd = __reduce_or_sync(~0u, (((sbase + SM_OH) & 0x3FFFF) >> 4) | (8u << 16));
        const uint32_t tabx = __reduce_or_sync(~0u, sbase + SM_TAB);
        const uint32_t bars = __reduce_or_sync(~0u, 2 * bar0 + 48), xds = __reduce_or_sync(~0u, 2 * xd0 + XS_BYTES / 16), eds = __reduce_or_sync(~0u, 2 * ed0 + ES_BYTES / 16);
        uint32_t bar = bar0, xd = xd0, ed = ed0, ph = 0, code, w1, ta, pta = NONE * 128 + c2;
        float pn0 = 0.f, pd0 = 1.f, pn1 = 0.f, pd1 = 1.f;
        uint2 ni = tile_info(lds32(sbase + SM_TINFO + wg * 32 + t * 8 + 4));
        auto fetch_a = [&]() {
            ta = (ni.x & 0xFFFFu) ^ c2;
            wf[36] = lds32(tabx + ta); wf[39] = lds32(tabx + ta);
            code = __reduce_or_sync(~0u, ni.y);
        };
        auto emit = [&]() { sts32(tabx + pta, pack_bf16(pn0 * rcpf(pd0), pn1 * rcpf(pd1))); };
        auto carry = [&]() {
            if (w1 & C_CONT) { pn0 += cyr.x; pd0 += cyr.y; pn1 += cyr.z; pd1 += cyr.w; }
            if (w1 & C_MORE) { cyr = make_float4(pn0, pd0 - EPS2, pn1, pd1 - EPS2); pn0 = pn1 = 0.f; pta = NONE * 128 + c2; }
        };
        auto next = [&](uint32_t fb) {
            pta = ta;
            w1 = ni.y;
            ni = lds64(fb + 16 + t8);
        };
        fetch_a();
        while (true) {
            switch (code & 15) {
                default: goto finished;
#define TILE(P) { \
                    float dmin; \
                    do { \
                        mbar_wait_c(bar, ph); \
                        TileMMA<P>::issue(g, h, wf, xd | (0x40000040ull << 32), ed | EDHI, ohd, wcd); \
                        const uint32_t eb = bar + 8; \
                        ph ^= bar != bar0; bar = bars - bar; xd = xds - xd; ed = eds - ed; \
                          \
                        asm volatile("{\n.reg .pred p;\nsetp.eq.u32 p, %0, 77;\n@p trap;\n}" :: "r"(xds) : "memory"); \
                        emit(); next(eb - 8); \
                        TileMMA<P>::wait_g(g); fetch_a(); TileMMA<P>::wait_h(h); \
                        mbar_arrive(eb); \
                        float m1; \
                        asm("set.gt.f32.f32 %0, %1, 0f0000007F;" : "=f"(m1) : "f"(__uint_as_float(w1))); \
                        epi_fast<P>(g, h, m1, __uint_as_float(w1), pn0, pd0, pn1, pd1, dmin); \
                    } while (!(__any_sync(~0u, dmin < TAU * 2 * P) | ((code & 31) != P))); \
                    if (__builtin_expect(__any_sync(~0u, (int)w1 < 0 || dmin < TAU * 2 * P), 0)) { \
                        int dv; \
                        const bool bad = unpad(w1, P, g[4 * P - 7], g[4 * P - 5], pd0, pd1, dv); \
                        const uint32_t nb_ = __reduce_add_sync(~0u, bad ? 256 + dv : 0); \
                        if (nb_) { \
                            FBT(2); \
                            const uint32_t spare = tabx + (NPB_MAX - 3) * 128; \
                            uint32_t taken = 1; \
                            if (nb_ < 512) { \
                                asm volatile("atom.shared.or.b32 %0, [%1], %2;" : "=r"(taken) : "r"(spare + LOCK_OFF + (bad ? 0 : 4)), "r"(bad ? 1 : 0) : "memory"); \
                                taken = __reduce_or_sync(~0u, taken); \
                            } \
                            float4 r; \
                            if (!taken) { \
                                if (bad) { _Pragma("unroll") for (int i = 0; i < P; i++) { \
                                    sts128(spare + i * 16, make_uint4(__float_as_uint(g[4*i]), __float_as_uint(g[4*i+1]), __float_as_uint(g[4*i+2]), __float_as_uint(g[4*i+3]))); \
                                    sts128(spare + (NPMAX + i) * 16, make_uint4(__float_as_uint(h[4*i]), __float_as_uint(h[4*i+1]), __float_as_uint(h[4*i+2]), __float_as_uint(h[4*i+3]))); } } \
                                FBT(3); \
                                r = epi_single(spare, nb_ - 256); \
                            } else { \
                                epi_dump<P>(g, h, lgh); \
                                FBT(3); \
                                r = epi_exact(lgh, P, dv); \
                            } \
                            if (bad) { pn0 = r.x; pd0 = r.y; pn1 = r.z; pd1 = r.w; } \
                            if (pd0 != 77.f) FBT(4); \
                        } \
                    } \
                    if (code & C_BRK) { carry(); if (P != 11 && (code & 15) == P) goto L##P; } \
                    if (P == 11) {         \
                        const uint32_t a = tabx + (SM_WC - SM_TAB) + (c2 & 0x60) * 16 + (c2 & 0x1C) * 8 + (t8 >> 1), sw = c2 & 16; \
                        wf[16] = lds32(a + sw); wf[17] = lds32(a + 256 + sw); wf[18] = lds32(a + (sw ^ 16)); wf[19] = lds32(a + 256 + (sw ^ 16)); \
                    } }
#define CASE(P, UP, DN) case P: L##P: TILE(P) \
                    if (P > NPMIN && (code & 15) == P - 1) goto L##DN; \
                    if (P <= 6 && (code & 15) == 0) goto finished; \
                    if ((code & 15) == UP) goto L##UP; \
                    break;
                CASE(11, 11, 10) CASE(10, 11, 9) CASE(9, 10, 8) CASE(8, 9, 7) CASE(7, 8, 6) CASE(6, 7, 5) CASE(5, 6, 4) CASE(4, 5, 4)
#undef CASE
#undef TILE
            }
        }
finished:
        emit();
        mbar_arrive(sbase + SM_ABAR + 48 + wg * 8);
        }
    }
    WS(17); WG1();
}

}

extern "C" void kernel_launch(void* const* d_in, const int* in_sizes, int n_in, void* d_out, int out_size) {
    const __nv_bfloat16* x = (const __nv_bfloat16*)d_in[0];
    const __nv_bfloat16* ea = (const __nv_bfloat16*)d_in[1];
    const int* src = (const int*)d_in[2];
    const int* dst = (const int*)d_in[3];
    const __nv_bfloat16* wa = (const __nv_bfloat16*)d_in[4];
    const __nv_bfloat16* wb = (const __nv_bfloat16*)d_in[5];
    const __nv_bfloat16* wc = (const __nv_bfloat16*)d_in[6];
    const __nv_bfloat16* wu = (const __nv_bfloat16*)d_in[7];
    const __nv_bfloat16* wv = (const __nv_bfloat16*)d_in[8];
    __nv_bfloat16* out = (__nv_bfloat16*)d_out;
    int N = in_sizes[0] / 64, E = in_sizes[2];
    static int sms = 0;
    static CUtensorMap tm2;
    static bool tm_ok = false;
    typedef CUresult (*EncFn)(CUtensorMap*, CUtensorMapDataType, cuuint32_t, void*, const cuuint64_t*, const cuuint64_t*, const cuuint32_t*,
                              const cuuint32_t*, CUtensorMapInterleave, CUtensorMapSwizzle, CUtensorMapL2promotion, CUtensorMapFloatOOBfill);
    static void* fn = nullptr;
    static void* gp = nullptr; static void* gb = nullptr;
    if (!sms) {
        cudaDeviceGetAttribute(&sms, cudaDevAttrMultiProcessorCount, 0);
        cudaDriverEntryPointQueryResult qr;
        cudaGetDriverEntryPoint("cuTensorMapEncodeTiled", &fn, cudaEnableDefault, &qr);
        cudaGetSymbolAddress(&gp, g_str); cudaGetSymbolAddress(&gb, g_bar);
        if (fn && gp && gb) {
            const cuuint32_t rows = sms < NB_MAX ? sms : NB_MAX;
            cuuint64_t g2[2] = {(P1B + P2B) / 4, NB_MAX}, gs[1] = {P1B + P2B};
            cuuint32_t b2[2] = {CE, rows}, es[2] = {1, 1};
            tm_ok = ((EncFn)fn)(&tm2, CU_TENSOR_MAP_DATA_TYPE_UINT32, 2, gp, g2, gs, b2, es, CU_TENSOR_MAP_INTERLEAVE_NONE, CU_TENSOR_MAP_SWIZZLE_NONE,
                                CU_TENSOR_MAP_L2_PROMOTION_NONE, CU_TENSOR_MAP_FLOAT_OOB_FILL_NONE) == CUDA_SUCCESS;
        }
        cudaFuncSetAttribute(gcn_kernel<true>, cudaFuncAttributeMaxDynamicSharedMemorySize, SMEM_LAUNCH);
        cudaFuncSetAttribute(gcn_kernel<false>, cudaFuncAttributeMaxDynamicSharedMemorySize, SMEM_LAUNCH);
    }
    auto rows = [&](CUtensorMap* tm, const void* base, uint64_t n, uint32_t box) {
        cuuint64_t gd[2] = {64, n}, gs[1] = {128};
        cuuint32_t bx[2] = {64, box}, es[2] = {1, 1};
        return ((EncFn)fn)(tm, CU_TENSOR_MAP_DATA_TYPE_BFLOAT16, 2, (void*)base, gd, gs, bx, es, CU_TENSOR_MAP_INTERLEAVE_NONE, CU_TENSOR_MAP_SWIZZLE_128B,
                           CU_TENSOR_MAP_L2_PROMOTION_NONE, CU_TENSOR_MAP_FLOAT_OOB_FILL_NONE) == CUDA_SUCCESS;
    };
    const uintptr_t wp[4] = {(uintptr_t)wa, (uintptr_t)wb, (uintptr_t)wu, (uintptr_t)wv};
    uintptr_t w0 = wp[0], w1 = wp[0], wal = 0;
    for (int i = 1; i < 4; i++) { w0 = wp[i] < w0 ? wp[i] : w0; w1 = wp[i] > w1 ? wp[i] : w1; wal |= wp[i] - wp[0]; }
    int4 wrow = make_int4((int)((wp[0] - w0) >> 7), (int)((wp[1] - w0) >> 7), (int)((wp[2] - w0) >> 7), (int)((wp[3] - w0) >> 7));
    CUtensorMap tmw, tmc, tmx;
    const bool maps = tm_ok && N > 0 && !(wal & 127) && ((w1 - w0) >> 7) < (1u << 30) && rows(&tmw, (void*)w0, ((w1 - w0) >> 7) + 64, 64) && rows(&tmc, wc, 16, 16) && rows(&tmx, x, N, 128);
    int nb = sms < NB_MAX ? sms : NB_MAX;
    int npb = (N + nb - 1) / nb;
    int ch = (((E + nb - 1) / nb) + 3) & ~3;
    if (!maps || npb > NPB_MAX || ch > CH_MAX || (E & 3) || N > 65535 || npb < 2 || (((uintptr_t)src | (uintptr_t)dst | (uintptr_t)wa | (uintptr_t)wb | (uintptr_t)wc | (uintptr_t)wu | (uintptr_t)wv) & 15)) {
        int g = 1024, p = (N + g - 1) / g;
        slow_kernel<<<g, 256>>>(x, ea, src, dst, wa, wb, wc, wu, wv, out, N, E, p < 1 ? 1 : p);
        return;
    }
    uint32_t magic = (uint32_t)((1ull << 32) / (uint32_t)npb) + 1u;
    void* args[] = {&dst, &gb, &gp, &src, &E, &ch, &N, &npb, &magic, &x, &ea, &wa, &wb, &wc, &wu, &wv, &out, &wrow, &tm2, &tmw, &tmc, &tmx};
    const bool lo32 = ((uintptr_t)x >> 32) == (((uintptr_t)x + (size_t)N * 128 - 1) >> 32) && ((uintptr_t)ea >> 32) == (((uintptr_t)ea + (size_t)E * 32 - 1) >> 32);
    cudaLaunchCooperativeKernel(lo32 && !FORCE64 ? (const void*)gcn_kernel<true> : (const void*)gcn_kernel<false>, dim3(nb), dim3(THREADS), args, SMEM_LAUNCH, cudaStreamPerThread);
}
```

```cpp
#include <cuda_runtime.h>
#include <cuda.h>
#include <cuda_bf16.h>
#include <stdint.h>

namespace {

constexpr int N_MAX = 65536;
constexpr int NPMIN = 4;
constexpr int NPMAX = 11;
constexpr int THREADS = 512;
constexpr int EPT = 12;
constexpr int CH_MAX = THREADS * EPT;
constexpr int NB_MAX = 134;
constexpr int GAL = 128;
constexpr int CE = 64;
constexpr int P1B = (256 + NB_MAX * CE * 2 + GAL - 1) / GAL * GAL;
constexpr int P2B = (256 + NB_MAX * CE * 4 + GAL - 1) / GAL * GAL;
constexpr int NPB_MAX = 384;
constexpr int SLOT_CAP = 6784;
constexpr int TILE_CAP = 124;
constexpr int TILE_X = 8;
constexpr int NCLS = 64;
constexpr int XCAP = 128;
constexpr int NSTAGE = 2;
constexpr int TR = 2;
constexpr float LOG2E = 1.4426950408889634f;

__device__ __align__(128) uint4 g_str[NB_MAX * (P1B + P2B) / 16];
__device__ __align__(128) unsigned g_bar[32];
__device__ float g_slow[N_MAX * 128];

#define WS(k)
#define WGD()
#define ZS(k)
#define FBT(k)
#define WSP(k)
#define WSL(k)
#define WSG(k)
#define WG0()
#define WG1()
#define SMEM_LAUNCH SMEM_BYTES
#define FORCE64 0
#define EDHI ((16ull << 32) | (3ull << 62))
template<int NP> struct TileMMA;
template<> struct TileMMA<4> {
  static __device__ __forceinline__ void issue(float* g, float* h, const uint32_t* w, uint64_t dx, uint64_t de, uint64_t dh, uint64_t dc) {
    asm volatile(
      "{\n.reg .b64 dx1, dx2, dx3;\n"
      "add.s64 dx1, %72, 2;\nadd.s64 dx2, %72, 4;\nadd.s64 dx3, %72, 6;\n"
      "wgmma.fence.sync.aligned;\n"
      "wgmma.mma_async.sync.aligned.m64n32k16.f32.bf16.bf16 {%0, %1, %2, %3, %4, %5, %6, %7, %8, %9, %10, %11, %12, %13, %14, %15}, {%68, %69, %70, %71}, %74, 0, 1, 1, 0;\n"
      "wgmma.mma_async.sync.aligned.m64n32k16.f32.bf16.bf16 {%0, %1, %2, %3, %4, %5, %6, %7, %8, %9, %10, %11, %12, %13, %14, %15}, {%48, %49, %50, %51}, %73, 1, 1, 1, 0;\n"
      "wgmma.mma_async.sync.aligned.m64n32k16.f32.bf16.bf16 {%0, %1, %2, %3, %4, %5, %6, %7, %8, %9, %10, %11, %12, %13, %14, %15}, {%32, %33, %34, %35}, %72, 1, 1, 1, 0;\n"
      "wgmma.mma_async.sync.aligned.m64n32k16.f32.bf16.bf16 {%0, %1, %2, %3, %4, %5, %6, %7, %8, %9, %10, %11, %12, %13, %14, %15}, {%36, %37, %38, %39}, dx1, 1, 1, 1, 0;\n"
      "wgmma.mma_async.sync.aligned.m64n32k16.f32.bf16.bf16 {%0, %1, %2, %3, %4, %5, %6, %7, %8, %9, %10, %11, %12, %13, %14, %15}, {%40, %41, %42, %43}, dx2, 1, 1, 1, 0;\n"
      "wgmma.mma_async.sync.aligned.m64n32k16.f32.bf16.bf16 {%0, %1, %2, %3, %4, %5, %6, %7, %8, %9, %10, %11, %12, %13, %14, %15}, {%44, %45, %46, %47}, dx3, 1, 1, 1, 0;\n"
      "wgmma.commit_group.sync.aligned;\n"
      "wgmma.mma_async.sync.aligned.m64n32k16.f32.bf16.bf16 {%16, %17, %18, %19, %20, %21, %22, %23, %24, %25, %26, %27, %28, %29, %30, %31}, {%52, %53, %54, %55}, %72, 0, 1, 1, 0;\n"
      "wgmma.mma_async.sync.aligned.m64n32k16.f32.bf16.bf16 {%16, %17, %18, %19, %20, %21, %22, %23, %24, %25, %26, %27, %28, %29, %30, %31}, {%56, %57, %58, %59}, dx1, 1, 1, 1, 0;\n"
      "wgmma.mma_async.sync.aligned.m64n32k16.f32.bf16.bf16 {%16, %17, %18, %19, %20, %21, %22, %23, %24, %25, %26, %27, %28, %29, %30, %31}, {%60, %61, %62, %63}, dx2, 1, 1, 1, 0;\n"
      "wgmma.mma_async.sync.aligned.m64n32k16.f32.bf16.bf16 {%16, %17, %18, %19, %20, %21, %22, %23, %24, %25, %26, %27, %28, %29, %30, %31}, {%64, %65, %66, %67}, dx3, 1, 1, 1, 0;\n"
      "wgmma.commit_group.sync.aligned;\n}\n"
      : "=f"(g[0]), "=f"(g[1]), "=f"(g[2]), "=f"(g[3]), "=f"(g[4]), "=f"(g[5]), "=f"(g[6]), "=f"(g[7]), "=f"(g[8]), "=f"(g[9]), "=f"(g[10]), "=f"(g[11]), "=f"(g[12]), "=f"(g[13]), "=f"(g[14]), "=f"(g[15]),
        "=f"(h[0]), "=f"(h[1]), "=f"(h[2]), "=f"(h[3]), "=f"(h[4]), "=f"(h[5]), "=f"(h[6]), "=f"(h[7]), "=f"(h[8]), "=f"(h[9]), "=f"(h[10]), "=f"(h[11]), "=f"(h[12]), "=f"(h[13]), "=f"(h[14]), "=f"(h[15])
      : "r"(w[0]), "r"(w[1]), "r"(w[2]), "r"(w[3]), "r"(w[4]), "r"(w[5]), "r"(w[6]), "r"(w[7]), "r"(w[8]), "r"(w[9]), "r"(w[10]), "r"(w[11]), "r"(w[12]), "r"(w[13]), "r"(w[14]), "r"(w[15]), "r"(w[16]), "r"(w[17]), "r"(w[18]), "r"(w[19]), "r"(w[20]), "r"(w[21]), "r"(w[22]), "r"(w[23]), "r"(w[24]), "r"(w[25]), "r"(w[26]), "r"(w[27]), "r"(w[28]), "r"(w[29]), "r"(w[30]), "r"(w[31]), "r"(w[32]), "r"(w[33]), "r"(w[34]), "r"(w[35]), "r"(w[36]), "r"(w[37]), "r"(w[38]), "r"(w[39]), "l"(dx), "l"(de), "l"(dh)
      : "memory");
  }
  static __device__ __forceinline__ void wait_g(float* g) {
    asm volatile("wgmma.wait_group.sync.aligned 1;\n"
      : "+f"(g[0]), "+f"(g[1]), "+f"(g[2]), "+f"(g[3]), "+f"(g[4]), "+f"(g[5]), "+f"(g[6]), "+f"(g[7]), "+f"(g[8]), "+f"(g[9]), "+f"(g[10]), "+f"(g[11]), "+f"(g[12]), "+f"(g[13]), "+f"(g[14]), "+f"(g[15])
      :: "memory");
  }
  static __device__ __forceinline__ void wait_h(float* h) {
    asm volatile("wgmma.wait_group.sync.aligned 0;\n"
      : "+f"(h[0]), "+f"(h[1]), "+f"(h[2]), "+f"(h[3]), "+f"(h[4]), "+f"(h[5]), "+f"(h[6]), "+f"(h[7]), "+f"(h[8]), "+f"(h[9]), "+f"(h[10]), "+f"(h[11]), "+f"(h[12]), "+f"(h[13]), "+f"(h[14]), "+f"(h[15])
      :: "memory");
  }
};
template<> struct TileMMA<5> {
  static __device__ __forceinline__ void issue(float* g, float* h, const uint32_t* w, uint64_t dx, uint64_t de, uint64_t dh, uint64_t dc) {
    asm volatile(
      "{\n.reg .b64 dx1, dx2, dx3;\n"
      "add.s64 dx1, %80, 2;\nadd.s64 dx2, %80, 4;\nadd.s64 dx3, %80, 6;\n"
      "wgmma.fence.sync.aligned;\n"
      "wgmma.mma_async.sync.aligned.m64n40k16.f32.bf16.bf16 {%0, %1, %2, %3, %4, %5, %6, %7, %8, %9, %10, %11, %12, %13, %14, %15, %16, %17, %18, %19}, {%76, %77, %78, %79}, %82, 0, 1, 1, 0;\n"
      "wgmma.mma_async.sync.aligned.m64n40k16.f32.bf16.bf16 {%0, %1, %2, %3, %4, %5, %6, %7, %8, %9, %10, %11, %12, %13, %14, %15, %16, %17, %18, %19}, {%56, %57, %58, %59}, %81, 1, 1, 1, 0;\n"
      "wgmma.mma_async.sync.aligned.m64n40k16.f32.bf16.bf16 {%0, %1, %2, %3, %4, %5, %6, %7, %8, %9, %10, %11, %12, %13, %14, %15, %16, %17, %18, %19}, {%40, %41, %42, %43}, %80, 1, 1, 1, 0;\n"
      "wgmma.mma_async.sync.aligned.m64n40k16.f32.bf16.bf16 {%0, %1, %2, %3, %4, %5, %6, %7, %8, %9, %10, %11, %12, %13, %14, %15, %16, %17, %18, %19}, {%44, %45, %46, %47}, dx1, 1, 1, 1, 0;\n"
      "wgmma.mma_async.sync.aligned.m64n40k16.f32.bf16.bf16 {%0, %1, %2, %3, %4, %5, %6, %7, %8, %9, %10, %11, %12, %13, %14, %15, %16, %17, %18, %19}, {%48, %49, %50, %51}, dx2, 1, 1, 1, 0;\n"
      "wgmma.mma_async.sync.aligned.m64n40k16.f32.bf16.bf16 {%0, %1, %2, %3, %4, %5, %6, %7, %8, %9, %10, %11, %12, %13, %14, %15, %16, %17, %18, %19}, {%52, %53, %54, %55}, dx3, 1, 1, 1, 0;\n"
      "wgmma.commit_group.sync.aligned;\n"
      "wgmma.mma_async.sync.aligned.m64n40k16.f32.bf16.bf16 {%20, %21, %22, %23, %24, %25, %26, %27, %28, %29, %30, %31, %32, %33, %34, %35, %36, %37, %38, %39}, {%60, %61, %62, %63}, %80, 0, 1, 1, 0;\n"
      "wgmma.mma_async.sync.aligned.m64n40k16.f32.bf16.bf16 {%20, %21, %22, %23, %24, %25, %26, %27, %28, %29, %30, %31, %32, %33, %34, %35, %36, %37, %38, %39}, {%64, %65, %66, %67}, dx1, 1, 1, 1, 0;\n"
      "wgmma.mma_async.sync.aligned.m64n40k16.f32.bf16.bf16 {%20, %21, %22, %23, %24, %25, %26, %27, %28, %29, %30, %31, %32, %33, %34, %35, %36, %37, %38, %39}, {%68, %69, %70, %71}, dx2, 1, 1, 1, 0;\n"
      "wgmma.mma_async.sync.aligned.m64n40k16.f32.bf16.bf16 {%20, %21, %22, %23, %24, %25, %26, %27, %28, %29, %30, %31, %32, %33, %34, %35, %36, %37, %38, %39}, {%72, %73, %74, %75}, dx3, 1, 1, 1, 0;\n"
      "wgmma.commit_group.sync.aligned;\n}\n"
      : "=f"(g[0]), "=f"(g[1]), "=f"(g[2]), "=f"(g[3]), "=f"(g[4]), "=f"(g[5]), "=f"(g[6]), "=f"(g[7]), "=f"(g[8]), "=f"(g[9]), "=f"(g[10]), "=f"(g[11]), "=f"(g[12]), "=f"(g[13]), "=f"(g[14]), "=f"(g[15]), "=f"(g[16]), "=f"(g[17]), "=f"(g[18]), "=f"(g[19]),
        "=f"(h[0]), "=f"(h[1]), "=f"(h[2]), "=f"(h[3]), "=f"(h[4]), "=f"(h[5]), "=f"(h[6]), "=f"(h[7]), "=f"(h[8]), "=f"(h[9]), "=f"(h[10]), "=f"(h[11]), "=f"(h[12]), "=f"(h[13]), "=f"(h[14]), "=f"(h[15]), "=f"(h[16]), "=f"(h[17]), "=f"(h[18]), "=f"(h[19])
      : "r"(w[0]), "r"(w[1]), "r"(w[2]), "r"(w[3]), "r"(w[4]), "r"(w[5]), "r"(w[6]), "r"(w[7]), "r"(w[8]), "r"(w[9]), "r"(w[10]), "r"(w[11]), "r"(w[12]), "r"(w[13]), "r"(w[14]), "r"(w[15]), "r"(w[16]), "r"(w[17]), "r"(w[18]), "r"(w[19]), "r"(w[20]), "r"(w[21]), "r"(w[22]), "r"(w[23]), "r"(w[24]), "r"(w[25]), "r"(w[26]), "r"(w[27]), "r"(w[28]), "r"(w[29]), "r"(w[30]), "r"(w[31]), "r"(w[32]), "r"(w[33]), "r"(w[34]), "r"(w[35]), "r"(w[36]), "r"(w[37]), "r"(w[38]), "r"(w[39]), "l"(dx), "l"(de), "l"(dh)
      : "memory");
  }
  static __device__ __forceinline__ void wait_g(float* g) {
    asm volatile("wgmma.wait_group.sync.aligned 1;\n"
      : "+f"(g[0]), "+f"(g[1]), "+f"(g[2]), "+f"(g[3]), "+f"(g[4]), "+f"(g[5]), "+f"(g[6]), "+f"(g[7]), "+f"(g[8]), "+f"(g[9]), "+f"(g[10]), "+f"(g[11]), "+f"(g[12]), "+f"(g[13]), "+f"(g[14]), "+f"(g[15]), "+f"(g[16]), "+f"(g[17]), "+f"(g[18]), "+f"(g[19])
      :: "memory");
  }
  static __device__ __forceinline__ void wait_h(float* h) {
    asm volatile("wgmma.wait_group.sync.aligned 0;\n"
      : "+f"(h[0]), "+f"(h[1]), "+f"(h[2]), "+f"(h[3]), "+f"(h[4]), "+f"(h[5]), "+f"(h[6]), "+f"(h[7]), "+f"(h[8]), "+f"(h[9]), "+f"(h[10]), "+f"(h[11]), "+f"(h[12]), "+f"(h[13]), "+f"(h[14]), "+f"(h[15]), "+f"(h[16]), "+f"(h[17]), "+f"(h[18]), "+f"(h[19])
      :: "memory");
  }
};
template<> struct TileMMA<6> {
  static __device__ __forceinline__ void issue(float* g, float* h, const uint32_t* w, uint64_t dx, uint64_t de, uint64_t dh, uint64_t dc) {
    asm volatile(
      "{\n.reg .b64 dx1, dx2, dx3;\n"
      "add.s64 dx1, %88, 2;\nadd.s64 dx2, %88, 4;\nadd.s64 dx3, %88, 6;\n"
      "wgmma.fence.sync.aligned;\n"
      "wgmma.mma_async.sync.aligned.m64n48k16.f32.bf16.bf16 {%0, %1, %2, %3, %4, %5, %6, %7, %8, %9, %10, %11, %12, %13, %14, %15, %16, %17, %18, %19, %20, %21, %22, %23}, {%84, %85, %86, %87}, %90, 0, 1, 1, 0;\n"
      "wgmma.mma_async.sync.aligned.m64n48k16.f32.bf16.bf16 {%0, %1, %2, %3, %4, %5, %6, %7, %8, %9, %10, %11, %12, %13, %14, %15, %16, %17, %18, %19, %20, %21, %22, %23}, {%64, %65, %66, %67}, %89, 1, 1, 1, 0;\n"
      "wgmma.mma_async.sync.aligned.m64n48k16.f32.bf16.bf16 {%0, %1, %2, %3, %4, %5, %6, %7, %8, %9, %10, %11, %12, %13, %14, %15, %16, %17, %18, %19, %20, %21, %22, %23}, {%48, %49, %50, %51}, %88, 1, 1, 1, 0;\n"
      "wgmma.mma_async.sync.aligned.m64n48k16.f32.bf16.bf16 {%0, %1, %2, %3, %4, %5, %6, %7, %8, %9, %10, %11, %12, %13, %14, %15, %16, %17, %18, %19, %20, %21, %22, %23}, {%52, %53, %54, %55}, dx1, 1, 1, 1, 0;\n"
      "wgmma.mma_async.sync.aligned.m64n48k16.f32.bf16.bf16 {%0, %1, %2, %3, %4, %5, %6, %7, %8, %9, %10, %11, %12, %13, %14, %15, %16, %17, %18, %19, %20, %21, %22, %23}, {%56, %57, %58, %59}, dx2, 1, 1, 1, 0;\n"
      "wgmma.mma_async.sync.aligned.m64n48k16.f32.bf16.bf16 {%0, %1, %2, %3, %4, %5, %6, %7, %8, %9, %10, %11, %12, %13, %14, %15, %16, %17, %18, %19, %20, %21, %22, %23}, {%60, %61, %62, %63}, dx3, 1, 1, 1, 0;\n"
      "wgmma.commit_group.sync.aligned;\n"
      "wgmma.mma_async.sync.aligned.m64n48k16.f32.bf16.bf16 {%24, %25, %26, %27, %28, %29, %30, %31, %32, %33, %34, %35, %36, %37, %38, %39, %40, %41, %42, %43, %44, %45, %46, %47}, {%68, %69, %70, %71}, %88, 0, 1, 1, 0;\n"
      "wgmma.mma_async.sync.aligned.m64n48k16.f32.bf16.bf16 {%24, %25, %26, %27, %28, %29, %30, %31, %32, %33, %34, %35, %36, %37, %38, %39, %40, %41, %42, %43, %44, %45, %46, %47}, {%72, %73, %74, %75}, dx1, 1, 1, 1, 0;\n"
      "wgmma.mma_async.sync.aligned.m64n48k16.f32.bf16.bf16 {%24, %25, %26, %27, %28, %29, %30, %31, %32, %33, %34, %35, %36, %37, %38, %39, %40, %41, %42, %43, %44, %45, %46, %47}, {%76, %77, %78, %79}, dx2, 1, 1, 1, 0;\n"
      "wgmma.mma_async.sync.aligned.m64n48k16.f32.bf16.bf16 {%24, %25, %26, %27, %28, %29, %30, %31, %32, %33, %34, %35, %36, %37, %38, %39, %40, %41, %42, %43, %44, %45, %46, %47}, {%80, %81, %82, %83}, dx3, 1, 1, 1, 0;\n"
      "wgmma.commit_group.sync.aligned;\n}\n"
      : "=f"(g[0]), "=f"(g[1]), "=f"(g[2]), "=f"(g[3]), "=f"(g[4]), "=f"(g[5]), "=f"(g[6]), "=f"(g[7]), "=f"(g[8]), "=f"(g[9]), "=f"(g[10]), "=f"(g[11]), "=f"(g[12]), "=f"(g[13]), "=f"(g[14]), "=f"(g[15]), "=f"(g[16]), "=f"(g[17]), "=f"(g[18]), "=f"(g[19]), "=f"(g[20]), "=f"(g[21]), "=f"(g[22]), "=f"(g[23]),
        "=f"(h[0]), "=f"(h[1]), "=f"(h[2]), "=f"(h[3]), "=f"(h[4]), "=f"(h[5]), "=f"(h[6]), "=f"(h[7]), "=f"(h[8]), "=f"(h[9]), "=f"(h[10]), "=f"(h[11]), "=f"(h[12]), "=f"(h[13]), "=f"(h[14]), "=f"(h[15]), "=f"(h[16]), "=f"(h[17]), "=f"(h[18]), "=f"(h[19]), "=f"(h[20]), "=f"(h[21]), "=f"(h[22]), "=f"(h[23])
      : "r"(w[0]), "r"(w[1]), "r"(w[2]), "r"(w[3]), "r"(w[4]), "r"(w[5]), "r"(w[6]), "r"(w[7]), "r"(w[8]), "r"(w[9]), "r"(w[10]), "r"(w[11]), "r"(w[12]), "r"(w[13]), "r"(w[14]), "r"(w[15]), "r"(w[16]), "r"(w[17]), "r"(w[18]), "r"(w[19]), "r"(w[20]), "r"(w[21]), "r"(w[22]), "r"(w[23]), "r"(w[24]), "r"(w[25]), "r"(w[26]), "r"(w[27]), "r"(w[28]), "r"(w[29]), "r"(w[30]), "r"(w[31]), "r"(w[32]), "r"(w[33]), "r"(w[34]), "r"(w[35]), "r"(w[36]), "r"(w[37]), "r"(w[38]), "r"(w[39]), "l"(dx), "l"(de), "l"(dh)
      : "memory");
  }
  static __device__ __forceinline__ void wait_g(float* g) {
    asm volatile("wgmma.wait_group.sync.aligned 1;\n"
      : "+f"(g[0]), "+f"(g[1]), "+f"(g[2]), "+f"(g[3]), "+f"(g[4]), "+f"(g[5]), "+f"(g[6]), "+f"(g[7]), "+f"(g[8]), "+f"(g[9]), "+f"(g[10]), "+f"(g[11]), "+f"(g[12]), "+f"(g[13]), "+f"(g[14]), "+f"(g[15]), "+f"(g[16]), "+f"(g[17]), "+f"(g[18]), "+f"(g[19]), "+f"(g[20]), "+f"(g[21]), "+f"(g[22]), "+f"(g[23])
      :: "memory");
  }
  static __device__ __forceinline__ void wait_h(float* h) {
    asm volatile("wgmma.wait_group.sync.aligned 0;\n"
      : "+f"(h[0]), "+f"(h[1]), "+f"(h[2]), "+f"(h[3]), "+f"(h[4]), "+f"(h[5]), "+f"(h[6]), "+f"(h[7]), "+f"(h[8]), "+f"(h[9]), "+f"(h[10]), "+f"(h[11]), "+f"(h[12]), "+f"(h[13]), "+f"(h[14]), "+f"(h[15]), "+f"(h[16]), "+f"(h[17]), "+f"(h[18]), "+f"(h[19]), "+f"(h[20]), "+f"(h[21]), "+f"(h[22]), "+f"(h[23])
      :: "memory");
  }
};
template<> struct TileMMA<7> {
  static __device__ __forceinline__ void issue(float* g, float* h, const uint32_t* w, uint64_t dx, uint64_t de, uint64_t dh, uint64_t dc) {
    asm volatile(
      "{\n.reg .b64 dx1, dx2, dx3;\n"
      "add.s64 dx1, %96, 2;\nadd.s64 dx2, %96, 4;\nadd.s64 dx3, %96, 6;\n"
      "wgmma.fence.sync.aligned;\n"
      "wgmma.mma_async.sync.aligned.m64n56k16.f32.bf16.bf16 {%0, %1, %2, %3, %4, %5, %6, %7, %8, %9, %10, %11, %12, %13, %14, %15, %16, %17, %18, %19, %20, %21, %22, %23, %24, %25, %26, %27}, {%92, %93, %94, %95}, %98, 0, 1, 1, 0;\n"
      "wgmma.mma_async.sync.aligned.m64n56k16.f32.bf16.bf16 {%0, %1, %2, %3, %4, %5, %6, %7, %8, %9, %10, %11, %12, %13, %14, %15, %16, %17, %18, %19, %20, %21, %22, %23, %24, %25, %26, %27}, {%72, %73, %74, %75}, %97, 1, 1, 1, 0;\n"
      "wgmma.mma_async.sync.aligned.m64n56k16.f32.bf16.bf16 {%0, %1, %2, %3, %4, %5, %6, %7, %8, %9, %10, %11, %12, %13, %14, %15, %16, %17, %18, %19, %20, %21, %22, %23, %24, %25, %26, %27}, {%56, %57, %58, %59}, %96, 1, 1, 1, 0;\n"
      "wgmma.mma_async.sync.aligned.m64n56k16.f32.bf16.bf16 {%0, %1, %2, %3, %4, %5, %6, %7, %8, %9, %10, %11, %12, %13, %14, %15, %16, %17, %18, %19, %20, %21, %22, %23, %24, %25, %26, %27}, {%60, %61, %62, %63}, dx1, 1, 1, 1, 0;\n"
      "wgmma.mma_async.sync.aligned.m64n56k16.f32.bf16.bf16 {%0, %1, %2, %3, %4, %5, %6, %7, %8, %9, %10, %11, %12, %13, %14, %15, %16, %17, %18, %19, %20, %21, %22, %23, %24, %25, %26, %27}, {%64, %65, %66, %67}, dx2, 1, 1, 1, 0;\n"
      "wgmma.mma_async.sync.aligned.m64n56k16.f32.bf16.bf16 {%0, %1, %2, %3, %4, %5, %6, %7, %8, %9, %10, %11, %12, %13, %14, %15, %16, %17, %18, %19, %20, %21, %22, %23, %24, %25, %26, %27}, {%68, %69, %70, %71}, dx3, 1, 1, 1, 0;\n"
      "wgmma.commit_group.sync.aligned;\n"
      "wgmma.mma_async.sync.aligned.m64n56k16.f32.bf16.bf16 {%28, %29, %30, %31, %32, %33, %34, %35, %36, %37, %38, %39, %40, %41, %42, %43, %44, %45, %46, %47, %48, %49, %50, %51, %52, %53, %54, %55}, {%76, %77, %78, %79}, %96, 0, 1, 1, 0;\n"
      "wgmma.mma_async.sync.aligned.m64n56k16.f32.bf16.bf16 {%28, %29, %30, %31, %32, %33, %34, %35, %36, %37, %38, %39, %40, %41, %42, %43, %44, %45, %46, %47, %48, %49, %50, %51, %52, %53, %54, %55}, {%80, %81, %82, %83}, dx1, 1, 1, 1, 0;\n"
      "wgmma.mma_async.sync.aligned.m64n56k16.f32.bf16.bf16 {%28, %29, %30, %31, %32, %33, %34, %35, %36, %37, %38, %39, %40, %41, %42, %43, %44, %45, %46, %47, %48, %49, %50, %51, %52, %53, %54, %55}, {%84, %85, %86, %87}, dx2, 1, 1, 1, 0;\n"
      "wgmma.mma_async.sync.aligned.m64n56k16.f32.bf16.bf16 {%28, %29, %30, %31, %32, %33, %34, %35, %36, %37, %38, %39, %40, %41, %42, %43, %44, %45, %46, %47, %48, %49, %50, %51, %52, %53, %54, %55}, {%88, %89, %90, %91}, dx3, 1, 1, 1, 0;\n"
      "wgmma.commit_group.sync.aligned;\n}\n"
      : "=f"(g[0]), "=f"(g[1]), "=f"(g[2]), "=f"(g[3]), "=f"(g[4]), "=f"(g[5]), "=f"(g[6]), "=f"(g[7]), "=f"(g[8]), "=f"(g[9]), "=f"(g[10]), "=f"(g[11]), "=f"(g[12]), "=f"(g[13]), "=f"(g[14]), "=f"(g[15]), "=f"(g[16]), "=f"(g[17]), "=f"(g[18]), "=f"(g[19]), "=f"(g[20]), "=f"(g[21]), "=f"(g[22]), "=f"(g[23]), "=f"(g[24]), "=f"(g[25]), "=f"(g[26]), "=f"(g[27]),
        "=f"(h[0]), "=f"(h[1]), "=f"(h[2]), "=f"(h[3]), "=f"(h[4]), "=f"(h[5]), "=f"(h[6]), "=f"(h[7]), "=f"(h[8]), "=f"(h[9]), "=f"(h[10]), "=f"(h[11]), "=f"(h[12]), "=f"(h[13]), "=f"(h[14]), "=f"(h[15]), "=f"(h[16]), "=f"(h[17]), "=f"(h[18]), "=f"(h[19]), "=f"(h[20]), "=f"(h[21]), "=f"(h[22]), "=f"(h[23]), "=f"(h[24]), "=f"(h[25]), "=f"(h[26]), "=f"(h[27])
      : "r"(w[0]), "r"(w[1]), "r"(w[2]), "r"(w[3]), "r"(w[4]), "r"(w[5]), "r"(w[6]), "r"(w[7]), "r"(w[8]), "r"(w[9]), "r"(w[10]), "r"(w[11]), "r"(w[12]), "r"(w[13]), "r"(w[14]), "r"(w[15]), "r"(w[16]), "r"(w[17]), "r"(w[18]), "r"(w[19]), "r"(w[20]), "r"(w[21]), "r"(w[22]), "r"(w[23]), "r"(w[24]), "r"(w[25]), "r"(w[26]), "r"(w[27]), "r"(w[28]), "r"(w[29]), "r"(w[30]), "r"(w[31]), "r"(w[32]), "r"(w[33]), "r"(w[34]), "r"(w[35]), "r"(w[36]), "r"(w[37]), "r"(w[38]), "r"(w[39]), "l"(dx), "l"(de), "l"(dh)
      : "memory");
  }
  static __device__ __forceinline__ void wait_g(float* g) {
    asm volatile("wgmma.wait_group.sync.aligned 1;\n"
      : "+f"(g[0]), "+f"(g[1]), "+f"(g[2]), "+f"(g[3]), "+f"(g[4]), "+f"(g[5]), "+f"(g[6]), "+f"(g[7]), "+f"(g[8]), "+f"(g[9]), "+f"(g[10]), "+f"(g[11]), "+f"(g[12]), "+f"(g[13]), "+f"(g[14]), "+f"(g[15]), "+f"(g[16]), "+f"(g[17]), "+f"(g[18]), "+f"(g[19]), "+f"(g[20]), "+f"(g[21]), "+f"(g[22]), "+f"(g[23]), "+f"(g[24]), "+f"(g[25]), "+f"(g[26]), "+f"(g[27])
      :: "memory");
  }
  static __device__ __forceinline__ void wait_h(float* h) {
    asm volatile("wgmma.wait_group.sync.aligned 0;\n"
      : "+f"(h[0]), "+f"(h[1]), "+f"(h[2]), "+f"(h[3]), "+f"(h[4]), "+f"(h[5]), "+f"(h[6]), "+f"(h[7]), "+f"(h[8]), "+f"(h[9]), "+f"(h[10]), "+f"(h[11]), "+f"(h[12]), "+f"(h[13]), "+f"(h[14]), "+f"(h[15]), "+f"(h[16]), "+f"(h[17]), "+f"(h[18]), "+f"(h[19]), "+f"(h[20]), "+f"(h[21]), "+f"(h[22]), "+f"(h[23]), "+f"(h[24]), "+f"(h[25]), "+f"(h[26]), "+f"(h[27])
      :: "memory");
  }
};
template<> struct TileMMA<8> {
  static __device__ __forceinline__ void issue(float* g, float* h, const uint32_t* w, uint64_t dx, uint64_t de, uint64_t dh, uint64_t dc) {
    asm volatile(
      "{\n.reg .b64 dx1, dx2, dx3;\n"
      "add.s64 dx1, %104, 2;\nadd.s64 dx2, %104, 4;\nadd.s64 dx3, %104, 6;\n"
      "wgmma.fence.sync.aligned;\n"
      "wgmma.mma_async.sync.aligned.m64n64k16.f32.bf16.bf16 {%0, %1, %2, %3, %4, %5, %6, %7, %8, %9, %10, %11, %12, %13, %14, %15, %16, %17, %18, %19, %20, %21, %22, %23, %24, %25, %26, %27, %28, %29, %30, %31}, {%100, %101, %102, %103}, %106, 0, 1, 1, 0;\n"
      "wgmma.mma_async.sync.aligned.m64n64k16.f32.bf16.bf16 {%0, %1, %2, %3, %4, %5, %6, %7, %8, %9, %10, %11, %12, %13, %14, %15, %16, %17, %18, %19, %20, %21, %22, %23, %24, %25, %26, %27, %28, %29, %30, %31}, {%80, %81, %82, %83}, %105, 1, 1, 1, 0;\n"
      "wgmma.mma_async.sync.aligned.m64n64k16.f32.bf16.bf16 {%0, %1, %2, %3, %4, %5, %6, %7, %8, %9, %10, %11, %12, %13, %14, %15, %16, %17, %18, %19, %20, %21, %22, %23, %24, %25, %26, %27, %28, %29, %30, %31}, {%64, %65, %66, %67}, %104, 1, 1, 1, 0;\n"
      "wgmma.mma_async.sync.aligned.m64n64k16.f32.bf16.bf16 {%0, %1, %2, %3, %4, %5, %6, %7, %8, %9, %10, %11, %12, %13, %14, %15, %16, %17, %18, %19, %20, %21, %22, %23, %24, %25, %26, %27, %28, %29, %30, %31}, {%68, %69, %70, %71}, dx1, 1, 1, 1, 0;\n"
      "wgmma.mma_async.sync.aligned.m64n64k16.f32.bf16.bf16 {%0, %1, %2, %3, %4, %5, %6, %7, %8, %9, %10, %11, %12, %13, %14, %15, %16, %17, %18, %19, %20, %21, %22, %23, %24, %25, %26, %27, %28, %29, %30, %31}, {%72, %73, %74, %75}, dx2, 1, 1, 1, 0;\n"
      "wgmma.mma_async.sync.aligned.m64n64k16.f32.bf16.bf16 {%0, %1, %2, %3, %4, %5, %6, %7, %8, %9, %10, %11, %12, %13, %14, %15, %16, %17, %18, %19, %20, %21, %22, %23, %24, %25, %26, %27, %28, %29, %30, %31}, {%76, %77, %78, %79}, dx3, 1, 1, 1, 0;\n"
      "wgmma.commit_group.sync.aligned;\n"
      "wgmma.mma_async.sync.aligned.m64n64k16.f32.bf16.bf16 {%32, %33, %34, %35, %36, %37, %38, %39, %40, %41, %42, %43, %44, %45, %46, %47, %48, %49, %50, %51, %52, %53, %54, %55, %56, %57, %58, %59, %60, %61, %62, %63}, {%84, %85, %86, %87}, %104, 0, 1, 1, 0;\n"
      "wgmma.mma_async.sync.aligned.m64n64k16.f32.bf16.bf16 {%32, %33, %34, %35, %36, %37, %38, %39, %40, %41, %42, %43, %44, %45, %46, %47, %48, %49, %50, %51, %52, %53, %54, %55, %56, %57, %58, %59, %60, %61, %62, %63}, {%88, %89, %90, %91}, dx1, 1, 1, 1, 0;\n"
      "wgmma.mma_async.sync.aligned.m64n64k16.f32.bf16.bf16 {%32, %33, %34, %35, %36, %37, %38, %39, %40, %41, %42, %43, %44, %45, %46, %47, %48, %49, %50, %51, %52, %53, %54, %55, %56, %57, %58, %59, %60, %61, %62, %63}, {%92, %93, %94, %95}, dx2, 1, 1, 1, 0;\n"
      "wgmma.mma_async.sync.aligned.m64n64k16.f32.bf16.bf16 {%32, %33, %34, %35, %36, %37, %38, %39, %40, %41, %42, %43, %44, %45, %46, %47, %48, %49, %50, %51, %52, %53, %54, %55, %56, %57, %58, %59, %60, %61, %62, %63}, {%96, %97, %98, %99}, dx3, 1, 1, 1, 0;\n"
      "wgmma.commit_group.sync.aligned;\n}\n"
      : "=f"(g[0]), "=f"(g[1]), "=f"(g[2]), "=f"(g[3]), "=f"(g[4]), "=f"(g[5]), "=f"(g[6]), "=f"(g[7]), "=f"(g[8]), "=f"(g[9]), "=f"(g[10]), "=f"(g[11]), "=f"(g[12]), "=f"(g[13]), "=f"(g[14]), "=f"(g[15]), "=f"(g[16]), "=f"(g[17]), "=f"(g[18]), "=f"(g[19]), "=f"(g[20]), "=f"(g[21]), "=f"(g[22]), "=f"(g[23]), "=f"(g[24]), "=f"(g[25]), "=f"(g[26]), "=f"(g[27]), "=f"(g[28]), "=f"(g[29]), "=f"(g[30]), "=f"(g[31]),
        "=f"(h[0]), "=f"(h[1]), "=f"(h[2]), "=f"(h[3]), "=f"(h[4]), "=f"(h[5]), "=f"(h[6]), "=f"(h[7]), "=f"(h[8]), "=f"(h[9]), "=f"(h[10]), "=f"(h[11]), "=f"(h[12]), "=f"(h[13]), "=f"(h[14]), "=f"(h[15]), "=f"(h[16]), "=f"(h[17]), "=f"(h[18]), "=f"(h[19]), "=f"(h[20]), "=f"(h[21]), "=f"(h[22]), "=f"(h[23]), "=f"(h[24]), "=f"(h[25]), "=f"(h[26]), "=f"(h[27]), "=f"(h[28]), "=f"(h[29]), "=f"(h[30]), "=f"(h[31])
      : "r"(w[0]), "r"(w[1]), "r"(w[2]), "r"(w[3]), "r"(w[4]), "r"(w[5]), "r"(w[6]), "r"(w[7]), "r"(w[8]), "r"(w[9]), "r"(w[10]), "r"(w[11]), "r"(w[12]), "r"(w[13]), "r"(w[14]), "r"(w[15]), "r"(w[16]), "r"(w[17]), "r"(w[18]), "r"(w[19]), "r"(w[20]), "r"(w[21]), "r"(w[22]), "r"(w[23]), "r"(w[24]), "r"(w[25]), "r"(w[26]), "r"(w[27]), "r"(w[28]), "r"(w[29]), "r"(w[30]), "r"(w[31]), "r"(w[32]), "r"(w[33]), "r"(w[34]), "r"(w[35]), "r"(w[36]), "r"(w[37]), "r"(w[38]), "r"(w[39]), "l"(dx), "l"(de), "l"(dh)
      : "memory");
  }
  static __device__ __forceinline__ void wait_g(float* g) {
    asm volatile("wgmma.wait_group.sync.aligned 1;\n"
      : "+f"(g[0]), "+f"(g[1]), "+f"(g[2]), "+f"(g[3]), "+f"(g[4]), "+f"(g[5]), "+f"(g[6]), "+f"(g[7]), "+f"(g[8]), "+f"(g[9]), "+f"(g[10]), "+f"(g[11]), "+f"(g[12]), "+f"(g[13]), "+f"(g[14]), "+f"(g[15]), "+f"(g[16]), "+f"(g[17]), "+f"(g[18]), "+f"(g[19]), "+f"(g[20]), "+f"(g[21]), "+f"(g[22]), "+f"(g[23]), "+f"(g[24]), "+f"(g[25]), "+f"(g[26]), "+f"(g[27]), "+f"(g[28]), "+f"(g[29]), "+f"(g[30]), "+f"(g[31])
      :: "memory");
  }
  static __device__ __forceinline__ void wait_h(float* h) {
    asm volatile("wgmma.wait_group.sync.aligned 0;\n"
      : "+f"(h[0]), "+f"(h[1]), "+f"(h[2]), "+f"(h[3]), "+f"(h[4]), "+f"(h[5]), "+f"(h[6]), "+f"(h[7]), "+f"(h[8]), "+f"(h[9]), "+f"(h[10]), "+f"(h[11]), "+f"(h[12]), "+f"(h[13]), "+f"(h[14]), "+f"(h[15]), "+f"(h[16]), "+f"(h[17]), "+f"(h[18]), "+f"(h[19]), "+f"(h[20]), "+f"(h[21]), "+f"(h[22]), "+f"(h[23]), "+f"(h[24]), "+f"(h[25]), "+f"(h[26]), "+f"(h[27]), "+f"(h[28]), "+f"(h[29]), "+f"(h[30]), "+f"(h[31])
      :: "memory");
  }
};
template<> struct TileMMA<9> {
  static __device__ __forceinline__ void issue(float* g, float* h, const uint32_t* w, uint64_t dx, uint64_t de, uint64_t dh, uint64_t dc) {
    asm volatile(
      "{\n.reg .b64 dx1, dx2, dx3;\n"
      "add.s64 dx1, %112, 2;\nadd.s64 dx2, %112, 4;\nadd.s64 dx3, %112, 6;\n"
      "wgmma.fence.sync.aligned;\n"
      "wgmma.mma_async.sync.aligned.m64n72k16.f32.bf16.bf16 {%0, %1, %2, %3, %4, %5, %6, %7, %8, %9, %10, %11, %12, %13, %14, %15, %16, %17, %18, %19, %20, %21, %22, %23, %24, %25, %26, %27, %28, %29, %30, %31, %32, %33, %34, %35}, {%108, %109, %110, %111}, %114, 0, 1, 1, 0;\n"
      "wgmma.mma_async.sync.aligned.m64n72k16.f32.bf16.bf16 {%0, %1, %2, %3, %4, %5, %6, %7, %8, %9, %10, %11, %12, %13, %14, %15, %16, %17, %18, %19, %20, %21, %22, %23, %24, %25, %26, %27, %28, %29, %30, %31, %32, %33, %34, %35}, {%88, %89, %90, %91}, %113, 1, 1, 1, 0;\n"
      "wgmma.mma_async.sync.aligned.m64n72k16.f32.bf16.bf16 {%0, %1, %2, %3, %4, %5, %6, %7, %8, %9, %10, %11, %12, %13, %14, %15, %16, %17, %18, %19, %20, %21, %22, %23, %24, %25, %26, %27, %28, %29, %30, %31, %32, %33, %34, %35}, {%72, %73, %74, %75}, %112, 1, 1, 1, 0;\n"
      "wgmma.mma_async.sync.aligned.m64n72k16.f32.bf16.bf16 {%0, %1, %2, %3, %4, %5, %6, %7, %8, %9, %10, %11, %12, %13, %14, %15, %16, %17, %18, %19, %20, %21, %22, %23, %24, %25, %26, %27, %28, %29, %30, %31, %32, %33, %34, %35}, {%76, %77, %78, %79}, dx1, 1, 1, 1, 0;\n"
      "wgmma.mma_async.sync.aligned.m64n72k16.f32.bf16.bf16 {%0, %1, %2, %3, %4, %5, %6, %7, %8, %9, %10, %11, %12, %13, %14, %15, %16, %17, %18, %19, %20, %21, %22, %23, %24, %25, %26, %27, %28, %29, %30, %31, %32, %33, %34, %35}, {%80, %81, %82, %83}, dx2, 1, 1, 1, 0;\n"
      "wgmma.mma_async.sync.aligned.m64n72k16.f32.bf16.bf16 {%0, %1, %2, %3, %4, %5, %6, %7, %8, %9, %10, %11, %12, %13, %14, %15, %16, %17, %18, %19, %20, %21, %22, %23, %24, %25, %26, %27, %28, %29, %30, %31, %32, %33, %34, %35}, {%84, %85, %86, %87}, dx3, 1, 1, 1, 0;\n"
      "wgmma.commit_group.sync.aligned;\n"
      "wgmma.mma_async.sync.aligned.m64n72k16.f32.bf16.bf16 {%36, %37, %38, %39, %40, %41, %42, %43, %44, %45, %46, %47, %48, %49, %50, %51, %52, %53, %54, %55, %56, %57, %58, %59, %60, %61, %62, %63, %64, %65, %66, %67, %68, %69, %70, %71}, {%92, %93, %94, %95}, %112, 0, 1, 1, 0;\n"
      "wgmma.mma_async.sync.aligned.m64n72k16.f32.bf16.bf16 {%36, %37, %38, %39, %40, %41, %42, %43, %44, %45, %46, %47, %48, %49, %50, %51, %52, %53, %54, %55, %56, %57, %58, %59, %60, %61, %62, %63, %64, %65, %66, %67, %68, %69, %70, %71}, {%96, %97, %98, %99}, dx1, 1, 1, 1, 0;\n"
      "wgmma.mma_async.sync.aligned.m64n72k16.f32.bf16.bf16 {%36, %37, %38, %39, %40, %41, %42, %43, %44, %45, %46, %47, %48, %49, %50, %51, %52, %53, %54, %55, %56, %57, %58, %59, %60, %61, %62, %63, %64, %65, %66, %67, %68, %69, %70, %71}, {%100, %101, %102, %103}, dx2, 1, 1, 1, 0;\n"
      "wgmma.mma_async.sync.aligned.m64n72k16.f32.bf16.bf16 {%36, %37, %38, %39, %40, %41, %42, %43, %44, %45, %46, %47, %48, %49, %50, %51, %52, %53, %54, %55, %56, %57, %58, %59, %60, %61, %62, %63, %64, %65, %66, %67, %68, %69, %70, %71}, {%104, %105, %106, %107}, dx3, 1, 1, 1, 0;\n"
      "wgmma.commit_group.sync.aligned;\n}\n"
      : "=f"(g[0]), "=f"(g[1]), "=f"(g[2]), "=f"(g[3]), "=f"(g[4]), "=f"(g[5]), "=f"(g[6]), "=f"(g[7]), "=f"(g[8]), "=f"(g[9]), "=f"(g[10]), "=f"(g[11]), "=f"(g[12]), "=f"(g[13]), "=f"(g[14]), "=f"(g[15]), "=f"(g[16]), "=f"(g[17]), "=f"(g[18]), "=f"(g[19]), "=f"(g[20]), "=f"(g[21]), "=f"(g[22]), "=f"(g[23]), "=f"(g[24]), "=f"(g[25]), "=f"(g[26]), "=f"(g[27]), "=f"(g[28]), "=f"(g[29]), "=f"(g[30]), "=f"(g[31]), "=f"(g[32]), "=f"(g[33]), "=f"(g[34]), "=f"(g[35]),
        "=f"(h[0]), "=f"(h[1]), "=f"(h[2]), "=f"(h[3]), "=f"(h[4]), "=f"(h[5]), "=f"(h[6]), "=f"(h[7]), "=f"(h[8]), "=f"(h[9]), "=f"(h[10]), "=f"(h[11]), "=f"(h[12]), "=f"(h[13]), "=f"(h[14]), "=f"(h[15]), "=f"(h[16]), "=f"(h[17]), "=f"(h[18]), "=f"(h[19]), "=f"(h[20]), "=f"(h[21]), "=f"(h[22]), "=f"(h[23]), "=f"(h[24]), "=f"(h[25]), "=f"(h[26]), "=f"(h[27]), "=f"(h[28]), "=f"(h[29]), "=f"(h[30]), "=f"(h[31]), "=f"(h[32]), "=f"(h[33]), "=f"(h[34]), "=f"(h[35])
      : "r"(w[0]), "r"(w[1]), "r"(w[2]), "r"(w[3]), "r"(w[4]), "r"(w[5]), "r"(w[6]), "r"(w[7]), "r"(w[8]), "r"(w[9]), "r"(w[10]), "r"(w[11]), "r"(w[12]), "r"(w[13]), "r"(w[14]), "r"(w[15]), "r"(w[16]), "r"(w[17]), "r"(w[18]), "r"(w[19]), "r"(w[20]), "r"(w[21]), "r"(w[22]), "r"(w[23]), "r"(w[24]), "r"(w[25]), "r"(w[26]), "r"(w[27]), "r"(w[28]), "r"(w[29]), "r"(w[30]), "r"(w[31]), "r"(w[32]), "r"(w[33]), "r"(w[34]), "r"(w[35]), "r"(w[36]), "r"(w[37]), "r"(w[38]), "r"(w[39]), "l"(dx), "l"(de), "l"(dh)
      : "memory");
  }
  static __device__ __forceinline__ void wait_g(float* g) {
    asm volatile("wgmma.wait_group.sync.aligned 1;\n"
      : "+f"(g[0]), "+f"(g[1]), "+f"(g[2]), "+f"(g[3]), "+f"(g[4]), "+f"(g[5]), "+f"(g[6]), "+f"(g[7]), "+f"(g[8]), "+f"(g[9]), "+f"(g[10]), "+f"(g[11]), "+f"(g[12]), "+f"(g[13]), "+f"(g[14]), "+f"(g[15]), "+f"(g[16]), "+f"(g[17]), "+f"(g[18]), "+f"(g[19]), "+f"(g[20]), "+f"(g[21]), "+f"(g[22]), "+f"(g[23]), "+f"(g[24]), "+f"(g[25]), "+f"(g[26]), "+f"(g[27]), "+f"(g[28]), "+f"(g[29]), "+f"(g[30]), "+f"(g[31]), "+f"(g[32]), "+f"(g[33]), "+f"(g[34]), "+f"(g[35])
      :: "memory");
  }
  static __device__ __forceinline__ void wait_h(float* h) {
    asm volatile("wgmma.wait_group.sync.aligned 0;\n"
      : "+f"(h[0]), "+f"(h[1]), "+f"(h[2]), "+f"(h[3]), "+f"(h[4]), "+f"(h[5]), "+f"(h[6]), "+f"(h[7]), "+f"(h[8]), "+f"(h[9]), "+f"(h[10]), "+f"(h[11]), "+f"(h[12]), "+f"(h[13]), "+f"(h[14]), "+f"(h[15]), "+f"(h[16]), "+f"(h[17]), "+f"(h[18]), "+f"(h[19]), "+f"(h[20]), "+f"(h[21]), "+f"(h[22]), "+f"(h[23]), "+f"(h[24]), "+f"(h[25]), "+f"(h[26]), "+f"(h[27]), "+f"(h[28]), "+f"(h[29]), "+f"(h[30]), "+f"(h[31]), "+f"(h[32]), "+f"(h[33]), "+f"(h[34]), "+f"(h[35])
      :: "memory");
  }
};
template<> struct TileMMA<10> {
  static __device__ __forceinline__ void issue(float* g, float* h, const uint32_t* w, uint64_t dx, uint64_t de, uint64_t dh, uint64_t dc) {
    asm volatile(
      "{\n.reg .b64 dx1, dx2, dx3;\n"
      "add.s64 dx1, %120, 2;\nadd.s64 dx2, %120, 4;\nadd.s64 dx3, %120, 6;\n"
      "wgmma.fence.sync.aligned;\n"
      "wgmma.mma_async.sync.aligned.m64n80k16.f32.bf16.bf16 {%0, %1, %2, %3, %4, %5, %6, %7, %8, %9, %10, %11, %12, %13, %14, %15, %16, %17, %18, %19, %20, %21, %22, %23, %24, %25, %26, %27, %28, %29, %30, %31, %32, %33, %34, %35, %36, %37, %38, %39}, {%116, %117, %118, %119}, %122, 0, 1, 1, 0;\n"
      "wgmma.mma_async.sync.aligned.m64n80k16.f32.bf16.bf16 {%0, %1, %2, %3, %4, %5, %6, %7, %8, %9, %10, %11, %12, %13, %14, %15, %16, %17, %18, %19, %20, %21, %22, %23, %24, %25, %26, %27, %28, %29, %30, %31, %32, %33, %34, %35, %36, %37, %38, %39}, {%96, %97, %98, %99}, %121, 1, 1, 1, 0;\n"
      "wgmma.mma_async.sync.aligned.m64n80k16.f32.bf16.bf16 {%0, %1, %2, %3, %4, %5, %6, %7, %8, %9, %10, %11, %12, %13, %14, %15, %16, %17, %18, %19, %20, %21, %22, %23, %24, %25, %26, %27, %28, %29, %30, %31, %32, %33, %34, %35, %36, %37, %38, %39}, {%80, %81, %82, %83}, %120, 1, 1, 1, 0;\n"
      "wgmma.mma_async.sync.aligned.m64n80k16.f32.bf16.bf16 {%0, %1, %2, %3, %4, %5, %6, %7, %8, %9, %10, %11, %12, %13, %14, %15, %16, %17, %18, %19, %20, %21, %22, %23, %24, %25, %26, %27, %28, %29, %30, %31, %32, %33, %34, %35, %36, %37, %38, %39}, {%84, %85, %86, %87}, dx1, 1, 1, 1, 0;\n"
      "wgmma.mma_async.sync.aligned.m64n80k16.f32.bf16.bf16 {%0, %1, %2, %3, %4, %5, %6, %7, %8, %9, %10, %11, %12, %13, %14, %15, %16, %17, %18, %19, %20, %21, %22, %23, %24, %25, %26, %27, %28, %29, %30, %31, %32, %33, %34, %35, %36, %37, %38, %39}, {%88, %89, %90, %91}, dx2, 1, 1, 1, 0;\n"
      "wgmma.mma_async.sync.aligned.m64n80k16.f32.bf16.bf16 {%0, %1, %2, %3, %4, %5, %6, %7, %8, %9, %10, %11, %12, %13, %14, %15, %16, %17, %18, %19, %20, %21, %22, %23, %24, %25, %26, %27, %28, %29, %30, %31, %32, %33, %34, %35, %36, %37, %38, %39}, {%92, %93, %94, %95}, dx3, 1, 1, 1, 0;\n"
      "wgmma.commit_group.sync.aligned;\n"
      "wgmma.mma_async.sync.aligned.m64n80k16.f32.bf16.bf16 {%40, %41, %42, %43, %44, %45, %46, %47, %48, %49, %50, %51, %52, %53, %54, %55, %56, %57, %58, %59, %60, %61, %62, %63, %64, %65, %66, %67, %68, %69, %70, %71, %72, %73, %74, %75, %76, %77, %78, %79}, {%100, %101, %102, %103}, %120, 0, 1, 1, 0;\n"
      "wgmma.mma_async.sync.aligned.m64n80k16.f32.bf16.bf16 {%40, %41, %42, %43, %44, %45, %46, %47, %48, %49, %50, %51, %52, %53, %54, %55, %56, %57, %58, %59, %60, %61, %62, %63, %64, %65, %66, %67, %68, %69, %70, %71, %72, %73, %74, %75, %76, %77, %78, %79}, {%104, %105, %106, %107}, dx1, 1, 1, 1, 0;\n"
      "wgmma.mma_async.sync.aligned.m64n80k16.f32.bf16.bf16 {%40, %41, %42, %43, %44, %45, %46, %47, %48, %49, %50, %51, %52, %53, %54, %55, %56, %57, %58, %59, %60, %61, %62, %63, %64, %65, %66, %67, %68, %69, %70, %71, %72, %73, %74, %75, %76, %77, %78, %79}, {%108, %109, %110, %111}, dx2, 1, 1, 1, 0;\n"
      "wgmma.mma_async.sync.aligned.m64n80k16.f32.bf16.bf16 {%40, %41, %42, %43, %44, %45, %46, %47, %48, %49, %50, %51, %52, %53, %54, %55, %56, %57, %58, %59, %60, %61, %62, %63, %64, %65, %66, %67, %68, %69, %70, %71, %72, %73, %74, %75, %76, %77, %78, %79}, {%112, %113, %114, %115}, dx3, 1, 1, 1, 0;\n"
      "wgmma.commit_group.sync.aligned;\n}\n"
      : "=f"(g[0]), "=f"(g[1]), "=f"(g[2]), "=f"(g[3]), "=f"(g[4]), "=f"(g[5]), "=f"(g[6]), "=f"(g[7]), "=f"(g[8]), "=f"(g[9]), "=f"(g[10]), "=f"(g[11]), "=f"(g[12]), "=f"(g[13]), "=f"(g[14]), "=f"(g[15]), "=f"(g[16]), "=f"(g[17]), "=f"(g[18]), "=f"(g[19]), "=f"(g[20]), "=f"(g[21]), "=f"(g[22]), "=f"(g[23]), "=f"(g[24]), "=f"(g[25]), "=f"(g[26]), "=f"(g[27]), "=f"(g[28]), "=f"(g[29]), "=f"(g[30]), "=f"(g[31]), "=f"(g[32]), "=f"(g[33]), "=f"(g[34]), "=f"(g[35]), "=f"(g[36]), "=f"(g[37]), "=f"(g[38]), "=f"(g[39]),
        "=f"(h[0]), "=f"(h[1]), "=f"(h[2]), "=f"(h[3]), "=f"(h[4]), "=f"(h[5]), "=f"(h[6]), "=f"(h[7]), "=f"(h[8]), "=f"(h[9]), "=f"(h[10]), "=f"(h[11]), "=f"(h[12]), "=f"(h[13]), "=f"(h[14]), "=f"(h[15]), "=f"(h[16]), "=f"(h[17]), "=f"(h[18]), "=f"(h[19]), "=f"(h[20]), "=f"(h[21]), "=f"(h[22]), "=f"(h[23]), "=f"(h[24]), "=f"(h[25]), "=f"(h[26]), "=f"(h[27]), "=f"(h[28]), "=f"(h[29]), "=f"(h[30]), "=f"(h[31]), "=f"(h[32]), "=f"(h[33]), "=f"(h[34]), "=f"(h[35]), "=f"(h[36]), "=f"(h[37]), "=f"(h[38]), "=f"(h[39])
      : "r"(w[0]), "r"(w[1]), "r"(w[2]), "r"(w[3]), "r"(w[4]), "r"(w[5]), "r"(w[6]), "r"(w[7]), "r"(w[8]), "r"(w[9]), "r"(w[10]), "r"(w[11]), "r"(w[12]), "r"(w[13]), "r"(w[14]), "r"(w[15]), "r"(w[16]), "r"(w[17]), "r"(w[18]), "r"(w[19]), "r"(w[20]), "r"(w[21]), "r"(w[22]), "r"(w[23]), "r"(w[24]), "r"(w[25]), "r"(w[26]), "r"(w[27]), "r"(w[28]), "r"(w[29]), "r"(w[30]), "r"(w[31]), "r"(w[32]), "r"(w[33]), "r"(w[34]), "r"(w[35]), "r"(w[36]), "r"(w[37]), "r"(w[38]), "r"(w[39]), "l"(dx), "l"(de), "l"(dh)
      : "memory");
  }
  static __device__ __forceinline__ void wait_g(float* g) {
    asm volatile("wgmma.wait_group.sync.aligned 1;\n"
      : "+f"(g[0]), "+f"(g[1]), "+f"(g[2]), "+f"(g[3]), "+f"(g[4]), "+f"(g[5]), "+f"(g[6]), "+f"(g[7]), "+f"(g[8]), "+f"(g[9]), "+f"(g[10]), "+f"(g[11]), "+f"(g[12]), "+f"(g[13]), "+f"(g[14]), "+f"(g[15]), "+f"(g[16]), "+f"(g[17]), "+f"(g[18]), "+f"(g[19]), "+f"(g[20]), "+f"(g[21]), "+f"(g[22]), "+f"(g[23]), "+f"(g[24]), "+f"(g[25]), "+f"(g[26]), "+f"(g[27]), "+f"(g[28]), "+f"(g[29]), "+f"(g[30]), "+f"(g[31]), "+f"(g[32]), "+f"(g[33]), "+f"(g[34]), "+f"(g[35]), "+f"(g[36]), "+f"(g[37]), "+f"(g[38]), "+f"(g[39])
      :: "memory");
  }
  static __device__ __forceinline__ void wait_h(float* h) {
    asm volatile("wgmma.wait_group.sync.aligned 0;\n"
      : "+f"(h[0]), "+f"(h[1]), "+f"(h[2]), "+f"(h[3]), "+f"(h[4]), "+f"(h[5]), "+f"(h[6]), "+f"(h[7]), "+f"(h[8]), "+f"(h[9]), "+f"(h[10]), "+f"(h[11]), "+f"(h[12]), "+f"(h[13]), "+f"(h[14]), "+f"(h[15]), "+f"(h[16]), "+f"(h[17]), "+f"(h[18]), "+f"(h[19]), "+f"(h[20]), "+f"(h[21]), "+f"(h[22]), "+f"(h[23]), "+f"(h[24]), "+f"(h[25]), "+f"(h[26]), "+f"(h[27]), "+f"(h[28]), "+f"(h[29]), "+f"(h[30]), "+f"(h[31]), "+f"(h[32]), "+f"(h[33]), "+f"(h[34]), "+f"(h[35]), "+f"(h[36]), "+f"(h[37]), "+f"(h[38]), "+f"(h[39])
      :: "memory");
  }
};
template<> struct TileMMA<11> {
  static __device__ __forceinline__ void issue(float* g, float* h, const uint32_t* w, uint64_t dx, uint64_t de, uint64_t dh, uint64_t dc) {
    asm volatile(
      "{\n.reg .b64 dx1, dx2, dx3;\n"
      "add.s64 dx1, %124, 2;\nadd.s64 dx2, %124, 4;\nadd.s64 dx3, %124, 6;\n"
      "wgmma.fence.sync.aligned;\n"
      "wgmma.mma_async.sync.aligned.m64n88k16.f32.bf16.bf16 {%0, %1, %2, %3, %4, %5, %6, %7, %8, %9, %10, %11, %12, %13, %14, %15, %16, %17, %18, %19, %20, %21, %22, %23, %24, %25, %26, %27, %28, %29, %30, %31, %32, %33, %34, %35, %36, %37, %38, %39, %40, %41, %42, %43}, {%120, %121, %122, %123}, %126, 0, 1, 1, 0;\n"
      "wgmma.mma_async.sync.aligned.m64n88k16.f32.bf16.bf16 {%0, %1, %2, %3, %4, %5, %6, %7, %8, %9, %10, %11, %12, %13, %14, %15, %16, %17, %18, %19, %20, %21, %22, %23, %24, %25, %26, %27, %28, %29, %30, %31, %32, %33, %34, %35, %36, %37, %38, %39, %40, %41, %42, %43}, %127, %125, 1, 1, 1, 0, 0;\n"
      "wgmma.mma_async.sync.aligned.m64n88k16.f32.bf16.bf16 {%0, %1, %2, %3, %4, %5, %6, %7, %8, %9, %10, %11, %12, %13, %14, %15, %16, %17, %18, %19, %20, %21, %22, %23, %24, %25, %26, %27, %28, %29, %30, %31, %32, %33, %34, %35, %36, %37, %38, %39, %40, %41, %42, %43}, {%88, %89, %90, %91}, %124, 1, 1, 1, 0;\n"
      "wgmma.mma_async.sync.aligned.m64n88k16.f32.bf16.bf16 {%0, %1, %2, %3, %4, %5, %6, %7, %8, %9, %10, %11, %12, %13, %14, %15, %16, %17, %18, %19, %20, %21, %22, %23, %24, %25, %26, %27, %28, %29, %30, %31, %32, %33, %34, %35, %36, %37, %38, %39, %40, %41, %42, %43}, {%92, %93, %94, %95}, dx1, 1, 1, 1, 0;\n"
      "wgmma.mma_async.sync.aligned.m64n88k16.f32.bf16.bf16 {%0, %1, %2, %3, %4, %5, %6, %7, %8, %9, %10, %11, %12, %13, %14, %15, %16, %17, %18, %19, %20, %21, %22, %23, %24, %25, %26, %27, %28, %29, %30, %31, %32, %33, %34, %35, %36, %37, %38, %39, %40, %41, %42, %43}, {%96, %97, %98, %99}, dx2, 1, 1, 1, 0;\n"
      "wgmma.mma_async.sync.aligned.m64n88k16.f32.bf16.bf16 {%0, %1, %2, %3, %4, %5, %6, %7, %8, %9, %10, %11, %12, %13, %14, %15, %16, %17, %18, %19, %20, %21, %22, %23, %24, %25, %26, %27, %28, %29, %30, %31, %32, %33, %34, %35, %36, %37, %38, %39, %40, %41, %42, %43}, {%100, %101, %102, %103}, dx3, 1, 1, 1, 0;\n"
      "wgmma.commit_group.sync.aligned;\n"
      "wgmma.mma_async.sync.aligned.m64n88k16.f32.bf16.bf16 {%44, %45, %46, %47, %48, %49, %50, %51, %52, %53, %54, %55, %56, %57, %58, %59, %60, %61, %62, %63, %64, %65, %66, %67, %68, %69, %70, %71, %72, %73, %74, %75, %76, %77, %78, %79, %80, %81, %82, %83, %84, %85, %86, %87}, {%104, %105, %106, %107}, %124, 0, 1, 1, 0;\n"
      "wgmma.mma_async.sync.aligned.m64n88k16.f32.bf16.bf16 {%44, %45, %46, %47, %48, %49, %50, %51, %52, %53, %54, %55, %56, %57, %58, %59, %60, %61, %62, %63, %64, %65, %66, %67, %68, %69, %70, %71, %72, %73, %74, %75, %76, %77, %78, %79, %80, %81, %82, %83, %84, %85, %86, %87}, {%108, %109, %110, %111}, dx1, 1, 1, 1, 0;\n"
      "wgmma.mma_async.sync.aligned.m64n88k16.f32.bf16.bf16 {%44, %45, %46, %47, %48, %49, %50, %51, %52, %53, %54, %55, %56, %57, %58, %59, %60, %61, %62, %63, %64, %65, %66, %67, %68, %69, %70, %71, %72, %73, %74, %75, %76, %77, %78, %79, %80, %81, %82, %83, %84, %85, %86, %87}, {%112, %113, %114, %115}, dx2, 1, 1, 1, 0;\n"
      "wgmma.mma_async.sync.aligned.m64n88k16.f32.bf16.bf16 {%44, %45, %46, %47, %48, %49, %50, %51, %52, %53, %54, %55, %56, %57, %58, %59, %60, %61, %62, %63, %64, %65, %66, %67, %68, %69, %70, %71, %72, %73, %74, %75, %76, %77, %78, %79, %80, %81, %82, %83, %84, %85, %86, %87}, {%116, %117, %118, %119}, dx3, 1, 1, 1, 0;\n"
      "wgmma.commit_group.sync.aligned;\n}\n"
      : "=f"(g[0]), "=f"(g[1]), "=f"(g[2]), "=f"(g[3]), "=f"(g[4]), "=f"(g[5]), "=f"(g[6]), "=f"(g[7]), "=f"(g[8]), "=f"(g[9]), "=f"(g[10]), "=f"(g[11]), "=f"(g[12]), "=f"(g[13]), "=f"(g[14]), "=f"(g[15]), "=f"(g[16]), "=f"(g[17]), "=f"(g[18]), "=f"(g[19]), "=f"(g[20]), "=f"(g[21]), "=f"(g[22]), "=f"(g[23]), "=f"(g[24]), "=f"(g[25]), "=f"(g[26]), "=f"(g[27]), "=f"(g[28]), "=f"(g[29]), "=f"(g[30]), "=f"(g[31]), "=f"(g[32]), "=f"(g[33]), "=f"(g[34]), "=f"(g[35]), "=f"(g[36]), "=f"(g[37]), "=f"(g[38]), "=f"(g[39]), "=f"(g[40]), "=f"(g[41]), "=f"(g[42]), "=f"(g[43]),
        "=f"(h[0]), "=f"(h[1]), "=f"(h[2]), "=f"(h[3]), "=f"(h[4]), "=f"(h[5]), "=f"(h[6]), "=f"(h[7]), "=f"(h[8]), "=f"(h[9]), "=f"(h[10]), "=f"(h[11]), "=f"(h[12]), "=f"(h[13]), "=f"(h[14]), "=f"(h[15]), "=f"(h[16]), "=f"(h[17]), "=f"(h[18]), "=f"(h[19]), "=f"(h[20]), "=f"(h[21]), "=f"(h[22]), "=f"(h[23]), "=f"(h[24]), "=f"(h[25]), "=f"(h[26]), "=f"(h[27]), "=f"(h[28]), "=f"(h[29]), "=f"(h[30]), "=f"(h[31]), "=f"(h[32]), "=f"(h[33]), "=f"(h[34]), "=f"(h[35]), "=f"(h[36]), "=f"(h[37]), "=f"(h[38]), "=f"(h[39]), "=f"(h[40]), "=f"(h[41]), "=f"(h[42]), "=f"(h[43])
      : "r"(w[0]), "r"(w[1]), "r"(w[2]), "r"(w[3]), "r"(w[4]), "r"(w[5]), "r"(w[6]), "r"(w[7]), "r"(w[8]), "r"(w[9]), "r"(w[10]), "r"(w[11]), "r"(w[12]), "r"(w[13]), "r"(w[14]), "r"(w[15]), "r"(w[20]), "r"(w[21]), "r"(w[22]), "r"(w[23]), "r"(w[24]), "r"(w[25]), "r"(w[26]), "r"(w[27]), "r"(w[28]), "r"(w[29]), "r"(w[30]), "r"(w[31]), "r"(w[32]), "r"(w[33]), "r"(w[34]), "r"(w[35]), "r"(w[36]), "r"(w[37]), "r"(w[38]), "r"(w[39]), "l"(dx), "l"(de), "l"(dh), "l"(dc)
      : "memory");
  }
  static __device__ __forceinline__ void wait_g(float* g) {
    asm volatile("wgmma.wait_group.sync.aligned 1;\n"
      : "+f"(g[0]), "+f"(g[1]), "+f"(g[2]), "+f"(g[3]), "+f"(g[4]), "+f"(g[5]), "+f"(g[6]), "+f"(g[7]), "+f"(g[8]), "+f"(g[9]), "+f"(g[10]), "+f"(g[11]), "+f"(g[12]), "+f"(g[13]), "+f"(g[14]), "+f"(g[15]), "+f"(g[16]), "+f"(g[17]), "+f"(g[18]), "+f"(g[19]), "+f"(g[20]), "+f"(g[21]), "+f"(g[22]), "+f"(g[23]), "+f"(g[24]), "+f"(g[25]), "+f"(g[26]), "+f"(g[27]), "+f"(g[28]), "+f"(g[29]), "+f"(g[30]), "+f"(g[31]), "+f"(g[32]), "+f"(g[33]), "+f"(g[34]), "+f"(g[35]), "+f"(g[36]), "+f"(g[37]), "+f"(g[38]), "+f"(g[39]), "+f"(g[40]), "+f"(g[41]), "+f"(g[42]), "+f"(g[43])
      :: "memory");
  }
  static __device__ __forceinline__ void wait_h(float* h) {
    asm volatile("wgmma.wait_group.sync.aligned 0;\n"
      : "+f"(h[0]), "+f"(h[1]), "+f"(h[2]), "+f"(h[3]), "+f"(h[4]), "+f"(h[5]), "+f"(h[6]), "+f"(h[7]), "+f"(h[8]), "+f"(h[9]), "+f"(h[10]), "+f"(h[11]), "+f"(h[12]), "+f"(h[13]), "+f"(h[14]), "+f"(h[15]), "+f"(h[16]), "+f"(h[17]), "+f"(h[18]), "+f"(h[19]), "+f"(h[20]), "+f"(h[21]), "+f"(h[22]), "+f"(h[23]), "+f"(h[24]), "+f"(h[25]), "+f"(h[26]), "+f"(h[27]), "+f"(h[28]), "+f"(h[29]), "+f"(h[30]), "+f"(h[31]), "+f"(h[32]), "+f"(h[33]), "+f"(h[34]), "+f"(h[35]), "+f"(h[36]), "+f"(h[37]), "+f"(h[38]), "+f"(h[39]), "+f"(h[40]), "+f"(h[41]), "+f"(h[42]), "+f"(h[43])
      :: "memory");
  }
};
__device__ __forceinline__ void node_mma2(float* u, float* a, const uint32_t* w, uint64_t dx) {
    asm volatile(
      "{\n.reg .b64 dx1, dx2, dx3, dy0, dy1, dy2, dy3;\n"
      "add.s64 dx1, %80, 2;\nadd.s64 dx2, %80, 4;\nadd.s64 dx3, %80, 6;\n"
      "add.s64 dy0, %80, 512;\nadd.s64 dy1, %80, 514;\nadd.s64 dy2, %80, 516;\nadd.s64 dy3, %80, 518;\n"
      "wgmma.fence.sync.aligned;\n"
      "wgmma.mma_async.sync.aligned.m64n64k16.f32.bf16.bf16 {%0, %1, %2, %3, %4, %5, %6, %7, %8, %9, %10, %11, %12, %13, %14, %15, %16, %17, %18, %19, %20, %21, %22, %23, %24, %25, %26, %27, %28, %29, %30, %31}, {%64, %65, %66, %67}, %80, 0, 1, 1, 0;\n"
      "wgmma.mma_async.sync.aligned.m64n64k16.f32.bf16.bf16 {%0, %1, %2, %3, %4, %5, %6, %7, %8, %9, %10, %11, %12, %13, %14, %15, %16, %17, %18, %19, %20, %21, %22, %23, %24, %25, %26, %27, %28, %29, %30, %31}, {%68, %69, %70, %71}, dx1, 1, 1, 1, 0;\n"
      "wgmma.mma_async.sync.aligned.m64n64k16.f32.bf16.bf16 {%0, %1, %2, %3, %4, %5, %6, %7, %8, %9, %10, %11, %12, %13, %14, %15, %16, %17, %18, %19, %20, %21, %22, %23, %24, %25, %26, %27, %28, %29, %30, %31}, {%72, %73, %74, %75}, dx2, 1, 1, 1, 0;\n"
      "wgmma.mma_async.sync.aligned.m64n64k16.f32.bf16.bf16 {%0, %1, %2, %3, %4, %5, %6, %7, %8, %9, %10, %11, %12, %13, %14, %15, %16, %17, %18, %19, %20, %21, %22, %23, %24, %25, %26, %27, %28, %29, %30, %31}, {%76, %77, %78, %79}, dx3, 1, 1, 1, 0;\n"
      "wgmma.commit_group.sync.aligned;\n"
      "wgmma.mma_async.sync.aligned.m64n64k16.f32.bf16.bf16 {%32, %33, %34, %35, %36, %37, %38, %39, %40, %41, %42, %43, %44, %45, %46, %47, %48, %49, %50, %51, %52, %53, %54, %55, %56, %57, %58, %59, %60, %61, %62, %63}, {%64, %65, %66, %67}, dy0, 0, 1, 1, 0;\n"
      "wgmma.mma_async.sync.aligned.m64n64k16.f32.bf16.bf16 {%32, %33, %34, %35, %36, %37, %38, %39, %40, %41, %42, %43, %44, %45, %46, %47, %48, %49, %50, %51, %52, %53, %54, %55, %56, %57, %58, %59, %60, %61, %62, %63}, {%68, %69, %70, %71}, dy1, 1, 1, 1, 0;\n"
      "wgmma.mma_async.sync.aligned.m64n64k16.f32.bf16.bf16 {%32, %33, %34, %35, %36, %37, %38, %39, %40, %41, %42, %43, %44, %45, %46, %47, %48, %49, %50, %51, %52, %53, %54, %55, %56, %57, %58, %59, %60, %61, %62, %63}, {%72, %73, %74, %75}, dy2, 1, 1, 1, 0;\n"
      "wgmma.mma_async.sync.aligned.m64n64k16.f32.bf16.bf16 {%32, %33, %34, %35, %36, %37, %38, %39, %40, %41, %42, %43, %44, %45, %46, %47, %48, %49, %50, %51, %52, %53, %54, %55, %56, %57, %58, %59, %60, %61, %62, %63}, {%76, %77, %78, %79}, dy3, 1, 1, 1, 0;\n"
      "wgmma.commit_group.sync.aligned;\n}\n"
      : "=f"(u[0]), "=f"(u[1]), "=f"(u[2]), "=f"(u[3]), "=f"(u[4]), "=f"(u[5]), "=f"(u[6]), "=f"(u[7]), "=f"(u[8]), "=f"(u[9]), "=f"(u[10]), "=f"(u[11]), "=f"(u[12]), "=f"(u[13]), "=f"(u[14]), "=f"(u[15]), "=f"(u[16]), "=f"(u[17]), "=f"(u[18]), "=f"(u[19]), "=f"(u[20]), "=f"(u[21]), "=f"(u[22]), "=f"(u[23]), "=f"(u[24]), "=f"(u[25]), "=f"(u[26]), "=f"(u[27]), "=f"(u[28]), "=f"(u[29]), "=f"(u[30]), "=f"(u[31]),
        "=f"(a[0]), "=f"(a[1]), "=f"(a[2]), "=f"(a[3]), "=f"(a[4]), "=f"(a[5]), "=f"(a[6]), "=f"(a[7]), "=f"(a[8]), "=f"(a[9]), "=f"(a[10]), "=f"(a[11]), "=f"(a[12]), "=f"(a[13]), "=f"(a[14]), "=f"(a[15]), "=f"(a[16]), "=f"(a[17]), "=f"(a[18]), "=f"(a[19]), "=f"(a[20]), "=f"(a[21]), "=f"(a[22]), "=f"(a[23]), "=f"(a[24]), "=f"(a[25]), "=f"(a[26]), "=f"(a[27]), "=f"(a[28]), "=f"(a[29]), "=f"(a[30]), "=f"(a[31])
      : "r"(w[0]), "r"(w[1]), "r"(w[2]), "r"(w[3]), "r"(w[4]), "r"(w[5]), "r"(w[6]), "r"(w[7]), "r"(w[8]), "r"(w[9]), "r"(w[10]), "r"(w[11]), "r"(w[12]), "r"(w[13]), "r"(w[14]), "r"(w[15]), "l"(dx)
      : "memory");
}

__device__ __forceinline__ uint32_t smem_u32(const void* p) { return (uint32_t)__cvta_generic_to_shared(p); }
__device__ __forceinline__ float ex2f(float x) { float y; asm("ex2.approx.ftz.f32 %0, %1;" : "=f"(y) : "f"(x)); return y; }
__device__ __forceinline__ float rcpf(float x) { float y; asm("rcp.approx.ftz.f32 %0, %1;" : "=f"(y) : "f"(x)); return y; }
__device__ __forceinline__ uint32_t pack_bf16(float lo, float hi) {
    uint32_t r; asm("cvt.rn.bf16x2.f32 %0, %1, %2;" : "=r"(r) : "f"(hi), "f"(lo)); return r;
}
__device__ __forceinline__ float bf_lo(uint32_t v) { return __uint_as_float(v << 16); }
__device__ __forceinline__ float bf_hi(uint32_t v) { return __uint_as_float(v & 0xFFFF0000u); }
template<int STRIDE>
__device__ __forceinline__ void cp16i(uint32_t dst, const char* base, uint32_t idx) {
    asm volatile("{\n.reg .b64 a;\nmad.wide.u32 a, %2, %3, %1;\ncp.async.cg.shared.global [%0], [a], 16;\n}\n" :: "r"(dst), "l"(base), "r"(idx), "n"(STRIDE) : "memory");
}
__device__ __forceinline__ void cp16e(uint32_t dst, const char* base, uint32_t idx, uint64_t pol) {
    asm volatile("{\n.reg .b64 a;\nmad.wide.u32 a, %2, 32, %1;\ncp.async.cg.shared.global.L2::cache_hint [%0], [a], 16, %3;\n}\n" :: "r"(dst), "l"(base), "r"(idx), "l"(pol) : "memory");
}
template<int STRIDE>
__device__ __forceinline__ void cp16z(uint32_t dst, const char* base, uint32_t idx, int k, int n, uint64_t pol) {
    if (STRIDE == 32)
        asm volatile("{\n.reg .b64 a;\n.reg .pred p;\nsetp.ge.s32 p, %3, %4;\nmad.wide.u32 a, %2, 32, %1;\ncp.async.cg.shared.global.L2::cache_hint [%0], [a], 16, p, %5;\n}\n"
                     :: "r"(dst), "l"(base), "r"(idx), "r"(k), "r"(n), "l"(pol) : "memory");
    else
        asm volatile("{\n.reg .b64 a;\n.reg .pred p;\nsetp.ge.s32 p, %3, %4;\nmad.wide.u32 a, %2, 128, %1;\ncp.async.cg.shared.global [%0], [a], 16, p;\n}\n"
                     :: "r"(dst), "l"(base), "r"(idx), "r"(k), "r"(n) : "memory");
}
template<int HI, bool Z>
__device__ __forceinline__ void cpx(uint32_t hi, uint32_t dst, uint32_t p, uint32_t lo, int k, int n) {
    if (Z) asm volatile("{\n.reg .b32 l;\n.reg .b64 a;\n.reg .pred q;\nsetp.ge.s32 q, %5, %6;\ndp2a.lo.u32.u32 l, %1, %2, %3;\nmov.b64 a, {l, %0};\ncp.async.cg.shared.global [%4], [a], 16, q;\n}\n"
                        :: "r"(hi), "r"(p), "r"(HI ? 0x8000u : 0x80u), "r"(lo), "r"(dst), "r"(k), "r"(n) : "memory");
    else asm volatile("{\n.reg .b32 l;\n.reg .b64 a;\ndp2a.lo.u32.u32 l, %1, %2, %3;\nmov.b64 a, {l, %0};\ncp.async.cg.shared.global [%4], [a], 16;\n}\n"
                      :: "r"(hi), "r"(p), "r"(HI ? 0x8000u : 0x80u), "r"(lo), "r"(dst) : "memory");
}
template<bool Z>
__device__ __forceinline__ void cpe(uint32_t hi, uint32_t dst, uint32_t idx, uint32_t lo, int k, int n, uint64_t pol) {
    if (Z) asm volatile("{\n.reg .b32 l;\n.reg .b64 a;\n.reg .pred q;\nsetp.ge.s32 q, %5, %6;\nmad.lo.u32 l, %1, 32, %2;\nmov.b64 a, {l, %0};\ncp.async.cg.shared.global.L2::cache_hint [%3], [a], 16, q, %4;\n}\n"
                        :: "r"(hi), "r"(idx), "r"(lo), "r"(dst), "l"(pol), "r"(k), "r"(n) : "memory");
    else asm volatile("{\n.reg .b32 l;\n.reg .b64 a;\nmad.lo.u32 l, %1, 32, %2;\nmov.b64 a, {l, %0};\ncp.async.cg.shared.global.L2::cache_hint [%3], [a], 16, %4;\n}\n"
                      :: "r"(hi), "r"(idx), "r"(lo), "r"(dst), "l"(pol) : "memory");
}
template<int N> __device__ __forceinline__ void cp_wait() { asm volatile("cp.async.wait_group %0;" :: "n"(N) : "memory"); }
__device__ __forceinline__ void mbar_init(uint32_t bar, int cnt) { asm volatile("mbarrier.init.shared.b64 [%0], %1;" :: "r"(bar), "r"(cnt) : "memory"); }
__device__ __forceinline__ void mbar_arrive(uint32_t bar) { asm volatile("mbarrier.arrive.shared.b64 _, [%0];" :: "r"(bar) : "memory"); }
__device__ __forceinline__ void mbar_expect(uint32_t bar, uint32_t bytes) { asm volatile("mbarrier.arrive.expect_tx.shared.b64 _, [%0], %1;" :: "r"(bar), "r"(bytes) : "memory"); }
__device__ __forceinline__ void mbar_cp_arrive(uint32_t bar) { asm volatile("cp.async.mbarrier.arrive.noinc.shared.b64 [%0];" :: "r"(bar) : "memory"); }
__device__ __forceinline__ void mbar_wait(uint32_t bar, uint32_t parity) {
    asm volatile("{\n.reg .pred p;\n.reg .u32 n;\nmbarrier.try_wait.parity.shared.b64 p, [%0], %1;\n@p bra DONE_%=;\nmov.u32 n, 0;\n"
                 "WAIT_%=:\nmbarrier.try_wait.parity.shared.b64 p, [%0], %1, 0x100000;\n@p bra DONE_%=;\n"
                 "add.u32 n, n, 1;\nsetp.lt.u32 p, n, 0x400000;\n@p bra WAIT_%=;\ntrap;\nDONE_%=:\n}\n"
                 :: "r"(bar), "r"(parity) : "memory");
}
__device__ __forceinline__ void mbar_wait_c(uint32_t bar, uint32_t parity) {
    asm volatile("{\n.reg .pred p;\nWAIT_%=:\nmbarrier.try_wait.parity.shared.b64 p, [%0], %1;\n@p bra DONE_%=;\nbra WAIT_%=;\nDONE_%=:\n}\n"
                 :: "r"(bar), "r"(parity) : "memory");
}
__device__ __forceinline__ void mbar_wait_h(uint32_t bar, uint32_t parity) {
    asm volatile("{\n.reg .pred p;\nWAIT_%=:\nmbarrier.try_wait.parity.shared.b64 p, [%0], %1, 0x100000;\n@p bra DONE_%=;\nbra WAIT_%=;\nDONE_%=:\n}\n"
                 :: "r"(bar), "r"(parity) : "memory");
}
__device__ __forceinline__ uint32_t lds32(uint32_t a) { uint32_t v; asm volatile("ld.shared.u32 %0, [%1];" : "=r"(v) : "r"(a) : "memory"); return v; }
__device__ __forceinline__ void sts32(uint32_t a, uint32_t v) { asm volatile("st.shared.u32 [%0], %1;" :: "r"(a), "r"(v) : "memory"); }
__device__ __forceinline__ uint2 lds64(uint32_t a) { uint2 v; asm volatile("ld.shared.v2.u32 {%0,%1}, [%2];" : "=r"(v.x), "=r"(v.y) : "r"(a) : "memory"); return v; }
__device__ __forceinline__ uint4 lds128(uint32_t a) { uint4 v; asm volatile("ld.shared.v4.u32 {%0,%1,%2,%3}, [%4];" : "=r"(v.x), "=r"(v.y), "=r"(v.z), "=r"(v.w) : "r"(a) : "memory"); return v; }
__device__ __forceinline__ void sts128(uint32_t a, uint4 v) { asm volatile("st.shared.v4.u32 [%0], {%1,%2,%3,%4};" :: "r"(a), "r"(v.x), "r"(v.y), "r"(v.z), "r"(v.w) : "memory"); }
__device__ __forceinline__ void ldsm4t(uint32_t* v, uint32_t a) {
    asm volatile("ldmatrix.sync.aligned.m8n8.x4.trans.shared.b16 {%0,%1,%2,%3}, [%4];" : "=r"(v[0]), "=r"(v[1]), "=r"(v[2]), "=r"(v[3]) : "r"(a) : "memory");
}
__device__ __forceinline__ void stsm4t(uint32_t a, const uint32_t* v) {
    asm volatile("stmatrix.sync.aligned.m8n8.x4.trans.shared.b16 [%0], {%1,%2,%3,%4};" :: "r"(a), "r"(v[0]), "r"(v[1]), "r"(v[2]), "r"(v[3]) : "memory");
}
__device__ __forceinline__ int atoms_inc(uint32_t a) { int v; asm volatile("atom.shared.add.u32 %0, [%1], 1;" : "=r"(v) : "r"(a) : "memory"); return v; }
__device__ __forceinline__ bool elect_one() {
    uint32_t el;
    asm volatile("{\n.reg .pred p;\nelect.sync _|p, 0xffffffff;\nselp.u32 %0, 1, 0, p;\n}" : "=r"(el));
    return el != 0;
}
__device__ __forceinline__ float tanhf_a(float x) { float y; asm("tanh.approx.f32 %0, %1;" : "=f"(y) : "f"(x)); return y; }
__device__ __forceinline__ const char* as_pair(const void* p, uint32_t scratch) {
    const char* r;
    asm volatile("st.shared.u64 [%1], %2;\nld.volatile.shared.u64 %0, [%1];" : "=l"(r) : "r"(scratch), "l"(p) : "memory");
    return r;
}
__device__ __forceinline__ void ld_unit(uint4& v, const char* p, bool ok) {
    asm volatile("{\n.reg .pred q;\nsetp.ne.u32 q, %5, 0;\n@q ld.relaxed.gpu.global.v4.u32 {%0,%1,%2,%3}, [%4];\n}"
                 : "+r"(v.x), "+r"(v.y), "+r"(v.z), "+r"(v.w) : "l"(p), "r"((uint32_t)ok) : "memory");
}
__device__ __forceinline__ void ld_unit(uint2& v, const char* p, bool ok) {
    asm volatile("{\n.reg .pred q;\nsetp.ne.u32 q, %3, 0;\n@q ld.relaxed.gpu.global.v2.u32 {%0,%1}, [%2];\n}"
                 : "+r"(v.x), "+r"(v.y) : "l"(p), "r"((uint32_t)ok) : "memory");
}
__device__ __forceinline__ void bulk_ld(uint32_t dst, const void* src, int bytes, uint32_t bar) {
    mbar_expect(bar, bytes);
    if (bytes > 0) asm volatile("cp.async.bulk.shared::cluster.global.mbarrier::complete_tx::bytes [%0], [%1], %2, [%3];" :: "r"(dst), "l"(src), "r"(bytes), "r"(bar) : "memory");
}
__device__ __forceinline__ void bulk_st(void* dst, uint32_t src, int bytes) {
    asm volatile("cp.async.bulk.global.shared::cta.bulk_group [%0], [%1], %2;" :: "l"(dst), "r"(src), "r"(bytes) : "memory");
}

__device__ __forceinline__ void finish(uint4& a, const uint4& xu, const uint4& xv) {
    asm("{\n.reg .b32 z;\nfma.rn.relu.bf16x2 z, %0, %3, %1;\nadd.rn.bf16x2 %0, z, %2;\n}" : "+r"(a.x) : "r"(xu.x), "r"(xv.x), "r"(0x3F803F80u));
    asm("{\n.reg .b32 z;\nfma.rn.relu.bf16x2 z, %0, %3, %1;\nadd.rn.bf16x2 %0, z, %2;\n}" : "+r"(a.y) : "r"(xu.y), "r"(xv.y), "r"(0x3F803F80u));
    asm("{\n.reg .b32 z;\nfma.rn.relu.bf16x2 z, %0, %3, %1;\nadd.rn.bf16x2 %0, z, %2;\n}" : "+r"(a.z) : "r"(xu.z), "r"(xv.z), "r"(0x3F803F80u));
    asm("{\n.reg .b32 z;\nfma.rn.relu.bf16x2 z, %0, %3, %1;\nadd.rn.bf16x2 %0, z, %2;\n}" : "+r"(a.w) : "r"(xu.w), "r"(xv.w), "r"(0x3F803F80u));
}

__device__ __forceinline__ void node_rows(uint32_t p, const float* a) {
    #pragma unroll
    for (int i = 0; i < 4; i++) {
        const float* u = a + 8 * i;
        const uint32_t v[4] = {pack_bf16(u[0], u[1]), pack_bf16(u[2], u[3]), pack_bf16(u[4], u[5]), pack_bf16(u[6], u[7])};
        stsm4t(p + i * 2048, v);
    }
}

constexpr int LOCK_OFF = 64732;
constexpr float EPS2 = 2e-6f;
constexpr float TAU = 2.5e-5f;

template<bool HALF>
__device__ __forceinline__ void make_wfrag(uint32_t* f, const uint32_t* v) {
    const uint32_t v0 = v[0], v1 = v[1], v2 = v[2], v3 = v[3];
    f[0] = __byte_perm(v0, v1, 0x5410); f[1] = __byte_perm(v0, v1, 0x7632);
    f[2] = __byte_perm(v2, v3, 0x5410); f[3] = __byte_perm(v2, v3, 0x7632);
    if (HALF) {
        #pragma unroll
        for (int i = 0; i < 4; i++) asm("mul.rn.bf16x2 %0, %0, %1;" : "+r"(f[i]) : "r"(0x3F003F00u));
    }
}

__host__ __device__ constexpr int rem_of(int np) { return (0x23343211u >> (4 * (np - NPMIN))) & 15; }
__host__ __device__ constexpr int last_at(int np) { return (0x40100300u >> (4 * (np - NPMIN))) & 15; }
template<int NP>
__device__ __forceinline__ void epi_fast(const float* g, const float* h, float m1, float m2,
                                         float& n0, float& d0, float& n1, float& d1, float& dmin)
{
    constexpr int MP = last_at(NP);
    static_assert(MP < NP - rem_of(NP), "masked pair before the test");
    #pragma unroll
    for (int i = 0; i < NP; i++) {
        const int j = i == MP ? NP - 1 : i < MP ? i : i - 1;
        float t0 = tanhf_a(g[4*j+0]), t1 = tanhf_a(g[4*j+1]), t2 = tanhf_a(g[4*j+2]), t3 = tanhf_a(g[4*j+3]);
        auto add_d = [&]() {
            if (i == 0) { d0 = t0 + (2.f * (NP - 1) + EPS2); d1 = t2 + (2.f * (NP - 1) + EPS2); } else { d0 += t0; d1 += t2; }
            d0 += t1; d1 += t3;
        };
        if (MP == 1 && i == 0) {
            add_d();
            n0 = fmaf(t0, h[0], h[0]); n1 = fmaf(t2, h[2], h[2]);
            n0 = fmaf(t1 + 1.f, h[1], n0); n1 = fmaf(t3 + 1.f, h[3], n1);
            continue;
        }
        if (j < NP - 1) { add_d(); t0 += 1.f; t1 += 1.f; t2 += 1.f; t3 += 1.f; }
        else { t0 = fmaf(t0, m1, m1); t1 = fmaf(t1, m2, m2); t2 = fmaf(t2, m1, m1); t3 = fmaf(t3, m2, m2); add_d(); }
        if (i == 0) { n0 = t0 * h[4*j]; n1 = t2 * h[4*j+2]; } else { n0 = fmaf(t0, h[4*j], n0); n1 = fmaf(t2, h[4*j+2], n1); }
        n0 = fmaf(t1, h[4*j+1], n0); n1 = fmaf(t3, h[4*j+3], n1);
        if (i == NP - 1 - rem_of(NP)) dmin = fminf(d0, d1);
    }
}

__device__ __noinline__ float4 epi_exact(const float4* gh, int np, int dv)
{
    float n0 = 0.f, d0 = EPS2, n1 = 0.f, d1 = EPS2;
    #pragma unroll 2
    for (int j = 0; j < np; j++) {
        const float4 g = gh[j], h = gh[NPMAX + j];
        const float ma = (2 * j < dv) ? 2.f : 0.f, mb = (2 * j + 1 < dv) ? 2.f : 0.f;
        const float e0 = ma * rcpf(1.f + ex2f(-2.f * LOG2E * g.x)), e1 = mb * rcpf(1.f + ex2f(-2.f * LOG2E * g.y));
        const float e2 = ma * rcpf(1.f + ex2f(-2.f * LOG2E * g.z)), e3 = mb * rcpf(1.f + ex2f(-2.f * LOG2E * g.w));
        d0 += e0 + e1; n0 = fmaf(e0, h.x, fmaf(e1, h.y, n0));
        d1 += e2 + e3; n1 = fmaf(e2, h.z, fmaf(e3, h.w, n1));
    }
    return make_float4(n0, d0, n1, d1);
}
__device__ __noinline__ float4 epi_single(uint32_t spare, int dv)
{
    __syncwarp();
    uint32_t lane; asm volatile("mov.u32 %0, %%laneid;" : "=r"(lane));
    const int j = lane & 15;
    const uint32_t p = spare + min(j, (dv - 1) >> 1) * 16 + (lane >> 4) * 8;
    const uint2 g = lds64(p), h = lds64(p + 16 * NPMAX);
    const float e0 = (2 * j < dv ? 2.f : 0.f) * rcpf(1.f + ex2f(-2.f * LOG2E * __uint_as_float(g.x)));
    const float e1 = (2 * j + 1 < dv ? 2.f : 0.f) * rcpf(1.f + ex2f(-2.f * LOG2E * __uint_as_float(g.y)));
    float d = e0 + e1, n = fmaf(e0, __uint_as_float(h.x), e1 * __uint_as_float(h.y));
    #pragma unroll
    for (int o = 8; o; o >>= 1) { n += __shfl_xor_sync(~0u, n, o); d += __shfl_xor_sync(~0u, d, o); }
    d += EPS2;
    sts32(spare + LOCK_OFF, 0);
    return make_float4(__shfl_sync(~0u, n, 0), __shfl_sync(~0u, d, 0), __shfl_sync(~0u, n, 16), __shfl_sync(~0u, d, 16));
}
template<int NP>
__device__ __forceinline__ void epi_dump(const float* g, const float* h, float4* gh) {
    #pragma unroll
    for (int i = 0; i < NP; i++) {
        gh[i] = make_float4(g[4*i], g[4*i+1], g[4*i+2], g[4*i+3]);
        gh[NPMAX + i] = make_float4(h[4*i], h[4*i+1], h[4*i+2], h[4*i+3]);
    }
}

__device__ __noinline__ void slow_bin(const __nv_bfloat16* x, const __nv_bfloat16* ea, const int* src, const int* dst,
                                      const __nv_bfloat16* wa, const __nv_bfloat16* wb, const __nv_bfloat16* wc,
                                      const __nv_bfloat16* wu, const __nv_bfloat16* wv, __nv_bfloat16* out,
                                      int E, int node0, int nn, int nthr)
{
    const int tid = threadIdx.x, lane = tid & 31;
    for (int i = tid; i < nn * 128; i += nthr) g_slow[(size_t)node0 * 128 + i] = 0.f;
    asm volatile("bar.sync 1, %0;" :: "r"(nthr) : "memory");
    for (int e0 = (tid >> 5) * 32; e0 < E; e0 += nthr) {
        int d = (e0 + lane < E) ? dst[e0 + lane] - node0 : -1;
        unsigned m = __ballot_sync(~0u, d >= 0 && d < nn);
        while (m) {
            int l = __ffs(m) - 1; m &= m - 1;
            int e = e0 + l, n = node0 + __shfl_sync(~0u, d, l), s = src[e];
            float g0 = 0, g1 = 0, h0 = 0, h1 = 0;
            for (int k = 0; k < 64; k++) {
                float xs = __bfloat162float(x[(size_t)s * 64 + k]), xd = __bfloat162float(x[(size_t)n * 64 + k]);
                uint32_t b2 = *(const uint32_t*)(wb + k * 64 + 2 * lane), v2 = *(const uint32_t*)(wv + k * 64 + 2 * lane);
                uint32_t a2 = *(const uint32_t*)(wa + k * 64 + 2 * lane);
                g0 = fmaf(xs, bf_lo(b2), fmaf(xd, bf_lo(a2), g0)); g1 = fmaf(xs, bf_hi(b2), fmaf(xd, bf_hi(a2), g1));
                h0 = fmaf(xs, bf_lo(v2), h0); h1 = fmaf(xs, bf_hi(v2), h1);
            }
            for (int k = 0; k < 16; k++) {
                float ev = __bfloat162float(ea[(size_t)e * 16 + k]);
                uint32_t c2 = *(const uint32_t*)(wc + k * 64 + 2 * lane);
                g0 = fmaf(ev, bf_lo(c2), g0); g1 = fmaf(ev, bf_hi(c2), g1);
            }
            float s0 = rcpf(1.f + ex2f(-LOG2E * g0)), s1 = rcpf(1.f + ex2f(-LOG2E * g1));
            float* acc = g_slow + (size_t)n * 128 + 4 * lane;
            atomicAdd(acc + 0, s0 * h0); atomicAdd(acc + 1, s0);
            atomicAdd(acc + 2, s1 * h1); atomicAdd(acc + 3, s1);
        }
    }
    __threadfence();
    asm volatile("bar.sync 1, %0;" :: "r"(nthr) : "memory");
    for (int i = tid; i < nn * 32; i += nthr) {
        int n = node0 + (i >> 5), cp = i & 31;
        float4 a = __ldcg((const float4*)(g_slow + (size_t)n * 128 + 4 * cp));
        float u0 = 0, u1 = 0;
        for (int k = 0; k < 64; k++) {
            float xd = __bfloat162float(x[(size_t)n * 64 + k]);
            uint32_t w2 = *(const uint32_t*)(wu + k * 64 + 2 * cp);
            u0 = fmaf(xd, bf_lo(w2), u0); u1 = fmaf(xd, bf_hi(w2), u1);
        }
        uint32_t xv = *(const uint32_t*)(x + (size_t)n * 64 + 2 * cp);
        float z0 = u0 + a.x / (a.y + 1e-6f), z1 = u1 + a.z / (a.w + 1e-6f);
        *(uint32_t*)(out + (size_t)n * 64 + 2 * cp) = pack_bf16(bf_lo(xv) + fmaxf(z0, 0.f), bf_hi(xv) + fmaxf(z1, 0.f));
    }
}

__global__ void __launch_bounds__(256) slow_kernel(const __nv_bfloat16* x, const __nv_bfloat16* ea, const int* src, const int* dst,
        const __nv_bfloat16* wa, const __nv_bfloat16* wb, const __nv_bfloat16* wc, const __nv_bfloat16* wu, const __nv_bfloat16* wv,
        __nv_bfloat16* out, int N, int E, int npb)
{
    int node0 = blockIdx.x * npb;
    slow_bin(x, ea, src, dst, wa, wb, wc, wu, wv, out, E, node0, max(0, min(npb, N - node0)), 256);
}

constexpr int XS_BYTES = NPMAX * 1024;
constexpr int ES_BYTES = NPMAX * 256;
constexpr int SM_XS = 0;
constexpr int SM_XU = SM_XS + 3 * NSTAGE * XS_BYTES;
constexpr int SM_TAB = SM_XU + NPB_MAX * 128;
constexpr int SM_ES = SM_TAB + (NPB_MAX + 2) * 128;
constexpr int SM_WC = SM_ES + 3 * NSTAGE * ES_BYTES;
constexpr int SM_OH = SM_WC + 2048;
constexpr int SM_EID = SM_OH + 256;
constexpr int SM_SRC = SM_EID + (SLOT_CAP + 32) * 4;
constexpr int SM_TINFO = SM_SRC + (SLOT_CAP + 32) * 2;
constexpr int SM_MISC = SM_TINFO + TILE_CAP * 32;
constexpr int SM_CLAIM = SM_TAB + (NPB_MAX + 1) * 128;
constexpr int SM_BARS = SM_MISC + 32 * 4;
constexpr int SM_ABAR = SM_BARS + 6 * 48;
constexpr int SM_XBAR = SM_ABAR + 10 * 8;
constexpr int SM_SBAR = SM_XBAR + 4 * 8;
constexpr int SM_GBAR = SM_SBAR + 3 * 8;
constexpr int SM_WL = SM_GBAR + 97 * 8;
constexpr int WST = 9;
constexpr int SMEM_BYTES = SM_WL + (96 + WST) * 8;
constexpr int SM_P2 = 0, SM_P1 = 6 * 384 * 16;
constexpr int SM_DEG = SM_P1 + P1B;
constexpr int SM_CNT = SM_DEG + 512 * 4;
constexpr int SM_CLS = SM_CNT + 512 * 4;
constexpr int SM_HIST = SM_CLS + NCLS * 4;
constexpr int SM_XLIST = SM_HIST + 136 * 4;
constexpr int SM_SORT = SM_XLIST + XCAP * 8;
constexpr int SM_BASE = SM_SORT + NPB_MAX * 4;
constexpr int SM_PAIR = SM_BASE + (NPB_MAX + 4) * 2;
constexpr int SM_IDX = SM_EID;
constexpr int SM_WR = SM_TAB;
static_assert(TILE_CAP <= 128 && TR >= 2 && SM_ES % 256 == 0 && NSTAGE == 2 && SM_BARS % 16 == 0 && SM_TINFO % 16 == 0 && SM_EID % 128 == 0 && SM_TAB % 1024 == 0 && SM_XU % 1024 == 0 && SM_TINFO % 8 == 0 && SM_OH % 16 == 0 && SM_SORT % 16 == 0 && SM_XLIST % 16 == 0 && SM_PAIR % 8 == 0, "align");
static_assert(P1B % 16 == 0 && P2B <= SM_P1 && NB_MAX <= 6 * 24 && SM_PAIR + 128 * 8 <= SM_XU && CH_MAX * 4 <= SM_SRC - SM_EID && SM_DEG >= 3 << 14, "alias");
static_assert(SMEM_BYTES <= 232448 && SM_TAB + (NPB_MAX - 3) * 128 + LOCK_OFF == SM_MISC + 28 && 32 * NPMAX <= 384, "smem");
constexpr uint32_t C_BRK = 16  , C_CONT = 32, C_MORE = 64;
constexpr uint32_t ONE_F = 0x3F800000u;
constexpr int NONE = NPB_MAX;

__device__ __forceinline__ uint2 tile_info(uint32_t e) {
    const uint32_t y = (uint32_t)((int)e >> 16) & (ONE_F | 0x1FFFu);
    return make_uint2(e, (e & 0x1F000000u) ? y | 0x80000000u : y);
}
__device__ __forceinline__ bool unpad(uint32_t w1, int np, float ga, float gb, float& d0, float& d1, int& dv) {
    const int pad = (int)w1 < 0 ? (w1 >> 8) & 31 : 0;
    dv = 2 * np - 2 - pad + ((int)w1 > 127) + ((int)w1 >= (int)ONE_F);
    float t0 = TAU * 2 * np, t1 = t0;
    if (pad) {
        t0 = fmaxf(t0, d0 * (1.f / 1024)); t1 = fmaxf(t1, d1 * (1.f / 1024));
        asm volatile("tanh.approx.f32 %0, %0;\ntanh.approx.f32 %1, %1;" : "+f"(ga), "+f"(gb));
        d0 -= pad * (1.f + ga); d1 -= pad * (1.f + gb);
    }
    if (dv == 0) { d0 = d1 = EPS2; t0 = t1 = 0.f; }
    return d0 < t0 || d1 < t1;
}
__device__ __forceinline__ uint64_t desc_sw128(uint32_t a) {
    return (uint64_t)((a & 0x3FFFF) >> 4) | ((uint64_t)1 << 16) | ((uint64_t)64 << 32) | ((uint64_t)1 << 62);
}

__device__ __forceinline__ uint32_t sel(bool c, uint32_t a, uint32_t b) {
    uint32_t r; asm("{\n.reg .pred p;\nsetp.ne.u32 p, %1, 0;\nselp.b32 %0, %2, %3, p;\n}" : "=r"(r) : "r"((uint32_t)c), "r"(a), "r"(b)); return r;
}
__device__ __forceinline__ void tile_entry(uint8_t* smem, uint32_t sv, int dg, int mn, int t, int tl, int np, int done, uint32_t flags, int next) {
    const uint32_t nd = sv & 0xFFFF, w0 = nd * 128 + ((nd & 7) << 4);
    const int dv = min(max(dg - done, 0), 2 * np), r = 2 * np - dv;
    const bool gen = mn - done < 2 * np - 2;
    const uint32_t w1 = (uint32_t)np | flags | sel(gen || flags, C_BRK, 0u) | sel(r < 2, 0x8000u >> (8 * r), (r - 2) << 8);
    *(uint2*)(smem + SM_TINFO + tl * 32 + t * 8) = make_uint2(sel(dv, (sv >> 16) + done, 0) | (sel(gen, 13 + (np > 5) + (np > 8), np) << 16) | (next << 20) | ((uint32_t)dv << 27), w0 | sel(np, w1 << 16, 0u));
}
__device__ __noinline__ void tiles_many(uint8_t* smem, uint32_t sv, int dg, int mn, int id, int left, unsigned sm) {
    int* misc = (int*)(smem + SM_MISC);
    int nt = (left + NPMAX - 1) / NPMAX, tl = id >> 2, done = 0, nx = 0;
    if ((id & 3) == 0) { nx = atomicAdd(&misc[5], nt - 1); if (nx + nt - 1 > TILE_CAP) misc[1] = 1; }
    nx = __shfl_sync(sm, nx, id & 28);
    if (nx + nt - 1 > TILE_CAP) left = 0;
    uint32_t cont = 0;
    #pragma unroll 1
    while (left > 0) {
        const int np = (left + nt - 1) / nt;
        left -= np; nt--;
        tile_entry(smem, sv, dg, mn, id & 3, tl, np, done, cont | (left > 0 ? C_MORE : 0u), left > 0 ? nx : 0);
        tl = nx++; cont = C_CONT; done += 2 * np;
    }
}
__device__ __forceinline__ void tables(uint8_t* smem, uint32_t sbase, int id0, int ngroups) {
    const int t = id0 & 3;
    uint4 s4[3];
    uint32_t me[3], sv[3];
    #pragma unroll
    for (int k = 0; k < 3; k++) { s4[k] = lds128(sbase + SM_SORT + (id0 & ~3) * 4 + k * 512); me[k] = lds32(sbase + SM_SORT + id0 * 4 + k * 512); }
    #pragma unroll
    for (int k = 0; k < 3; k++) asm volatile("ld.shared.u16 %0, [%1];" : "=r"(sv[k]) : "r"(sbase + SM_BASE + (me[k] & 0xFFFF) * 2) : "memory");
    int mn[3], left[3];
    uint32_t more = 0;
    #pragma unroll
    for (int k = 0; k < 3; k++) {
        const int g = (id0 >> 2) + 32 * k, nx = ngroups + 4 + g;
        sv[k] = sv[k] << 16 | (me[k] & 0xFFFF);
        mn[k] = min(min(s4[k].x, s4[k].y), min(s4[k].z, s4[k].w)) >> 16;
        left[k] = ((max(max(s4[k].x, s4[k].y), max(s4[k].z, s4[k].w)) >> 16) + 1) >> 1;
        const bool two = left[k] > NPMAX;
        more |= two << k;
        tile_entry(smem, sv[k], me[k] >> 16, mn[k], t, sel(g >= ngroups + 4, ngroups, g), sel(two, min((left[k] + 1) >> 1, NPMAX), sel(left[k], max(left[k], NPMIN), 0)), 0, sel(two, C_MORE, 0u), sel(two, nx & 127, 0));
    }
    #pragma unroll 1
    for (int id = id0; __any_sync(~0u, more); id += 128) {
        const int nx = ngroups + 4 + (id >> 2);
        const bool odd = left[0] > 2 * NPMAX || ((more & 1) && nx >= TILE_CAP - TILE_X);
        const unsigned sm = __ballot_sync(~0u, odd);
        if (__builtin_expect(odd, 0)) tiles_many(smem, sv[0], me[0] >> 16, mn[0], id, left[0], sm);
        else if (more & 1) tile_entry(smem, sv[0], me[0] >> 16, mn[0], t, nx, left[0] >> 1, (left[0] + 1) & ~1, C_CONT, 0);
        __syncwarp();
        more >>= 1;
        sv[0] = sv[1]; sv[1] = sv[2]; me[0] = me[1]; me[1] = me[2]; mn[0] = mn[1]; mn[1] = mn[2]; left[0] = left[1]; left[1] = left[2];
    }
}
__device__ __forceinline__ uint32_t to_list(uint32_t sbase, uint32_t e, uint32_t bin) {
    uint32_t j; asm volatile("atom.shared.inc.u32 %0, [%1], 0x7fffffff;" : "=r"(j) : "r"(sbase + SM_MISC + 8) : "memory");
    j = min(j, 63u);
    sts32(sbase + SM_P1 + j * 4, e | ((j < 63 ? bin : 255u) << 16));
    return j;
}

template<bool LO32>
__global__ void __launch_bounds__(THREADS, 1)
gcn_kernel(const int* __restrict__ dst, unsigned* gbar, char* gs, const int* __restrict__ src, int E, int ch, int N, int npb, uint32_t magic,
           const __nv_bfloat16* __restrict__ x, const __nv_bfloat16* __restrict__ ea,
           const __nv_bfloat16* __restrict__ wa, const __nv_bfloat16* __restrict__ wb, const __nv_bfloat16* __restrict__ wc,
           const __nv_bfloat16* __restrict__ wu, const __nv_bfloat16* __restrict__ wv,
           __nv_bfloat16* out, int4 wrow, const __grid_constant__ CUtensorMap tm2, const __grid_constant__ CUtensorMap tmw,
           const __grid_constant__ CUtensorMap tmc, const __grid_constant__ CUtensorMap tmx)
{
    extern __shared__ __align__(1024) uint8_t smem[];
    int* cls = (int*)(smem + SM_CLS);
    int* misc = (int*)(smem + SM_MISC);
    uint32_t* xlist = (uint32_t*)(smem + SM_XLIST);
    WG0(); WS(0); ZS(0);
    const uint32_t sbase = smem_u32(smem);
    const int tid = threadIdx.x, lane = tid & 31;
    const int b = blockIdx.x, nb = gridDim.x;
    const int cnt = max(0, min(ch, E - b * ch));
    const int node0 = b * npb;
    auto src_ld = [&](int v) { bulk_ld(sbase + SM_XU + v * 8192, src + b * ch + v * 2048, min(max(cnt * 4 - v * 8192, 0), 8192), sbase + SM_SBAR + v * 8); };
    auto dst_ld = [&](int v) { bulk_ld(sbase + SM_IDX + v * 8192, dst + b * ch + v * 2048, min(max(cnt * 4 - v * 8192, 0), 8192), sbase + SM_ABAR + v * 8); };
    auto box_ld = [&](uint32_t dst, const CUtensorMap* tm, int col, int row, uint32_t bar) {
        asm volatile("cp.async.bulk.tensor.2d.shared::cluster.global.mbarrier::complete_tx::bytes [%0], [%1, {%3, %4}], [%2];"
            :: "r"(dst), "l"((uint64_t)tm), "r"(bar), "r"(col), "r"(row) : "memory");
    };
    auto w_ld = [&]() {
        mbar_expect(sbase + SM_ABAR + 24, 272 * 128);
        box_ld(sbase + SM_WR, &tmw, 0, wrow.y, sbase + SM_ABAR + 24); box_ld(sbase + SM_WR + 64 * 128, &tmc, 0, 0, sbase + SM_ABAR + 24);
        box_ld(sbase + SM_WR + 80 * 128, &tmw, 0, wrow.w, sbase + SM_ABAR + 24); box_ld(sbase + SM_WR + 144 * 128, &tmw, 0, wrow.x, sbase + SM_ABAR + 24);
        box_ld(sbase + SM_WR + 208 * 128, &tmw, 0, wrow.z, sbase + SM_ABAR + 24);
    };
    auto x_ld = [&](int k) {
        mbar_expect(sbase + SM_XBAR + k * 8, 16384);
        box_ld(sbase + SM_XU + k * 16384, &tmx, 0, node0 + 128 * k, sbase + SM_XBAR + k * 8);
    };
    uint32_t tag = 0;
    if (tid < 32) asm volatile("ld.relaxed.gpu.global.u32 %0, [%1];" : "=r"(tag) : "l"(gbar));
    if (tid >> 5 == 11) {
        if (elect_one()) {
            mbar_init(sbase + SM_ABAR, 1);
            asm volatile("fence.mbarrier_init.release.cluster;" ::: "memory");
            dst_ld(0);
        }
    }
    if (tid >= 384) {
        if (elect_one()) {
            const int v = (tid >> 5) & 3;
            if (v) mbar_init(sbase + SM_ABAR + v * 8, 1);
            asm volatile("fence.mbarrier_init.release.cluster;" ::: "memory");
            if (v == 1) dst_ld(v);
            if (v == 3) {
                mbar_init(sbase + SM_ABAR + 40, 1); mbar_init(sbase + SM_GBAR + 96 * 8, 32); mbar_init(sbase + SM_ABAR + 72, 384); mbar_init(sbase + SM_XBAR + 24, 512);
            }
            #pragma unroll 1
            for (int j = 0; j < 3; j++) {
                #pragma unroll
                for (int i = 0; i < 8; i++) mbar_init(sbase + SM_GBAR + (v * 24 + j * 8 + i) * 8, 32);
                if (j == 1 && v == 2) dst_ld(v);
            }
            if (tid < 480) {
                #pragma unroll
                for (int i = 0; i < 2; i++) { mbar_init(sbase + SM_BARS + (v * 2 + i) * 48, 64); mbar_init(sbase + SM_BARS + (v * 2 + i) * 48 + 8, 128); }
                mbar_init(sbase + SM_ABAR + 48 + v * 8, 128); mbar_init(sbase + SM_XBAR + v * 8, 1); mbar_init(sbase + SM_SBAR + v * 8, 1);
            }
            asm volatile("fence.mbarrier_init.release.cluster;" ::: "memory");
        }
    }
    if (tid >= 128 && tid < 132) asm volatile("prefetch.tensormap [%0];" :: "l"((uint64_t)(tid == 128 ? &tmw : tid == 129 ? &tmc : tid == 130 ? &tm2 : &tmx)) : "memory");
    const int warp = (int)__reduce_max_sync(~0u, (unsigned)tid >> 5);
    const int wg = warp >> 2, w = warp & 3;
    const int q = lane >> 2, t = lane & 3;
    const int ch0 = 16 * w + 2 * q;
    const int nn = max(0, min(npb, N - node0));
    if (sbase & 1023) __trap();

    sts32(sbase + (tid < NPB_MAX ? SM_DEG : SM_CNT) + tid * 4, tid < NPB_MAX ? 0 : 0xC0000000u);
    if (tid < NCLS + NB_MAX) cls[tid] = tid < NCLS ? 0 : (tid - NCLS) * CE + 64;
    else if (wg == 2) {
        if (w < 2) {
            *(uint32_t*)(smem + SM_OH + (tid & 63) * 4) = t != (q >> 1) ? 0u : (w == 0 ? 0x00003F00u : 0x3F000000u);
        } else if (w == 2) *(uint32_t*)(smem + SM_TAB + NPB_MAX * 128 + lane * 4) = 0u;
        else misc[lane] = lane == 5 ? TILE_CAP - TILE_X : lane == 7 && npb > NPB_MAX - 3;
    }
    if (warp == 13 && lane < WST * 2) sts32(sbase + SM_WL + 768 + lane * 4, NONE * 0x10001u);
    if (warp == 14) sts32(sbase + SM_TINFO + 96 * 32 + lane * 4, 0);
    if (warp == 15) sts32(sbase + SM_CLAIM + lane * 4, lane == 0 ? 3 : 0x40000000);
    if (wg < 3) {
        #pragma unroll 1
        for (int i = tid; i < P2B / 32; i += 384) { sts128(sbase + SM_P2 + i * 16, make_uint4(0, 0, 0, 0)); sts128(sbase + SM_P2 + P2B / 2 + i * 16, make_uint4(0, 0, 0, 0)); }
    }
    if (tid == 0) sts32(sbase + SM_PAIR, tag);
    if (wg < 3) { asm volatile("bar.sync 1, 384;" ::: "memory"); tag = lds32(sbase + SM_PAIR); }
    tag = (tag & 1) | 2;
    if (wg < 3) {
        const uint32_t d0 = ((NPB_MAX + ((2 * lane) & 15) + 16 * (b & 1)) * 4 | (tag << 14)) * 0x10001u, d1 = d0 + 0x40004u;
        #pragma unroll
        for (int i = 0; i < 3; i++) if (i < 2 || tid + 768 < P1B / 16) sts128(sbase + SM_P1 + (tid + 384 * i) * 16, make_uint4(d0, d0, d1, d1));
    }
    if (warp == 15 && elect_one()) w_ld();
    WS(1); ZS(1);
    __syncthreads();
    if (wg == 3) tag = (lds32(sbase + SM_PAIR) & 1) | 2;

    uint32_t ent[EPT];
    #pragma unroll
    for (int v = 0; v < EPT / 4; v++) {
        mbar_wait_c(sbase + SM_ABAR + v * 8, 0);
        if (v == 0) ZS(2);
        if (((v == 0 && (warp == 13 || warp == 14)) || (v == 1 && warp == 15)) && elect_one()) src_ld(warp - 13);
        const uint32_t off = v * (THREADS * 4) + tid * 4;
        if (off < (uint32_t)cnt) {
            const uint32_t ia = sbase + SM_IDX + off * 4;
            const uint4 u = lds128(ia);
            uint32_t dv[4] = {u.x, u.y, u.z, u.w}, ps[4], ck[4];
            uint32_t* en = ent + 4 * v;
            #pragma unroll
            for (int k = 0; k < 4; k++) {
                dv[k] = min(dv[k], (uint32_t)(nb * npb - 1));
                ps[k] = __umulhi(dv[k], magic); en[k] = atoms_inc(sbase + SM_HIST + ps[k] * 4);
            }
            #pragma unroll
            for (int k = 0; k < 4; k++) {
                dv[k] = (dv[k] - ps[k] * npb) * 4 + (tag << 14);
                ck[k] = en[k] - ps[k] * CE;
                en[k] ^= ps[k] * 4 & 60;
            }
            if (__builtin_expect(max(max(ck[0], ck[1]), max(ck[2], ck[3])) >= 64 + CE, 0)) {
                #pragma unroll
                for (int k = 0; k < 4; k++) if (ck[k] >= 64 + CE) en[k] = to_list(sbase, dv[k], ps[k]);
            }
            #pragma unroll
            for (int k = 0; k < 4; k++)
                asm volatile("{\n.reg .pred p;\nsetp.ge.u32 p, %2, 64;\n@p st.shared.u16 [%0], %1;\n}" :: "r"(sbase + SM_P1 + 128 + en[k] * 2), "r"(dv[k]), "r"(en[k]) : "memory");
        }
    }
    WS(5); ZS(3);
    __syncthreads();
    auto send = [&](int o, uint32_t a, int bytes) {
        if (warp == 14 && elect_one()) {
            asm volatile("fence.proxy.async.shared::cta;" ::: "memory");
            bulk_st(gs + b * (P1B + P2B) + o, a, bytes);
            asm volatile("cp.async.bulk.commit_group;" ::: "memory");
        }
    };
    send(0, sbase + SM_P1, 256 + nb * (CE * 2));
    #pragma unroll
    for (int v = 0; v < EPT / 4; v++) {
        mbar_wait_c(sbase + SM_SBAR + v * 8, 0);
        const uint32_t off = v * (THREADS * 4) + tid * 4;
        if (off < (uint32_t)cnt) {
            const uint4 sv = lds128(sbase + SM_XU + off * 4);
            const uint32_t ss[4] = {sv.x, sv.y, sv.z, sv.w};
            #pragma unroll
            for (int k = 0; k < 4; k++) sts32(sbase + SM_P2 + ent[4*v+k] * 4, (ss[k] & 0xFFFF) | (((off + k) << 19) + (tag << 16)));
        }
    }
    WS(7); ZS(4);
    __syncthreads();
    send(P1B, sbase + SM_P2, 256 + nb * (CE * 4));
    WSL(8);

    const int ngroups = (nn + 3) >> 2;
    if (wg == 3) {
        asm volatile("setmaxnreg.dec.sync.aligned.u32 56;");
        WS(2);
        const char* const ga = as_pair((const char*)x + (w < 3 ? 0 : (size_t)node0 * 128) + (lane & 7) * 16, sbase + SM_PAIR + (tid & 127) * 8);
        const char* const gb = as_pair(w < 3 ? (const char*)ea + (lane & 1) * 16 : (const char*)out + (size_t)node0 * 128 + (lane & 7) * 16, sbase + SM_PAIR + (tid & 127) * 8);
        WS(3);
        const uint32_t dm = ((NPB_MAX + lane) * 4 | (tag << 14)) * 0x10001u;
        const uint32_t db = sbase + SM_DEG - (tag << 14);
        const char* gl = gs + ((tid & 127) >> 2) * (P1B + P2B) + t * 16;
        uint4 rl[5];
        #pragma unroll
        for (int i = 0; i < 5; i++) rl[i].w = ((tid & 127) >> 2) + 32 * i < nb ? 0 : dm;
        auto p2_ld = [&]() {
            mbar_expect(sbase + SM_ABAR + 40, nb * (CE * 4));
            box_ld(sbase + SM_P2, &tm2, P1B / 4 + 64 + b * CE, 0, sbase + SM_ABAR + 40);
        };
        asm volatile("cp.async.bulk.wait_group.read 0;" ::: "memory");
        asm volatile("bar.sync 6, 128;" ::: "memory");
        WSL(12);
        uint32_t spins = 0;
        #pragma unroll 1
        for (int r = 0;; r++) {
            #pragma unroll
            for (int i = 0; i < 5; i++) rl[i].x = rl[i].y = rl[i].z = dm;
            while (true) {
                #pragma unroll
                for (int i = 0; i < 5; i++) ld_unit(rl[i], gl + i * (32 * (P1B + P2B)), (rl[i].w ^ dm) & 0xC000);
                if (spins == 0) asm volatile("bar.sync 5, 512;" ::: "memory");
                if (++spins > (1u << 22)) __trap();
                if (!__any_sync(~0u, ((rl[0].w ^ dm) | (rl[1].w ^ dm) | (rl[2].w ^ dm) | (rl[3].w ^ dm) | (rl[4].w ^ dm)) & 0xC000)) break;
            }
            WS(4);
            uint32_t own = 0;
            #pragma unroll
            for (int i = 0; i < 5; i++) {
                const uint32_t bb = b << 16;
                own |= (min(min(rl[i].x ^ bb, rl[i].y ^ bb), min(rl[i].z ^ bb, rl[i].w ^ bb)) < 0x10000u) << i;
            }
            while (own != 0) {
                uint32_t n; asm volatile("atom.shared.inc.u32 %0, [%1], 0x7fffffff;" : "=r"(n) : "r"(sbase + SM_MISC) : "memory");
                uint4 u = rl[4];
                #pragma unroll
                for (int i = 3; i >= 0; i--) { const bool c = (own >> i) & 1; u.x = sel(c, rl[i].x, u.x); u.y = sel(c, rl[i].y, u.y); u.z = sel(c, rl[i].z, u.z); u.w = sel(c, rl[i].w, u.w); }
                const uint32_t s = (((tid & 127) >> 2) + 32 * (__ffs(own) - 1) << 16) + (4 * r + t << 26);
                own &= own - 1;
                const uint32_t e[4] = {min(u.x ^ (b << 16), dm & 0xFFFF), min(u.y ^ (b << 16), dm & 0xFFFF), min(u.z ^ (b << 16), dm & 0xFFFF), min(u.w ^ (b << 16), dm & 0xFFFF)};
                #pragma unroll
                for (int k = 0; k < 4; k++) asm volatile("red.shared.add.u32 [%0], 1;" :: "r"(db + e[k]) : "memory");
                sts128(sbase + SM_XLIST + min(n, XCAP / 4 - 1) * 16, make_uint4(e[0] + s, e[1] + s + (1 << 24), e[2] + s + (2 << 24), e[3] + s + (3 << 24)));
            }
            __syncwarp();
            if (__builtin_expect(!__any_sync(~0u, t == 3 && min(min(min(rl[0].w, rl[1].w), min(rl[2].w, rl[3].w)), rl[4].w) < 0x1000000u), 1)) break;
            if (r == 3) { misc[1] = 1; break; }
            #pragma unroll
            for (int i = 0; i < 5; i++) rl[i].w = __shfl_sync(~0u, rl[i].w, lane | 3) < 0x1000000u ? 0 : dm;
            gl += 64;
        }
        WS(11); ZS(5);
        asm volatile("bar.sync 7, 512;" ::: "memory");
        auto rest_ld = [&]() {
            if (w == 2 && elect_one()) {
                p2_ld(); x_ld(2);
            }
            __syncwarp();
        };
        WS(9);
        {
            int dg[3], cl[3], cr[3];
            #pragma unroll
            for (int k = 0; k < 3; k++) dg[k] = lds32(sbase + SM_DEG + ((tid & 127) + 128 * k) * 4);
            const int xi = (tid + 96) & 127, nx = lds32(sbase + SM_MISC);
            const uint32_t xe = xlist[xi];
            if (nx > XCAP / 4) sts32(sbase + SM_MISC + 4, 1);
            #pragma unroll
            for (int k = 0; k < 3; k++) {
                cl[k] = NCLS - 1 - (dg[k] <= 40 ? dg[k] : min(41 + ((dg[k] - 41) >> 3), NCLS - 1));
                cr[k] = atoms_inc(sbase + ((tid & 127) + 128 * k < nn ? SM_CLS + cl[k] * 4 : SM_DEG + NPB_MAX * 4));
            }
            rest_ld(); ZS(6);
            asm volatile("bar.sync 6, 128;" ::: "memory");
            WS(13);
            const uint2 c = lds64(sbase + SM_CLS + lane * 8);
            uint32_t inc = c.x + c.y;
            #pragma unroll
            for (int o = 1; o < 32; o <<= 1) { const uint32_t y = __shfl_up_sync(~0u, inc, o); if (lane >= o) inc += y; }
            inc = (inc - c.x - c.y) | (inc - c.y) << 16;
            #pragma unroll
            for (int k = 0; k < 3; k++) {
                const int id = (tid & 127) + 128 * k;
                const uint32_t e = __shfl_sync(~0u, inc, cl[k] >> 1);
                const uint32_t pos = id < nn ? (cl[k] & 1 ? e >> 16 : e & 0xFFFF) + cr[k] : id, nd = id < nn ? id : NONE;
                sts32(sbase + SM_SORT + pos * 4, nd | min(dg[k], 65535) << 16);
                asm volatile("st.shared.u16 [%0], %1;" :: "r"(sbase + SM_WL + pos * 2), "r"(nd) : "memory");
            }
            if (tid == 511) misc[4] = (nn - c.y + 3) >> 2;
            asm volatile("bar.sync 4, 512;" ::: "memory");
            WS(14);
            uint32_t xs = 0x80000000u, xv = tag << 16;
            auto x_get = [&]() { asm volatile("ld.relaxed.gpu.global.u32 %0, [%1];" : "=r"(xv) : "l"(gs + ((xe >> 16) & 0xFF) * (P1B + P2B) + P1B + (xe >> 24) * 4) : "memory"); };
            if (xi < 4 * nx && (xe & 0x3FFF) < NPB_MAX * 4) {
                asm volatile("atom.shared.add.u32 %0, [%1], 4;" : "=r"(xs) : "r"(db + (SM_CNT - SM_DEG) + (xe & 0xFFFF)) : "memory");
                x_get();
            }
            ZS(7);
            tables(smem, sbase, (tid + 32) & 127, ngroups);
            __syncwarp();
            while (__any_sync(~0u, ((xv >> 16) & 3) != tag)) { if (((xv >> 16) & 3) != tag) x_get(); if (++spins > (1u << 22)) __trap(); }
            if (xs < 4 * SLOT_CAP) {
                sts32(sbase + SM_EID + xs, ((xe >> 16) & 0xFF) * ch + (xv >> 19));
                asm volatile("st.shared.u16 [%0], %1;" :: "r"(sbase + SM_SRC + (xs >> 1)), "r"(xv) : "memory");
            }
            mbar_arrive(sbase + SM_XBAR + 24);
            asm volatile("bar.sync 6, 128;" ::: "memory");
        }
        WS(10); ZS(8);
        WGD();
        asm volatile("setmaxnreg.dec.sync.aligned.u32 48;");
        const int r4 = lane >> 3, c8 = lane & 7;
        const uint32_t sb = __reduce_or_sync(~0u, sbase);
        if (w < 3) {
            const char* gx = ga; const char* ge = gb;
            const uint32_t gx0 = (uint32_t)(uint64_t)gx, ge0 = (uint32_t)(uint64_t)ge, hi = (uint64_t)gx >> 32, he = (uint64_t)ge >> 32;
            const int s = (lane >> 1) & 3;
            const uint32_t xs0 = sb + SM_XS + w * NSTAGE * XS_BYTES;
            const uint32_t es0 = sb + SM_ES + w * NSTAGE * ES_BYTES + r4 * 64 + (((lane ^ (r4 >> 1)) & 1) << 4) + (s >> 1) * 256 + (s & 1) * 32;
            const uint32_t bars = sb + SM_BARS + w * 96;
            const uint32_t xoffA = (2 * r4) * 128 + ((c8 ^ (2 * r4)) << 4), xoffB = (2 * r4 + 1) * 128 + ((c8 ^ (2 * r4 + 1)) << 4);
            uint64_t pol;
            asm volatile("createpolicy.fractional.L2::evict_first.b64 %0, 1.0;" : "=l"(pol));
            uint32_t first = 1;
            WS(15);
            uint32_t ph = 1, cur = w;
            uint32_t hist = 96 * 0x010101u;
            auto done3 = [&]() { mbar_arrive(sb + SM_GBAR + ((hist >> 16) & 0xFF) * 8); };
            const uint32_t ca = sb + SM_CLAIM + lane * 4, pa = sb + SM_TINFO + r4 * 8;
            const uint2 p0 = lds64(pa + w * 32);
            const bool go = lds32(sb + SM_MISC + 4) == 0 && nn > 0;
            uint32_t pw = go ? p0.x : 0, brk = (p0.y >> 16) & C_BRK;
            const uint32_t se0 = sb + SM_EID + s * 4, xab = xoffB - xoffA, das = 2 * (xs0 + xoffA) + XS_BYTES, des = 2 * es0 + ES_BYTES, brs = 2 * bars + 48;
            uint32_t da = xs0 + xoffA, de = es0, br = bars;
            #pragma unroll 1
            while (true) {
                const uint32_t pt = __reduce_or_sync(~0u, pw);
                uint32_t se, sx;
                asm("dp2a.lo.u32.u32 %0, %1, 4, %2;" : "=r"(se) : "r"(pw), "r"(se0));
                asm("dp2a.lo.u32.u32 %0, %1, 2, %2;" : "=r"(sx) : "r"(pw), "r"(sb + SM_SRC));
                const int dv = pw >> 27;
                const uint32_t db = da + xab;
                const uint32_t sel = (pt >> 16) & 15, nx = (pt >> 20) & 127;
                uint32_t g;
                auto claim = [&]() { asm volatile("atom.shared.add.u32 %0, [%1], %2;" : "=r"(g) : "r"(ca), "r"(nx == 0 ? 1u : 0u) : "memory"); };
                if (sel == 0) break;
                claim();
                switch (sel) {
#define CASE(L, P, GEN) case L: { \
                        uint32_t oe[(P + 1) / 2], o[P]; \
                        if (first) asm volatile("bar.sync 3, 480;" ::: "memory"); \
                        _Pragma("unroll") for (int j = 0; j < (P + 1) / 2; j++) oe[j] = lds32(se + j * 16); \
                        _Pragma("unroll") for (int j = 0; j < P; j++) o[j] = lds32(sx + j * 4); \
                        mbar_wait_h(br + 8, ph); \
                        _Pragma("unroll") for (int j = 0; j < (P + 1) / 2; j++) \
                            if (LO32) { if (!GEN && 2 * j + 2 < P) cpe<false>(he, de + j * 512, oe[j], ge0, 0, 0, pol); \
                                else if (2 * j + 1 < NPMAX || s < 2) cpe<true>(he, de + j * 512, oe[j], ge0, 4 * j + s, dv, pol); } \
                            else if (!GEN && 2 * j + 2 < P) cp16e(de + j * 512, ge, oe[j], pol); else if (2 * j + 1 < NPMAX || s < 2) cp16z<32>(de + j * 512, ge, oe[j], 4 * j + s, dv, pol); \
                        _Pragma("unroll") for (int j = 0; j < P - 1; j++) { \
                            if (LO32) { cpx<0, GEN>(hi, da + j * 1024, o[j], gx0, 2 * j, dv); cpx<1, GEN>(hi, db + j * 1024, o[j], gx0, 2 * j + 1, dv); } \
                            else if (GEN) { cp16z<128>(da + j * 1024, gx, o[j] & 0xFFFFu, 2 * j, dv, 0); cp16z<128>(db + j * 1024, gx, o[j] >> 16, 2 * j + 1, dv, 0); } \
                            else { cp16i<128>(da + j * 1024, gx, o[j] & 0xFFFFu); cp16i<128>(db + j * 1024, gx, o[j] >> 16); } } \
                        if (LO32) { cpx<0, true>(hi, da + (P - 1) * 1024, o[P - 1], gx0, 2 * P - 2, dv); cpx<1, true>(hi, db + (P - 1) * 1024, o[P - 1], gx0, 2 * P - 1, dv); } \
                        else { cp16z<128>(da + (P - 1) * 1024, gx, o[P - 1] & 0xFFFFu, 2 * P - 2, dv, 0); cp16z<128>(db + (P - 1) * 1024, gx, o[P - 1] >> 16, 2 * P - 1, dv, 0); } \
                    } break;
                    CASE(6, 6, false) CASE(7, 7, false) CASE(8, 8, false) CASE(9, 9, false) CASE(10, 10, false) CASE(11, 11, false)
                    CASE(15, NPMAX, true) CASE(14, 8, true) default: CASE(13, 5, true)
#undef CASE
                }
                first = 0;
                mbar_cp_arrive(br);
                done3();
                g = __reduce_min_sync(~0u, g);
                {
                    const uint2 e = lds64(pa + (nx == 0 ? g : nx) * 32);
                    const uint2 v = tile_info(e.y);
                    pw = e.x;
                    asm volatile("st.shared.v2.u32 [%0], {%1, %2};" :: "r"(br + 16 + r4 * 8), "r"(v.x), "r"((v.y & ~C_BRK) | brk) : "memory");
                    brk = v.y & C_BRK;
                }
                mbar_arrive(br);
                hist = (hist << 8) | (nx == 0 ? cur : 96u);
                cur = nx == 0 ? g : cur;
                ph ^= br != bars; br = brs - br; da = das - da; de = des - de;
            }
            if (first) asm volatile("bar.sync 3, 480;" ::: "memory");
            if (go) {
                mbar_wait(sb + SM_ABAR + 72, 0);
                const int g0 = 3 * max((ngroups + 2) / 3 - TR, 0) + w;
                uint32_t ra[TR], gb[TR]; uint4 xv[TR], xu[TR]; char* po[TR];
                const int gz = misc[4];
                #pragma unroll
                for (int k = 0; k < TR; k++) {
                    uint32_t nd;
                    asm volatile("ld.shared.u16 %0, [%1];" : "=r"(nd) : "r"(sb + SM_WL + (g0 + 3 * k) * 8 + r4 * 2) : "memory");
                    xv[k] = __ldg((const uint4*)(gx + (size_t)(node0 + (nd == NONE ? 0u : nd)) * 128));
                    const uint32_t ro = sb + nd * 128 + ((c8 ^ (nd & 7)) << 4);
                    xu[k] = lds128(ro + SM_XU);
                    const bool some = g0 + 3 * k < gz;
                    ra[k] = some ? ro + SM_TAB : sb + SM_MISC + 64;
                    gb[k] = some ? sb + SM_GBAR + (g0 + 3 * k) * 8 : sb + SM_ABAR + 72;
                    po[k] = nd != NONE ? (char*)out + (size_t)(node0 + nd) * 128 + c8 * 16 : nullptr;
                    asm volatile("" : "+r"(ra[k]), "+r"(gb[k]), "+l"(po[k]));
                }
                #pragma unroll 1
                for (int k = 0; k < 3; k++) {
                    mbar_wait(k < 2 ? br + 8 : sb + SM_ABAR + 48 + w * 8, k < 2 ? ph : 0);
                    done3(); hist <<= 8;
                    ph ^= br != bars; br = brs - br;
                }
                #pragma unroll
                for (int k = 0; k < TR; k++) {
                    mbar_wait_c(gb[k], 0);
                    uint4 a = lds128(ra[k]);
                    finish(a, xu[k], xv[k]);
                    if (po[k]) *(uint4*)po[k] = a;
                }
            }
            cp_wait<0>();
        } else {
            const char* gx = ga; const char* ob = gb;
            mbar_wait(sb + SM_ABAR + 72, 0);
            WS(15); ZS(9);
            if (b == 0 && lane == 0) asm volatile("red.relaxed.gpu.global.add.u32 [%0], 1;" :: "l"(gbar) : "memory");
            const int rounds = misc[1] ? 0 : max((ngroups + 2) / 3 - TR, 0);
            const int gz = misc[4], fast = __reduce_min_sync(~0u, min(rounds, gz / 3));
            uint32_t wl = sb + SM_WL + r4 * 2, gbar = sb + SM_GBAR;
            auto row_at = [&](uint32_t a) { uint32_t n; asm volatile("ld.shared.u16 %0, [%1];" : "=r"(n) : "r"(a) : "memory"); return n; };
            auto fetch = [&](uint32_t n, uint4& v) {
                asm volatile("{\n.reg .b64 p;\nmad.wide.u32 p, %5, 128, %4;\nld.global.nc.L1::no_allocate.v4.u32 {%0,%1,%2,%3}, [p];\n}"
                             : "=r"(v.x), "=r"(v.y), "=r"(v.z), "=r"(v.w) : "l"(gx), "r"(n));
            };
            auto store = [&](uint32_t n, const uint4& a) {
                asm volatile("{\n.reg .b64 p;\nmad.wide.u32 p, %1, 128, %0;\nst.global.v4.u32 [p], {%2,%3,%4,%5};\n}" :: "l"(ob), "r"(n), "r"(a.x), "r"(a.y), "r"(a.z), "r"(a.w) : "memory");
            };
            uint32_t n0[3]; uint4 x0[3];
            if (fast) {
                #pragma unroll
                for (int r = 0; r < 3; r++) { n0[r] = row_at(wl + r * 8); fetch(n0[r], x0[r]); }
            }
            #pragma unroll 1
            for (int k = 0; k < fast; k++) {
                wl += 24;
                #pragma unroll
                for (int r = 0; r < 3; r++) {
                    const uint32_t nd = n0[r], ro = sb + nd * 128 + ((c8 ^ (nd & 7)) << 4);
                    const uint4 xu = lds128(ro + SM_XU);
                    n0[r] = row_at(wl + r * 8);
                    mbar_wait(gbar + r * 8, 0);
                    uint4 a = lds128(ro + SM_TAB);
                    finish(a, xu, x0[r]);
                    fetch(n0[r], x0[r]);
                    store(nd, a);
                }
                gbar += 24;
            }
            #pragma unroll 1
            for (int g = 3 * fast; g < 3 * rounds; g++) {
                const uint32_t nd = row_at(sb + SM_WL + r4 * 2 + g * 8), ro = sb + nd * 128 + ((c8 ^ (nd & 7)) << 4);
                uint4 xv, a = make_uint4(0, 0, 0, 0);
                fetch(nd, xv);
                if (g < gz) { mbar_wait(sb + SM_GBAR + g * 8, 0); a = lds128(ro + SM_TAB); }
                finish(a, lds128(ro + SM_XU), xv);
                store(nd, a);
            }
        }
    } else {
        asm volatile("setmaxnreg.inc.sync.aligned.u32 152;");
        float4 lgh[2 * NPMAX];
        uint32_t wf[40], wn[16], wt[16];
        const uint32_t mo0 = sbase + SM_TAB + (8 * (lane >> 4) + (lane & 7)) * 128 + (((2 * w + ((lane >> 3) & 1)) ^ (lane & 7)) << 4);
        mbar_wait_c(sbase + SM_ABAR + 24, 0);
        {
            const uint32_t wo = sbase + SM_WR + (2 * t) * 128 + ((ch0 * 2) ^ (t * 32));
            #pragma unroll
            for (int ks = 0; ks < 9; ks++) {
                uint32_t wr[4];
                #pragma unroll
                for (int i = 0; i < 4; i++) wr[i] = lds32((wo ^ ((i & 1) * 16)) + (16 * ks + (i & 1) + 4 * (i & 2)) * 128);
                if (ks < 5) make_wfrag<true>(wf + 4 * ks, wr); else make_wfrag<false>(wf + 4 * ks, wr);
            }
            #pragma unroll
            for (int ks = 0; ks < 4; ks++) { ldsm4t(wn + 4 * ks, mo0 + (144 + 16 * ks) * 128); ldsm4t(wt + 4 * ks, mo0 + (208 + 16 * ks) * 128); }
            if (wg == 2) {
                const uint32_t a = sbase + SM_WC + (16 * w + q) * 32 + t * 4, sw = (q >> 2) << 4;
                sts32(a + sw, wf[16]); sts32(a + 256 + sw, wf[17]); sts32(a + (sw ^ 16), wf[18]); sts32(a + 256 + (sw ^ 16), wf[19]);
                asm volatile("fence.proxy.async.shared::cta;" ::: "memory");
            }
            #pragma unroll
            for (int i = 0; i < 36; i++) asm volatile("" : "+r"(wf[i]));
        }
        WS(9);
        constexpr int NU = 6;
        const uint32_t dm = ((NPB_MAX + lane) * 4 | (tag << 14)) * 0x10001u;
        const char* const g1 = gs + (tid >> 4) * (P1B + P2B) + 256 + b * (CE * 2) + (lane & 15) * 8;
        const bool last = 2 * warp + 24 * (NU - 1) < nb;
        uint2 r1[NU];
        #pragma unroll
        for (int i = 0; i < NU; i++) r1[i] = make_uint2(dm, (tid >> 4) + 24 * i < nb ? 0 : dm);
        uint32_t spins = 0;
        asm volatile("bar.sync 5, 512;" ::: "memory");
        while (true) {
            #pragma unroll
            for (int i = 0; i < NU; i++) ld_unit(r1[i], g1 + i * (24 * (P1B + P2B)), (r1[i].y ^ dm) & 0xC000);
            #pragma unroll
            for (int i = 0; i < 4; i++) sts128(mo0 + wg * 16384 + 8192 + i * 2048, make_uint4(wt[4*i], wt[4*i+1], wt[4*i+2], wt[4*i+3]));
            uint32_t bad = 0;
            #pragma unroll
            for (int i = 0; i < NU; i++) bad |= r1[i].y ^ dm;
            const bool more = __any_sync(~0u, bad & 0xC000);
            if (spins == 0) WS(2);
            if (!more) break;
            if (++spins > (1u << 22)) __trap();
        }
        WS(3);
        const uint32_t db = sbase + SM_DEG - (tag << 14);
        uint32_t rk[NU][4];
        #pragma unroll
        for (int i = 0; i < NU; i++) {
            #pragma unroll
            for (int k = 0; k < 4; k++) {
                asm("dp2a.lo.u32.u32 %0, %1, %2, %3;" : "=r"(rk[i][k]) : "r"(k < 2 ? r1[i].x : r1[i].y), "r"(k & 1 ? 0x100u : 1u), "r"(db));
                if (i < NU - 1 || last) asm volatile("red.shared.add.u32 [%0], 1;" :: "r"(rk[i][k]) : "memory");
            }
        }
        WS(10);
        asm volatile("bar.sync 7, 512;" ::: "memory");
        WS(11);
        {
            const uint32_t ev = (lds32(sbase + SM_DEG + tid * 4) + 1) & ~1u;
            uint32_t inc = ev, base = 0;
            #pragma unroll
            for (int o = 1; o < 32; o <<= 1) { const uint32_t y = __shfl_up_sync(~0u, inc, o); if (lane >= o) inc += y; }
            if (lane == 31) {
                asm volatile("atom.shared.add.u32 %0, [%1], %2;" : "=r"(base) : "r"(sbase + SM_MISC + 24), "r"(inc) : "memory");
                if (base + inc > SLOT_CAP) misc[1] = 1;
            }
            const uint32_t s0 = min(__shfl_sync(~0u, base, 31) + inc - ev, SLOT_CAP);
            sts32(sbase + SM_CNT + tid * 4, 4 * s0);
            asm volatile("st.shared.u16 [%0], %1;" :: "r"(sbase + SM_BASE + tid * 2), "r"(s0) : "memory");
        }
        asm volatile("bar.arrive 4, 512;" ::: "memory");
        asm volatile("bar.sync 1, 384;" ::: "memory");
        WS(13);
        #pragma unroll
        for (int i = 0; i < NU; i++) {
            if (i < NU - 1 || last) {
                #pragma unroll
                for (int k = 0; k < 4; k++) asm volatile("atom.shared.add.u32 %0, [%0+%1], 4;" : "+r"(rk[i][k]) : "n"(SM_CNT - SM_DEG) : "memory");
            }
        }
        WS(14);
        uint4 r2[NU];
        mbar_wait_c(sbase + SM_ABAR + 40, 0);
        WS(4);
        #pragma unroll
        for (int i = 0; i < NU; i++) r2[i] = lds128(sbase + SM_P2 + (i < NU - 1 ? tid + 384 * i : min(tid + 384 * i, P2B / 16 - 1)) * 16);
        while (true) {
            uint32_t bad = 0;
            #pragma unroll
            for (int i = 0; i < NU; i++) if (i < NU - 1 || last) bad |= (r2[i].x ^ (tag << 16)) & ~(rk[i][0] >> 14);
            if (__builtin_expect(!__any_sync(~0u, bad & 0x30000), 1)) break;
            #pragma unroll
            for (int i = 0; i < NU; i++)
                ld_unit(r2[i], g1 + (P1B + b * (CE * 2) + (lane & 15) * 8 + i * (24 * (P1B + P2B))), (i < NU - 1 || last) && ((r2[i].x ^ (tag << 16)) & ~(rk[i][0] >> 14) & 0x30000));
            if (++spins > (1u << 22)) __trap();
        }
        WS(16);
        const uint32_t sbu = __reduce_or_sync(~0u, sbase);
        auto place = [&](uint32_t s4, uint32_t v, uint32_t eb) {
            asm volatile("{\n.reg .pred p;\nsetp.lt.u32 p, %0, %5;\n@p st.shared.u32 [%1], %2;\n@p st.shared.u16 [%3], %4;\n}"
                         :: "r"(s4), "r"(sbu + SM_EID + s4), "r"(eb + (v >> 19)), "r"(sbu + SM_SRC + (s4 >> 1)), "r"(v), "n"(4 * SLOT_CAP) : "memory");
        };
        #pragma unroll
        for (int i = 0; i < NU; i++) {
            const uint32_t eb = ((tid >> 4) + 24 * i) * ch;
            if (i == 2 && warp == 10 && elect_one()) { x_ld(1); x_ld(0); }
            if (i < NU - 1 || last) { place(rk[i][0], r2[i].x, eb); place(rk[i][1], r2[i].y, eb); place(rk[i][2], r2[i].z, eb); place(rk[i][3], r2[i].w, eb); }
        }
        WS(1);
        WGD();
        asm volatile("bar.arrive 3, 480;" ::: "memory");
        {
        int lane;
        asm volatile("mov.u32 %0, %%laneid;" : "=r"(lane));
        const int q = lane >> 2, t = lane & 3, ch0 = 16 * w + 2 * q;
        const uint32_t sbase = sbu;
        { const uint2 z = lds64(sbase + SM_OH + 8); wf[37] = z.x; wf[38] = z.y; }
        const uint32_t c2 = __shfl_sync(~0u, ch0 * 2, lane), t8 = __shfl_sync(~0u, t * 8, lane);
        float g[4 * NPMAX], h[4 * NPMAX];
        float4 cyr = make_float4(0.f, 0.f, 0.f, 0.f);
        {
            const uint32_t mo = sbase + (8 * (lane >> 4) + (lane & 7)) * 128 + (((2 * w + ((lane >> 3) & 1)) ^ (lane & 7)) << 4);
            mbar_wait_c(sbase + SM_XBAR + wg * 8, 0);
            WSP(4);
            node_mma2(g, h, wn, desc_sw128(sbase + SM_XU + wg * 16384));
            TileMMA<8>::wait_g(g);
            node_rows(mo + SM_TAB + wg * 16384, g);
            TileMMA<8>::wait_h(h);
            WSP(5);
            #pragma unroll
            for (int i = 0; i < 4; i++) {
                const uint4 f = lds128(mo + SM_TAB + wg * 16384 + 8192 + i * 2048);
                wn[4*i] = f.x; wn[4*i+1] = f.y; wn[4*i+2] = f.z; wn[4*i+3] = f.w;
            }
            __syncwarp();
            node_rows(mo + SM_TAB + wg * 16384 + 8192, h);
            mbar_arrive(sbase + SM_XBAR + 24);
            WSP(2);
            node_mma2(g, h, wn, desc_sw128(sbase + SM_XU + wg * 16384));
            TileMMA<8>::wait_g(g);
            asm volatile("bar.sync %0, 128;" :: "r"(8 + wg) : "memory");
            node_rows(mo + SM_XU + wg * 16384, g);
            TileMMA<8>::wait_h(h);
            WSP(3);
            asm volatile("bar.sync %0, 128;" :: "r"(8 + wg) : "memory");
            node_rows(mo + SM_XU + wg * 16384 + 8192, h);
            mbar_arrive(sbase + SM_ABAR + 72);
            mbar_wait_c(sbase + SM_XBAR + 24, 0);
            if (__builtin_expect(lds32(sbase + SM_MISC + 4) != 0, 0)) { slow_bin(x, ea, src, dst, wa, wb, wc, wu, wv, out, E, node0, nn, 384); return; }
            WS(6);
        }
        const uint64_t wcd = __reduce_or_sync(~0u, (((sbase + SM_WC) & 0x3FFFF) >> 4) | (8u << 16)) | EDHI;
        const uint32_t bar0 = __reduce_or_sync(~0u, sbase + SM_BARS + wg * 96);
        const uint32_t xd0 = __reduce_or_sync(~0u, (((sbase + SM_XS + wg * NSTAGE * XS_BYTES) & 0x3FFFF) >> 4) | (1u << 16));
        const uint32_t ed0 = __reduce_or_sync(~0u, (((sbase + SM_ES + wg * NSTAGE * ES_BYTES) & 0x3FFFF) >> 4) | (8u << 16));
        const uint64_t ohd = __reduce_or_sync(~0u, (((sbase + SM_OH) & 0x3FFFF) >> 4) | (8u << 16));
        const uint32_t tabx = __reduce_or_sync(~0u, sbase + SM_TAB);
        const uint32_t bars = __reduce_or_sync(~0u, 2 * bar0 + 48), xds = __reduce_or_sync(~0u, 2 * xd0 + XS_BYTES / 16), eds = __reduce_or_sync(~0u, 2 * ed0 + ES_BYTES / 16);
        uint32_t bar = bar0, xd = xd0, ed = ed0, ph = 0, code, w1, ta, pta = NONE * 128 + c2;
        float pn0 = 0.f, pd0 = 1.f, pn1 = 0.f, pd1 = 1.f;
        uint2 ni = tile_info(lds32(sbase + SM_TINFO + wg * 32 + t * 8 + 4));
        auto fetch_a = [&]() {
            ta = (ni.x & 0xFFFFu) ^ c2;
            wf[36] = lds32(tabx + ta); wf[39] = lds32(tabx + ta);
            code = __reduce_or_sync(~0u, ni.y);
        };
        auto emit = [&]() { sts32(tabx + pta, pack_bf16(pn0 * rcpf(pd0), pn1 * rcpf(pd1))); };
        auto carry = [&]() {
            if (w1 & C_CONT) { pn0 += cyr.x; pd0 += cyr.y; pn1 += cyr.z; pd1 += cyr.w; }
            if (w1 & C_MORE) { cyr = make_float4(pn0, pd0 - EPS2, pn1, pd1 - EPS2); pn0 = pn1 = 0.f; pta = NONE * 128 + c2; }
        };
        auto next = [&](uint32_t fb) {
            pta = ta;
            w1 = ni.y;
            ni = lds64(fb + 16 + t8);
        };
        fetch_a();
        while (true) {
            switch (code & 15) {
                default: goto finished;
#define TILE(P) { \
                    float dmin; \
                    do { \
                        mbar_wait_c(bar, ph); \
                        TileMMA<P>::issue(g, h, wf, xd | (0x40000040ull << 32), ed | EDHI, ohd, wcd); \
                        const uint32_t eb = bar + 8; \
                        ph ^= bar != bar0; bar = bars - bar; xd = xds - xd; ed = eds - ed; \
                          \
                        asm volatile("{\n.reg .pred p;\nsetp.eq.u32 p, %0, 77;\n@p trap;\n}" :: "r"(xds) : "memory"); \
                        emit(); next(eb - 8); \
                        TileMMA<P>::wait_g(g); fetch_a(); TileMMA<P>::wait_h(h); \
                        mbar_arrive(eb); \
                        float m1; \
                        asm("set.gt.f32.f32 %0, %1, 0f0000007F;" : "=f"(m1) : "f"(__uint_as_float(w1))); \
                        epi_fast<P>(g, h, m1, __uint_as_float(w1), pn0, pd0, pn1, pd1, dmin); \
                    } while (!(__any_sync(~0u, dmin < TAU * 2 * P + 2 * rem_of(P)) | ((code & 31) != P))); \
                    if (__builtin_expect(__any_sync(~0u, (int)w1 < 0 || dmin < TAU * 2 * P + 2 * rem_of(P)), 0)) { \
                        int dv; \
                        const bool bad = unpad(w1, P, g[4 * P - 7], g[4 * P - 5], pd0, pd1, dv); \
                        const uint32_t nb_ = __reduce_add_sync(~0u, bad ? 256 + dv : 0); \
                        if (nb_) { \
                            FBT(2); \
                            const uint32_t spare = tabx + (NPB_MAX - 3) * 128; \
                            uint32_t taken = 1; \
                            if (nb_ < 512) { \
                                asm volatile("atom.shared.or.b32 %0, [%1], %2;" : "=r"(taken) : "r"(spare + LOCK_OFF + (bad ? 0 : 4)), "r"(bad ? 1 : 0) : "memory"); \
                                taken = __reduce_or_sync(~0u, taken); \
                            } \
                            float4 r; \
                            if (!taken) { \
                                if (bad) { _Pragma("unroll") for (int i = 0; i < P; i++) { \
                                    sts128(spare + i * 16, make_uint4(__float_as_uint(g[4*i]), __float_as_uint(g[4*i+1]), __float_as_uint(g[4*i+2]), __float_as_uint(g[4*i+3]))); \
                                    sts128(spare + (NPMAX + i) * 16, make_uint4(__float_as_uint(h[4*i]), __float_as_uint(h[4*i+1]), __float_as_uint(h[4*i+2]), __float_as_uint(h[4*i+3]))); } } \
                                FBT(3); \
                                r = epi_single(spare, nb_ - 256); \
                            } else { \
                                epi_dump<P>(g, h, lgh); \
                                FBT(3); \
                                r = epi_exact(lgh, P, dv); \
                            } \
                            if (bad) { pn0 = r.x; pd0 = r.y; pn1 = r.z; pd1 = r.w; } \
                            if (pd0 != 77.f) FBT(4); \
                        } \
                    } \
                    if (code & C_BRK) { carry(); if (P != 11 && (code & 15) == P) goto L##P; } \
                    if (P == 11) {         \
                        const uint32_t a = tabx + (SM_WC - SM_TAB) + (c2 & 0x60) * 16 + (c2 & 0x1C) * 8 + (t8 >> 1), sw = c2 & 16; \
                        wf[16] = lds32(a + sw); wf[17] = lds32(a + 256 + sw); wf[18] = lds32(a + (sw ^ 16)); wf[19] = lds32(a + 256 + (sw ^ 16)); \
                    } }
#define CASE(P, UP, DN) case P: L##P: TILE(P) \
                    if (P > NPMIN && (code & 15) == P - 1) goto L##DN; \
                    if (P <= 6 && (code & 15) == 0) goto finished; \
                    if ((code & 15) == UP) goto L##UP; \
                    break;
                CASE(11, 11, 10) CASE(10, 11, 9) CASE(9, 10, 8) CASE(8, 9, 7) CASE(7, 8, 6) CASE(6, 7, 5) CASE(5, 6, 4) CASE(4, 5, 4)
#undef CASE
#undef TILE
            }
        }
finished:
        emit();
        mbar_arrive(sbase + SM_ABAR + 48 + wg * 8);
        }
    }
    WS(17); WG1();
}

}

extern "C" void kernel_launch(void* const* d_in, const int* in_sizes, int n_in, void* d_out, int out_size) {
    const __nv_bfloat16* x = (const __nv_bfloat16*)d_in[0];
    const __nv_bfloat16* ea = (const __nv_bfloat16*)d_in[1];
    const int* src = (const int*)d_in[2];
    const int* dst = (const int*)d_in[3];
    const __nv_bfloat16* wa = (const __nv_bfloat16*)d_in[4];
    const __nv_bfloat16* wb = (const __nv_bfloat16*)d_in[5];
    const __nv_bfloat16* wc = (const __nv_bfloat16*)d_in[6];
    const __nv_bfloat16* wu = (const __nv_bfloat16*)d_in[7];
    const __nv_bfloat16* wv = (const __nv_bfloat16*)d_in[8];
    __nv_bfloat16* out = (__nv_bfloat16*)d_out;
    int N = in_sizes[0] / 64, E = in_sizes[2];
    static int sms = 0;
    static CUtensorMap tm2;
    static bool tm_ok = false;
    typedef CUresult (*EncFn)(CUtensorMap*, CUtensorMapDataType, cuuint32_t, void*, const cuuint64_t*, const cuuint64_t*, const cuuint32_t*,
                              const cuuint32_t*, CUtensorMapInterleave, CUtensorMapSwizzle, CUtensorMapL2promotion, CUtensorMapFloatOOBfill);
    static void* fn = nullptr;
    static void* gp = nullptr; static void* gb = nullptr;
    if (!sms) {
        cudaDeviceGetAttribute(&sms, cudaDevAttrMultiProcessorCount, 0);
        cudaDriverEntryPointQueryResult qr;
        cudaGetDriverEntryPoint("cuTensorMapEncodeTiled", &fn, cudaEnableDefault, &qr);
        cudaGetSymbolAddress(&gp, g_str); cudaGetSymbolAddress(&gb, g_bar);
        if (fn && gp && gb) {
            const cuuint32_t rows = sms < NB_MAX ? sms : NB_MAX;
            cuuint64_t g2[2] = {(P1B + P2B) / 4, NB_MAX}, gs[1] = {P1B + P2B};
            cuuint32_t b2[2] = {CE, rows}, es[2] = {1, 1};
            tm_ok = ((EncFn)fn)(&tm2, CU_TENSOR_MAP_DATA_TYPE_UINT32, 2, gp, g2, gs, b2, es, CU_TENSOR_MAP_INTERLEAVE_NONE, CU_TENSOR_MAP_SWIZZLE_NONE,
                                CU_TENSOR_MAP_L2_PROMOTION_NONE, CU_TENSOR_MAP_FLOAT_OOB_FILL_NONE) == CUDA_SUCCESS;
        }
        cudaFuncSetAttribute(gcn_kernel<true>, cudaFuncAttributeMaxDynamicSharedMemorySize, SMEM_LAUNCH);
        cudaFuncSetAttribute(gcn_kernel<false>, cudaFuncAttributeMaxDynamicSharedMemorySize, SMEM_LAUNCH);
    }
    auto rows = [&](CUtensorMap* tm, const void* base, uint64_t n, uint32_t box) {
        cuuint64_t gd[2] = {64, n}, gs[1] = {128};
        cuuint32_t bx[2] = {64, box}, es[2] = {1, 1};
        return ((EncFn)fn)(tm, CU_TENSOR_MAP_DATA_TYPE_BFLOAT16, 2, (void*)base, gd, gs, bx, es, CU_TENSOR_MAP_INTERLEAVE_NONE, CU_TENSOR_MAP_SWIZZLE_128B,
                           CU_TENSOR_MAP_L2_PROMOTION_NONE, CU_TENSOR_MAP_FLOAT_OOB_FILL_NONE) == CUDA_SUCCESS;
    };
    const uintptr_t wp[4] = {(uintptr_t)wa, (uintptr_t)wb, (uintptr_t)wu, (uintptr_t)wv};
    uintptr_t w0 = wp[0], w1 = wp[0], wal = 0;
    for (int i = 1; i < 4; i++) { w0 = wp[i] < w0 ? wp[i] : w0; w1 = wp[i] > w1 ? wp[i] : w1; wal |= wp[i] - wp[0]; }
    int4 wrow = make_int4((int)((wp[0] - w0) >> 7), (int)((wp[1] - w0) >> 7), (int)((wp[2] - w0) >> 7), (int)((wp[3] - w0) >> 7));
    CUtensorMap tmw, tmc, tmx;
    const bool maps = tm_ok && N > 0 && !(wal & 127) && ((w1 - w0) >> 7) < (1u << 30) && rows(&tmw, (void*)w0, ((w1 - w0) >> 7) + 64, 64) && rows(&tmc, wc, 16, 16) && rows(&tmx, x, N, 128);
    int nb = sms < NB_MAX ? sms : NB_MAX;
    int npb = (N + nb - 1) / nb;
    int ch = (((E + nb - 1) / nb) + 3) & ~3;
    if (!maps || npb > NPB_MAX || ch > CH_MAX || (E & 3) || N > 65535 || npb < 2 || (((uintptr_t)src | (uintptr_t)dst | (uintptr_t)wa | (uintptr_t)wb | (uintptr_t)wc | (uintptr_t)wu | (uintptr_t)wv) & 15)) {
        int g = 1024, p = (N + g - 1) / g;
        slow_kernel<<<g, 256>>>(x, ea, src, dst, wa, wb, wc, wu, wv, out, N, E, p < 1 ? 1 : p);
        return;
    }
    uint32_t magic = (uint32_t)((1ull << 32) / (uint32_t)npb) + 1u;
    void* args[] = {&dst, &gb, &gp, &src, &E, &ch, &N, &npb, &magic, &x, &ea, &wa, &wb, &wc, &wu, &wv, &out, &wrow, &tm2, &tmw, &tmc, &tmx};
    const bool lo32 = ((uintptr_t)x >> 32) == (((uintptr_t)x + (size_t)N * 128 - 1) >> 32) && ((uintptr_t)ea >> 32) == (((uintptr_t)ea + (size_t)E * 32 - 1) >> 32);
    cudaLaunchCooperativeKernel(lo32 && !FORCE64 ? (const void*)gcn_kernel<true> : (const void*)gcn_kernel<false>, dim3(nb), dim3(THREADS), args, SMEM_LAUNCH, cudaStreamPerThread);
}
```
